```python
import torch

def _softmax(x, axis=-1):
    return torch.softmax(x, dim=axis)
def _gelu(x):
    return torch.nn.functional.gelu(x, approximate="tanh")
def _silu(x):
    return torch.nn.functional.silu(x)
def _sigmoid(x):
    return torch.sigmoid(x)
def _layernorm(x, axis=-1, eps=1e-5):
    m = x.mean(dim=axis, keepdim=True)
    v = x.var(dim=axis, keepdim=True, unbiased=False)
    return (x - m) / torch.sqrt(v + eps)
def _scatter_add(tgt, idx, src, axis=0):
    return tgt.clone().index_add_(axis, idx, src)
def _segment_sum(src, seg, n):
    out = torch.zeros((n,) + src.shape[1:], dtype=src.dtype)
    return out.index_add_(0, seg, src)
def _pad(x, pw):
    flat = tuple(v for pair in reversed(pw) for v in pair)
    return torch.nn.functional.pad(x, flat)

kernel_name = 'sequential_preLN__softmax_full_mha__moe_arch_mod__prompt'

def setup_inputs():

    _w = (lambda a: (lambda t: t.to(torch.bfloat16) if t.is_floating_point() else t)(torch.as_tensor(a)))
    def _A_setup():
        B, S, D = 1, 2048, 512
        return {
            "x": _w((lambda *s: torch.randn(*s, dtype=torch.bfloat16) * 0.05)(B, S, D)),
            "wqkv": _w((lambda *s: torch.randn(*s, dtype=torch.bfloat16) * 0.05)(D, 3 * D)),
            "wo": _w((lambda *s: torch.randn(*s, dtype=torch.bfloat16) * 0.05)(D, D)),
        }
    _A_in = _A_setup()

    def _B_setup():
        B, S, D, F, C = 1, 2048, 512, 1792, 2
        return {
            "x": _w((lambda *s: torch.randn(*s, dtype=torch.bfloat16) * 0.05)(B, S, D)),
            "w_r": _w((lambda *s: torch.randn(*s, dtype=torch.bfloat16) * 0.05)(D)),
            "w_gate": _w((lambda *s: torch.randn(*s, dtype=torch.bfloat16) * 0.05)(D, F)),
            "w_up": _w((lambda *s: torch.randn(*s, dtype=torch.bfloat16) * 0.05)(D, F)),
            "w_down": _w((lambda *s: torch.randn(*s, dtype=torch.bfloat16) * 0.05)(F, D)),
        }
    _B_in = _B_setup()

    return {
        "A_x": _A_in["x"],
        "A_wqkv": _A_in["wqkv"],
        "A_wo": _A_in["wo"],
        "B_x": _B_in["x"],
        "B_w_r": _B_in["w_r"],
        "B_w_gate": _B_in["w_gate"],
        "B_w_up": _B_in["w_up"],
        "B_w_down": _B_in["w_down"],
    }

def reference(A_x, A_wqkv, A_wo, B_x, B_w_r, B_w_gate, B_w_up, B_w_down):
    def _A_ref(x, wqkv, wo):
        B, S, D = x.shape
        H = 32; Dh = D // H
        qkv = (lambda x, *d: x.permute(*d))((x @ wqkv).reshape(B, S, 3, H, Dh), 2, 0, 3, 1, 4)
        q, k, v = qkv[0], qkv[1], qkv[2]
        scale = Dh ** -0.5
        scores = torch.einsum("bhqd,bhkd->bhqk", q, k) * scale
        p = _softmax(scores, axis=-1)
        o = torch.einsum("bhqk,bhkd->bhqd", p, v)
        return (lambda x, *d: x.permute(*d))(o, 0, 2, 1, 3).reshape(B, S, D) @ wo

    def _B_ref(x, w_r, w_gate, w_up, w_down):
        B, S, D = x.shape
        C = 2
        r = x @ w_r
        idx = torch.argsort(-r, axis=-1)[:, :C]
        idx_e = (lambda x, n, axis: torch.repeat_interleave(x, n, dim=axis))(idx.reshape(B, C, 1), D, axis=2)
        x_sel = (lambda x, i, axis: torch.take_along_dim(x, i, dim=axis))(x, idx_e, axis=1)
        g = _silu(x_sel @ w_gate)
        u = x_sel @ w_up
        y = (g * u) @ w_down
        r_sel = _sigmoid((lambda x, i, axis: torch.take_along_dim(x, i, dim=axis))(r, idx, axis=1))
        y = y * r_sel.reshape(B, C, 1)
        b_off = (torch.arange(B) * S).reshape(B, 1)
        flat_idx = (idx + b_off).reshape(B * C)
        zero = (x * 0.0).reshape(B * S, D)
        upd = _scatter_add(zero, flat_idx, y.reshape(B * C, D), axis=0)
        return x + upd.reshape(B, S, D)

    x = A_x
    h = x + _A_ref(_layernorm(x, axis=-1), A_wqkv, A_wo)
    h2 = h + _B_ref(_layernorm(h, axis=-1), B_w_r, B_w_gate, B_w_up, B_w_down)
    return h2
```

```cpp
#include <cuda_runtime.h>
#include <cuda_bf16.h>
#include <cuda.h>
#include <stdint.h>

namespace {

constexpr int SEQ = 2048, DM = 512, NH = 32, FF = 1792;

__device__ __align__(1024) uint8_t g_q[NH * 2 * SEQ * 16];
__device__ __align__(1024) uint8_t g_kv[NH * 8 * 16384];
__device__ float g_norm[16 * NH * 3];
__device__ __align__(1024) __nv_bfloat16 g_o[SEQ * DM];
__device__ __align__(1024) __nv_bfloat16 g_h[SEQ * DM];
__device__ float2 g_stat[SEQ];
__device__ unsigned long long g_cand[64];
__device__ __align__(16) float g_y[2 * DM];
__device__ unsigned int g_cnt;

__device__ __forceinline__ uint32_t smem_u32(const void* p) { return (uint32_t)__cvta_generic_to_shared(p); }
__device__ __forceinline__ void wg_fence() { asm volatile("wgmma.fence.sync.aligned;" ::: "memory"); }
__device__ __forceinline__ void wg_commit() { asm volatile("wgmma.commit_group.sync.aligned;" ::: "memory"); }
template <int N> __device__ __forceinline__ void wg_wait() { asm volatile("wgmma.wait_group.sync.aligned %0;" ::"n"(N) : "memory"); }
template <int N> __device__ __forceinline__ void fence_regs(float (&r)[N]) {
#pragma unroll
    for (int i = 0; i < N; i++) asm volatile("" : "+f"(r[i])::"memory");
}
__device__ __forceinline__ uint64_t make_desc(uint32_t addr, uint32_t lbo, uint32_t sbo, uint32_t swz) {
    uint64_t d = 0;
    d |= (uint64_t)((addr & 0x3FFFF) >> 4);
    d |= (uint64_t)((lbo & 0x3FFFF) >> 4) << 16;
    d |= (uint64_t)((sbo & 0x3FFFF) >> 4) << 32;
    d |= (uint64_t)swz << 62;
    return d;
}
__device__ __forceinline__ void mbar_init(uint32_t bar, uint32_t cnt) {
    asm volatile("mbarrier.init.shared::cta.b64 [%0], %1;" ::"r"(bar), "r"(cnt) : "memory");
}
__device__ __forceinline__ void mbar_expect_tx(uint32_t bar, uint32_t bytes) {
    asm volatile("mbarrier.arrive.expect_tx.shared::cta.b64 _, [%0], %1;" ::"r"(bar), "r"(bytes) : "memory");
}
__device__ __forceinline__ void mbar_arrive(uint32_t bar) {
    asm volatile("mbarrier.arrive.shared::cta.b64 _, [%0];" ::"r"(bar) : "memory");
}
__device__ __forceinline__ void mbar_wait(uint32_t bar, uint32_t parity) {
    asm volatile(
        "{\n.reg .pred p;\nWAIT_%=:\n"
        "mbarrier.try_wait.parity.shared::cta.b64 p, [%0], %1;\n"
        "@p bra DONE_%=;\nbra WAIT_%=;\nDONE_%=:\n}\n" ::"r"(bar), "r"(parity) : "memory");
}
__device__ __forceinline__ void bulk_g2s(uint32_t dst, const void* src, uint32_t bytes, uint32_t bar) {
    asm volatile("cp.async.bulk.shared::cluster.global.mbarrier::complete_tx::bytes [%0], [%1], %2, [%3];" ::"r"(dst),
                 "l"(src), "r"(bytes), "r"(bar) : "memory");
}
__device__ __forceinline__ void bulk_s2g(void* dst, uint32_t src, uint32_t bytes) {
    asm volatile("cp.async.bulk.global.shared::cta.bulk_group [%0], [%1], %2;" ::"l"(dst), "r"(src), "r"(bytes) : "memory");
}
__device__ __forceinline__ void tma_load_2d(uint32_t dst, const CUtensorMap* tm, int c0, int c1, uint32_t bar) {
    asm volatile("cp.async.bulk.tensor.2d.shared::cluster.global.mbarrier::complete_tx::bytes [%0], [%1, {%3, %4}], [%2];" ::"r"(dst),
                 "l"(tm), "r"(bar), "r"(c0), "r"(c1) : "memory");
}
__device__ __forceinline__ void fence_proxy_async() { asm volatile("fence.proxy.async.shared::cta;" ::: "memory"); }
__device__ __forceinline__ void fence_barrier_init() { asm volatile("fence.mbarrier_init.release.cluster;" ::: "memory"); }
__device__ __forceinline__ void pdl_launch() { asm volatile("griddepcontrol.launch_dependents;" ::: "memory"); }
__device__ __forceinline__ void pdl_wait() { asm volatile("griddepcontrol.wait;" ::: "memory"); }
__device__ __forceinline__ void named_sync(int id, int n) { asm volatile("bar.sync %0, %1;" ::"r"(id), "r"(n) : "memory"); }
__device__ __forceinline__ void named_arrive(int id, int n) { asm volatile("bar.arrive %0, %1;" ::"r"(id), "r"(n) : "memory"); }

__device__ __forceinline__ float ex2f(float x) { float y; asm("ex2.approx.ftz.f32 %0, %1;" : "=f"(y) : "f"(x)); return y; }
__device__ __forceinline__ uint32_t pack_bf16(float lo, float hi) {
    uint32_t r; asm("cvt.rn.bf16x2.f32 %0, %1, %2;" : "=r"(r) : "f"(hi), "f"(lo)); return r;
}
__device__ __forceinline__ float bf_lo(uint32_t v) { return __uint_as_float(v << 16); }
__device__ __forceinline__ float bf_hi(uint32_t v) { return __uint_as_float(v & 0xFFFF0000u); }
__device__ __forceinline__ float rbf(float x) { return __bfloat162float(__float2bfloat16_rn(x)); }
__device__ __forceinline__ uint32_t fma_bf16x2(uint32_t a, uint32_t b, uint32_t c) {
    uint32_t r; asm("fma.rn.bf16x2 %0, %1, %2, %3;" : "=r"(r) : "r"(a), "r"(b), "r"(c)); return r;
}
__device__ __forceinline__ void stmatrix_x4(uint32_t addr, uint32_t r0, uint32_t r1, uint32_t r2, uint32_t r3) {
    asm volatile("stmatrix.sync.aligned.m8n8.x4.shared.b16 [%0], {%1, %2, %3, %4};" ::"r"(addr), "r"(r0), "r"(r1), "r"(r2), "r"(r3) : "memory");
}
__device__ __forceinline__ void stmatrix_x4_trans(uint32_t addr, uint32_t r0, uint32_t r1, uint32_t r2, uint32_t r3) {
    asm volatile("stmatrix.sync.aligned.m8n8.x4.trans.shared.b16 [%0], {%1, %2, %3, %4};" ::"r"(addr), "r"(r0), "r"(r1), "r"(r2), "r"(r3) : "memory");
}

__device__ __forceinline__ void wgmma_k1_n136(float (&d)[68], uint64_t desca, uint64_t descb, int scale_d) {
  asm volatile("{\n.reg .pred p;\nsetp.ne.b32 p, %70, 0;\n"
    "wgmma.mma_async.sync.aligned.m64n136k16.f32.bf16.bf16 "
    "{%0, %1, %2, %3, %4, %5, %6, %7, %8, %9, %10, %11, %12, %13, %14, %15, %16, %17, %18, %19, %20, %21, %22, %23, %24, %25, %26, %27, %28, %29, %30, %31, %32, %33, %34, %35, %36, %37, %38, %39, %40, %41, %42, %43, %44, %45, %46, %47, %48, %49, %50, %51, %52, %53, %54, %55, %56, %57, %58, %59, %60, %61, %62, %63, %64, %65, %66, %67}, "
    "%68, %69, p, 1, 1, 1, 0;\n}\n"
    : "+f"(d[0]), "+f"(d[1]), "+f"(d[2]), "+f"(d[3]), "+f"(d[4]), "+f"(d[5]), "+f"(d[6]), "+f"(d[7]), "+f"(d[8]), "+f"(d[9]), "+f"(d[10]), "+f"(d[11]), "+f"(d[12]), "+f"(d[13]), "+f"(d[14]), "+f"(d[15]), "+f"(d[16]), "+f"(d[17]), "+f"(d[18]), "+f"(d[19]), "+f"(d[20]), "+f"(d[21]), "+f"(d[22]), "+f"(d[23]), "+f"(d[24]), "+f"(d[25]), "+f"(d[26]), "+f"(d[27]), "+f"(d[28]), "+f"(d[29]), "+f"(d[30]), "+f"(d[31]), "+f"(d[32]), "+f"(d[33]), "+f"(d[34]), "+f"(d[35]), "+f"(d[36]), "+f"(d[37]), "+f"(d[38]), "+f"(d[39]), "+f"(d[40]), "+f"(d[41]), "+f"(d[42]), "+f"(d[43]), "+f"(d[44]), "+f"(d[45]), "+f"(d[46]), "+f"(d[47]), "+f"(d[48]), "+f"(d[49]), "+f"(d[50]), "+f"(d[51]), "+f"(d[52]), "+f"(d[53]), "+f"(d[54]), "+f"(d[55]), "+f"(d[56]), "+f"(d[57]), "+f"(d[58]), "+f"(d[59]), "+f"(d[60]), "+f"(d[61]), "+f"(d[62]), "+f"(d[63]), "+f"(d[64]), "+f"(d[65]), "+f"(d[66]), "+f"(d[67])
    : "l"(desca), "l"(descb), "r"(scale_d));
}
__device__ __forceinline__ void wgmma_qk_n64(float (&d)[32], uint32_t a0, uint32_t a1, uint32_t a2, uint32_t a3, uint64_t descb) {
  asm volatile("{\n.reg .pred p;\nsetp.ne.b32 p, 0, 0;\n"
    "wgmma.mma_async.sync.aligned.m64n64k16.f32.bf16.bf16 "
    "{%0, %1, %2, %3, %4, %5, %6, %7, %8, %9, %10, %11, %12, %13, %14, %15, %16, %17, %18, %19, %20, %21, %22, %23, %24, %25, %26, %27, %28, %29, %30, %31}, "
    "{%32, %33, %34, %35}, %36, p, 1, 1, 0;\n}\n"
    : "=f"(d[0]), "=f"(d[1]), "=f"(d[2]), "=f"(d[3]), "=f"(d[4]), "=f"(d[5]), "=f"(d[6]), "=f"(d[7]), "=f"(d[8]), "=f"(d[9]), "=f"(d[10]), "=f"(d[11]), "=f"(d[12]), "=f"(d[13]), "=f"(d[14]), "=f"(d[15]), "=f"(d[16]), "=f"(d[17]), "=f"(d[18]), "=f"(d[19]), "=f"(d[20]), "=f"(d[21]), "=f"(d[22]), "=f"(d[23]), "=f"(d[24]), "=f"(d[25]), "=f"(d[26]), "=f"(d[27]), "=f"(d[28]), "=f"(d[29]), "=f"(d[30]), "=f"(d[31])
    : "r"(a0), "r"(a1), "r"(a2), "r"(a3), "l"(descb));
}
__device__ __forceinline__ void wgmma_pv_n24(float (&d)[12], uint32_t a0, uint32_t a1, uint32_t a2, uint32_t a3, uint64_t descb) {
  asm volatile("{\n.reg .pred p;\nsetp.eq.b32 p, 0, 0;\n"
    "wgmma.mma_async.sync.aligned.m64n24k16.f32.bf16.bf16 "
    "{%0, %1, %2, %3, %4, %5, %6, %7, %8, %9, %10, %11}, "
    "{%12, %13, %14, %15}, %16, p, 1, 1, 1;\n}\n"
    : "+f"(d[0]), "+f"(d[1]), "+f"(d[2]), "+f"(d[3]), "+f"(d[4]), "+f"(d[5]), "+f"(d[6]), "+f"(d[7]), "+f"(d[8]), "+f"(d[9]), "+f"(d[10]), "+f"(d[11])
    : "r"(a0), "r"(a1), "r"(a2), "r"(a3), "l"(descb));
}
__device__ __forceinline__ void wgmma_k3_n64(float (&d)[32], uint64_t desca, uint64_t descb, int scale_d) {
  asm volatile("{\n.reg .pred p;\nsetp.ne.b32 p, %34, 0;\n"
    "wgmma.mma_async.sync.aligned.m64n64k16.f32.bf16.bf16 "
    "{%0, %1, %2, %3, %4, %5, %6, %7, %8, %9, %10, %11, %12, %13, %14, %15, %16, %17, %18, %19, %20, %21, %22, %23, %24, %25, %26, %27, %28, %29, %30, %31}, "
    "%32, %33, p, 1, 1, 0, 1;\n}\n"
    : "+f"(d[0]), "+f"(d[1]), "+f"(d[2]), "+f"(d[3]), "+f"(d[4]), "+f"(d[5]), "+f"(d[6]), "+f"(d[7]), "+f"(d[8]), "+f"(d[9]), "+f"(d[10]), "+f"(d[11]), "+f"(d[12]), "+f"(d[13]), "+f"(d[14]), "+f"(d[15]), "+f"(d[16]), "+f"(d[17]), "+f"(d[18]), "+f"(d[19]), "+f"(d[20]), "+f"(d[21]), "+f"(d[22]), "+f"(d[23]), "+f"(d[24]), "+f"(d[25]), "+f"(d[26]), "+f"(d[27]), "+f"(d[28]), "+f"(d[29]), "+f"(d[30]), "+f"(d[31])
    : "l"(desca), "l"(descb), "r"(scale_d));
}

constexpr int K1_XS = 17408;
constexpr int K1_WS = 24576;
constexpr int K1_NST = 3;
constexpr int K1_OFF_W = 8 * K1_XS;
constexpr int K1_OFF_MISC = K1_OFF_W + K1_NST * K1_WS;
constexpr int K1_SMEM = K1_OFF_MISC + 2048 + 1024;
constexpr float QSCALE = 0.25f * 1.4426950408889634f;

__global__ void __launch_bounds__(544, 1)
k1_qkv(const __grid_constant__ CUtensorMap tm_x, const __grid_constant__ CUtensorMap tm_w) {
    extern __shared__ uint8_t smem_raw[];
    const uint32_t sraw = smem_u32(smem_raw);
    const uint32_t sb = (sraw + 1023) & ~1023u;
    uint8_t* sp = smem_raw + (sb - sraw);
    const uint32_t xbar = sb + K1_OFF_MISC;
    const uint32_t wfull = xbar + 64;
    const uint32_t wempty = wfull + 32;
    float* s_m = (float*)(sp + K1_OFF_MISC + 256);
    float* s_r = s_m + 128;

    const int tid = threadIdx.x, warp = tid >> 5, lane = tid & 31;
    const int mt = blockIdx.x >> 3, nt = blockIdx.x & 7;

    pdl_launch();
    if (tid == 0) {
        for (int i = 0; i < 8; i++) mbar_init(xbar + 8 * i, 1);
        for (int i = 0; i < K1_NST; i++) { mbar_init(wfull + 8 * i, 1); mbar_init(wempty + 8 * i, 3); }
        fence_barrier_init();
    }
    if (tid < 512) {
        *(uint4*)(sp + (tid >> 6) * K1_XS + 16384 + (tid & 63) * 16) =
            make_uint4(0x3F803F80u, 0x3F803F80u, 0x3F803F80u, 0x3F803F80u);
    }
    if (blockIdx.x == 0) {
        for (int i = tid; i < 2 * DM; i += 544) g_y[i] = 0.f;
        if (tid == 0) g_cnt = 0;
    }
    fence_proxy_async();
    __syncthreads();

    if (warp == 16) {
        if (lane == 0) {
            for (int kb = 0; kb < 8; kb++) {
                mbar_expect_tx(xbar + 8 * kb, 16384);
                tma_load_2d(sb + kb * K1_XS, &tm_x, kb * 64, mt * 128, xbar + 8 * kb);
                const int s = kb % K1_NST;
                if (kb >= K1_NST) continue;
                mbar_expect_tx(wfull + 8 * s, K1_WS);
                for (int p = 0; p < 3; p++)
                    tma_load_2d(sb + K1_OFF_W + s * K1_WS + p * 8192, &tm_w, p * 512 + nt * 64, kb * 64, wfull + 8 * s);
            }
            for (int kb = K1_NST; kb < 8; kb++) {
                const int s = kb % K1_NST;
                mbar_wait(wempty + 8 * s, ((kb / K1_NST) - 1) & 1);
                mbar_expect_tx(wfull + 8 * s, K1_WS);
                for (int p = 0; p < 3; p++)
                    tma_load_2d(sb + K1_OFF_W + s * K1_WS + p * 8192, &tm_w, p * 512 + nt * 64, kb * 64, wfull + 8 * s);
            }
        }
    } else if (warp >= 12) {
        const int r = tid - 384;
        float x0 = 0.f, s1 = 0.f, s2 = 0.f;
#pragma unroll 1
        for (int kb = 0; kb < 8; kb++) {
            mbar_wait(xbar + 8 * kb, 0);
            const uint8_t* rowp = sp + kb * K1_XS + r * 128;
            if (kb == 0) x0 = bf_lo(*(const uint32_t*)(rowp + ((r & 7) << 4)));
#pragma unroll
            for (int c = 0; c < 8; c++) {
                const uint4 v = *(const uint4*)(rowp + ((c ^ (r & 7)) << 4));
                const uint32_t w[4] = {v.x, v.y, v.z, v.w};
#pragma unroll
                for (int i = 0; i < 4; i++) {
                    const float a = bf_lo(w[i]) - x0, b = bf_hi(w[i]) - x0;
                    s1 += a; s2 = fmaf(a, a, s2);
                    s1 += b; s2 = fmaf(b, b, s2);
                }
            }
        }
        const float md = s1 * (1.f / DM);
        const float mean = x0 + md;
        const float var = fmaxf(s2 * (1.f / DM) - md * md, 0.f);
        const float den = rbf(sqrtf(rbf(rbf(var) + 1e-5f)));
        s_m[r] = rbf(mean);
        s_r[r] = 1.f / den;
        named_arrive(1, 512);
    } else {
        const int part = warp >> 2, hw = warp & 3;
        float acc[68];
#pragma unroll
        for (int i = 0; i < 68; i++) acc[i] = 0.f;
        fence_regs(acc);
#pragma unroll 1
        for (int kb = 0; kb < 8; kb++) {
            const int s = kb % K1_NST;
            mbar_wait(xbar + 8 * kb, 0);
            mbar_wait(wfull + 8 * s, (kb / K1_NST) & 1);
            const uint64_t da = make_desc(sb + K1_OFF_W + s * K1_WS + part * 8192, 1024, 1024, 1);
            const uint64_t db = make_desc(sb + kb * K1_XS, 16, 1024, 1);
            wg_fence();
#pragma unroll
            for (int k = 0; k < 4; k++) wgmma_k1_n136(acc, da + k * 128, db + k * 2, (kb | k) != 0);
            wg_commit();
            if (kb > 0) {
                wg_wait<1>();
                if ((tid & 127) == 0) mbar_arrive(wempty + 8 * ((kb - 1) % K1_NST));
            }
        }
        wg_wait<0>();
        fence_regs(acc);
        named_sync(1, 512);

        const int t = lane & 3;
        const float cs0 = acc[64], cs1 = acc[66];
        const float sc = (part == 0) ? QSCALE : 1.f;
        const uint32_t stg = sb + K1_OFF_W + (hw >> 1) * K1_WS + part * 8192 + (hw & 1) * 4096;
        const uint32_t st_addr = stg + ((lane >> 3) & 1) * 2048 + ((lane >> 4) * 8 + (lane & 7)) * 16;
#pragma unroll
        for (int j = 0; j < 16; j += 2) {
            uint32_t rr[4];
#pragma unroll
            for (int u = 0; u < 2; u++) {
                const int jj = j + u;
                const float2 m2 = *(const float2*)(s_m + 8 * jj + 2 * t);
                const float2 r2 = *(const float2*)(s_r + 8 * jj + 2 * t);
                const float ra = r2.x * sc, rb = r2.y * sc;
                rr[2 * u] = pack_bf16((acc[4 * jj] - m2.x * cs0) * ra, (acc[4 * jj + 1] - m2.y * cs0) * rb);
                rr[2 * u + 1] = pack_bf16((acc[4 * jj + 2] - m2.x * cs1) * ra, (acc[4 * jj + 3] - m2.y * cs1) * rb);
            }
            stmatrix_x4_trans(st_addr + j * 128, rr[0], rr[1], rr[2], rr[3]);
        }
        __syncwarp();
        float nmax = 0.f;
#pragma unroll
        for (int i = 0; i < 4; i++) {
            const int tok = lane + 32 * i;
            const uint4 a = *(const uint4*)(sp + (stg - sb) + tok * 16);
            const uint4 b = *(const uint4*)(sp + (stg - sb) + 2048 + tok * 16);
            const uint32_t w[8] = {a.x, a.y, a.z, a.w, b.x, b.y, b.z, b.w};
            float n2 = 0.f;
#pragma unroll
            for (int q = 0; q < 8; q++) {
                const float lo = bf_lo(w[q]), hi = bf_hi(w[q]);
                n2 = fmaf(lo, lo, n2); n2 = fmaf(hi, hi, n2);
            }
            nmax = (n2 > nmax || n2 != n2) ? n2 : nmax;
        }
#pragma unroll
        for (int o = 16; o > 0; o >>= 1) {
            const float v = __shfl_xor_sync(0xffffffffu, nmax, o);
            nmax = (v > nmax || v != v) ? v : nmax;
        }
        fence_proxy_async();
        __syncwarp();
        if (lane == 0) {
            const int head = nt * 4 + hw;
            g_norm[(mt * NH + head) * 3 + part] = nmax;
            uint8_t* dst;
            uint32_t hstride;
            if (part == 0) { dst = g_q + (size_t)head * 65536 + mt * 2048; hstride = 32768; }
            else { dst = g_kv + (size_t)head * 131072 + (mt >> 1) * 16384 + (part - 1) * 8192 + (mt & 1) * 2048; hstride = 4096; }
            bulk_s2g(dst, stg, 2048);
            bulk_s2g(dst + hstride, stg + 2048, 2048);
            asm volatile("cp.async.bulk.commit_group;" ::: "memory");
            asm volatile("cp.async.bulk.wait_group 0;" ::: "memory");
        }
    }
}

constexpr int K2_CH_G = 16384, K2_CH_S = 20480, K2_NCH = 8;
constexpr int K2_SMEM = K2_NCH * K2_CH_S + 128 + 1024;

__device__ __forceinline__ uint32_t exp2_pair_poly(float s0, float s1) {
    const float KB = 65536.0f + 127.0f;
    const float t0 = s0 + KB, t1 = s1 + KB;
    const uint32_t w = __byte_perm(__float_as_uint(t0), __float_as_uint(t1), 0x5410);
    uint32_t z;
    asm("lop3.b32 %0, %1, %2, %3, 0xEA;" : "=r"(z) : "r"(w), "r"(0x007F007Fu), "r"(0x3F803F80u));
    uint32_t p = fma_bf16x2(0x3eab3eabu, z, 0xbc73bc73u);
    p = fma_bf16x2(p, z, 0x3f2f3f2fu);
    return p + w - z;
}
constexpr uint32_t K2_EMASK = 0x5757u;
template <int LO, int HI>
__device__ __forceinline__ void softmax_part(const float (&s)[32], uint32_t (&p)[16]) {
#pragma unroll
    for (int i = LO; i < HI; i++) {
        if ((K2_EMASK >> i) & 1) p[i] = exp2_pair_poly(s[2 * i], s[2 * i + 1]);
        else p[i] = pack_bf16(ex2f(s[2 * i]), ex2f(s[2 * i + 1]));
    }
}
#define K2_PV(P, OFF)                                                                              \
    _Pragma("unroll") for (int kk = 0; kk < 4; kk++)                                               \
        wgmma_pv_n24(o, P[4 * kk], P[4 * kk + 1], P[4 * kk + 2], P[4 * kk + 3], dv + ((OFF) + kk * 16));

__global__ void __launch_bounds__(512, 1) k2_attn() {
    extern __shared__ uint8_t smem_raw[];
    const uint32_t sraw = smem_u32(smem_raw);
    const uint32_t sb = (sraw + 1023) & ~1023u;
    uint8_t* sp = smem_raw + (sb - sraw);
    const uint32_t bars = sb + K2_NCH * K2_CH_S;
    const int tid = threadIdx.x;
    const int head = blockIdx.x >> 2, quarter = blockIdx.x & 3;

    pdl_launch();
    if (tid == 0) {
        for (int c = 0; c < K2_NCH; c++) mbar_init(bars + 8 * c, 1);
        fence_barrier_init();
    }
    for (int i = tid; i < K2_NCH * 256; i += 512)
        *(uint4*)(sp + (i >> 8) * K2_CH_S + 16384 + (i & 255) * 16) =
            make_uint4(0x3F803F80u, 0x3F803F80u, 0x3F803F80u, 0x3F803F80u);
    fence_proxy_async();
    __syncthreads();
    pdl_wait();
    if (tid == 0) {
        const uint8_t* src = g_kv + (size_t)head * (K2_NCH * K2_CH_G);
        for (int c = 0; c < K2_NCH; c++) {
            mbar_expect_tx(bars + 8 * c, K2_CH_G);
            bulk_g2s(sb + c * K2_CH_S, src + c * K2_CH_G, K2_CH_G, bars + 8 * c);
        }
    }
    const int wg = tid >> 7, warp = (tid >> 5) & 3, lane = tid & 31, g = lane >> 2, t = lane & 3;

    bool fast;
    {
        const int m16 = lane & 15;
        float kn = g_norm[(m16 * NH + head) * 3 + 1];
        float vn = g_norm[(m16 * NH + head) * 3 + 2];
        float qn = g_norm[((quarter * 4 + (lane & 3)) * NH + head) * 3 + 0];
        bool bad = !(kn < 1e30f) || !(vn < 1e30f) || !(qn < 1e30f);
#pragma unroll
        for (int o = 8; o > 0; o >>= 1) {
            kn = fmaxf(kn, __shfl_xor_sync(0xffffffffu, kn, o));
            qn = fmaxf(qn, __shfl_xor_sync(0xffffffffu, qn, o));
        }
        bad = __any_sync(0xffffffffu, bad);
        fast = !bad && (qn * kn <= 3500.f);
    }
    const uint64_t dk0 = make_desc(sb, 4096, 128, 0);
    const uint64_t dv0 = make_desc(sb + 8192, 128, 4096, 0);

#pragma unroll 1
    for (int pass = 0; pass < 2; pass++) {
        const int row0 = quarter * 512 + pass * 256 + wg * 64 + warp * 16 + g;
        uint32_t qa[4];
        {
            const uint8_t* qb = g_q + (size_t)head * 65536 + row0 * 16 + t * 4;
            qa[0] = *(const uint32_t*)(qb);
            qa[1] = *(const uint32_t*)(qb + 128);
            qa[2] = *(const uint32_t*)(qb + 32768);
            qa[3] = *(const uint32_t*)(qb + 32768 + 128);
        }
        float o[12];
#pragma unroll
        for (int i = 0; i < 12; i++) o[i] = 0.f;
        fence_regs(o);
        if (fast) {
#pragma unroll 1
            for (int c = 0; c < K2_NCH; c++) {
                const uint64_t dk = dk0 + (uint64_t)(c * (K2_CH_S >> 4));
                const uint64_t dv = dv0 + (uint64_t)(c * (K2_CH_S >> 4));
                float s0[32], s1[32], s2[32], s3[32];
                uint32_t p0[16], p1[16], p2[16], p3[16];
                mbar_wait(bars + 8 * c, 0);
                wg_wait<1>();
                wg_fence();
                wgmma_qk_n64(s0, qa[0], qa[1], qa[2], qa[3], dk);
                wg_commit();
                wg_wait<1>();
                wg_fence();
                wgmma_qk_n64(s1, qa[0], qa[1], qa[2], qa[3], dk + 64);
                wg_commit();
                wg_wait<1>();
                fence_regs(s0);
                softmax_part<0, 16>(s0, p0);
                wg_fence();
                K2_PV(p0, 0);
                wg_commit();
                wg_wait<1>();
                fence_regs(s1);
                softmax_part<0, 8>(s1, p1);
                wg_wait<0>();
                wg_fence();
                wgmma_qk_n64(s2, qa[0], qa[1], qa[2], qa[3], dk + 128);
                wg_commit();
                softmax_part<8, 16>(s1, p1);
                wg_fence();
                K2_PV(p1, 64);
                wg_commit();
                wg_wait<1>();
                fence_regs(s2);
                softmax_part<0, 8>(s2, p2);
                wg_wait<0>();
                wg_fence();
                wgmma_qk_n64(s3, qa[0], qa[1], qa[2], qa[3], dk + 192);
                wg_commit();
                softmax_part<8, 16>(s2, p2);
                wg_fence();
                K2_PV(p2, 128);
                wg_commit();
                wg_wait<1>();
                fence_regs(s3);
                softmax_part<0, 16>(s3, p3);
                wg_fence();
                K2_PV(p3, 192);
                wg_commit();
            }
            wg_wait<0>();
            fence_regs(o);
        } else {
            float m0 = -INFINITY, m1 = -INFINITY;
#pragma unroll 1
            for (int b = 0; b < 32; b++) {
                const int c = b >> 2;
                const uint64_t dk = dk0 + (uint64_t)(c * (K2_CH_S >> 4) + (b & 3) * 64);
                const uint64_t dv = dv0 + (uint64_t)(c * (K2_CH_S >> 4) + (b & 3) * 64);
                float s[32];
                uint32_t p[16];
                mbar_wait(bars + 8 * c, 0);
                wg_fence();
                wgmma_qk_n64(s, qa[0], qa[1], qa[2], qa[3], dk);
                wg_commit();
                wg_wait<0>();
                fence_regs(s);
                float x0 = s[0], x1 = s[2];
#pragma unroll
                for (int j = 0; j < 8; j++) {
                    x0 = fmaxf(x0, fmaxf(s[4 * j], s[4 * j + 1]));
                    x1 = fmaxf(x1, fmaxf(s[4 * j + 2], s[4 * j + 3]));
                }
                x0 = fmaxf(x0, __shfl_xor_sync(0xffffffffu, x0, 1));
                x0 = fmaxf(x0, __shfl_xor_sync(0xffffffffu, x0, 2));
                x1 = fmaxf(x1, __shfl_xor_sync(0xffffffffu, x1, 1));
                x1 = fmaxf(x1, __shfl_xor_sync(0xffffffffu, x1, 2));
                const float n0 = fmaxf(m0, x0), n1 = fmaxf(m1, x1);
                const float c0 = ex2f(m0 - n0), c1 = ex2f(m1 - n1);
                m0 = n0; m1 = n1;
#pragma unroll
                for (int j = 0; j < 3; j++) {
                    o[4 * j] *= c0; o[4 * j + 1] *= c0; o[4 * j + 2] *= c1; o[4 * j + 3] *= c1;
                }
#pragma unroll
                for (int j = 0; j < 8; j++) {
                    p[2 * j] = pack_bf16(ex2f(s[4 * j] - n0), ex2f(s[4 * j + 1] - n0));
                    p[2 * j + 1] = pack_bf16(ex2f(s[4 * j + 2] - n1), ex2f(s[4 * j + 3] - n1));
                }
                fence_regs(o);
                wg_fence();
                K2_PV(p, 0);
                wg_commit();
                wg_wait<0>();
                fence_regs(o);
            }
        }
        const float inv0 = 1.f / o[8], inv1 = 1.f / o[10];
        uint32_t* out0 = (uint32_t*)(g_o + (size_t)row0 * DM + head * 16);
        uint32_t* out1 = (uint32_t*)(g_o + (size_t)(row0 + 8) * DM + head * 16);
        out0[t] = pack_bf16(o[0] * inv0, o[1] * inv0);
        out0[4 + t] = pack_bf16(o[4] * inv0, o[5] * inv0);
        out1[t] = pack_bf16(o[2] * inv1, o[3] * inv1);
        out1[4 + t] = pack_bf16(o[6] * inv1, o[7] * inv1);
    }
}

constexpr int K3_OFF_W = 65536;
constexpr int K3_OFF_MISC = K3_OFF_W + 131072;
constexpr int K3_SMEM = K3_OFF_MISC + 128 + 8 * 64 * 16 + 512 + 1024;

__device__ __forceinline__ unsigned long long make_key(float r_bf, int idx) {
    uint32_t u = __float_as_uint(r_bf);
    u = (u & 0x80000000u) ? ~u : (u | 0x80000000u);
    return ((unsigned long long)u << 32) | (uint32_t)(0x7FFFFFFF - idx);
}
__device__ __forceinline__ float key_value(unsigned long long k) {
    uint32_t u = (uint32_t)(k >> 32);
    u = (u & 0x80000000u) ? (u & 0x7FFFFFFFu) : ~u;
    return __uint_as_float(u);
}
__device__ __forceinline__ int key_index(unsigned long long k) { return 0x7FFFFFFF - (int)(uint32_t)k; }
__device__ __forceinline__ void warp_top2(unsigned long long& a, unsigned long long& b) {
#pragma unroll
    for (int o = 16; o > 0; o >>= 1) {
        const unsigned long long c = __shfl_xor_sync(0xffffffffu, a, o);
        const unsigned long long d = __shfl_xor_sync(0xffffffffu, b, o);
        const unsigned long long hi = a > c ? a : c, lo = a > c ? c : a;
        const unsigned long long m = b > d ? b : d;
        a = hi;
        b = lo > m ? lo : m;
    }
}

__global__ void __cluster_dims__(4, 1, 1) __launch_bounds__(288, 1)
k3_proj(const __grid_constant__ CUtensorMap tm_o, const __grid_constant__ CUtensorMap tm_wo,
        const __nv_bfloat16* __restrict__ x, const __nv_bfloat16* __restrict__ w_r, __nv_bfloat16* __restrict__ out) {
    extern __shared__ uint8_t smem_raw[];
    const uint32_t sraw = smem_u32(smem_raw);
    const uint32_t sb = (sraw + 1023) & ~1023u;
    uint8_t* sp = smem_raw + (sb - sraw);
    const uint32_t obar = sb + K3_OFF_MISC;
    const uint32_t wbar = obar + 64;
    const uint32_t s_part = sb + K3_OFF_MISC + 128;
    unsigned long long* s_key = (unsigned long long*)(sp + K3_OFF_MISC + 128 + 8 * 64 * 16);

    const int tid = threadIdx.x, warp = tid >> 5, lane = tid & 31;
    const int mt = blockIdx.x >> 2, nt = blockIdx.x & 3;

    pdl_launch();
    if (tid == 0) {
        for (int i = 0; i < 16; i++) mbar_init(obar + 8 * i, 1);
        fence_barrier_init();
    }
    __syncthreads();

    const int wg = warp >> 2, wi = warp & 3, g = lane >> 2, t = lane & 3;
    const int r0 = mt * 64 + wi * 16 + g;
    const int cb = nt * 128 + wg * 64;
    float hv[32];
    if (warp == 8) {
        if (lane == 0) {
            for (int kb = 0; kb < 8; kb++) {
                mbar_expect_tx(wbar + 8 * kb, 16384);
                tma_load_2d(sb + K3_OFF_W + kb * 16384, &tm_wo, nt * 128, kb * 64, wbar + 8 * kb);
                tma_load_2d(sb + K3_OFF_W + kb * 16384 + 8192, &tm_wo, nt * 128 + 64, kb * 64, wbar + 8 * kb);
            }
            pdl_wait();
            for (int kb = 0; kb < 8; kb++) {
                mbar_expect_tx(obar + 8 * kb, 8192);
                tma_load_2d(sb + kb * 8192, &tm_o, kb * 64, mt * 64, obar + 8 * kb);
            }
        }
        __syncwarp();
    } else {
        uint32_t xr[16], wr[8];
#pragma unroll
        for (int j = 0; j < 8; j++) {
            xr[2 * j] = *(const uint32_t*)(x + (size_t)r0 * DM + cb + 8 * j + 2 * t);
            xr[2 * j + 1] = *(const uint32_t*)(x + (size_t)(r0 + 8) * DM + cb + 8 * j + 2 * t);
            wr[j] = *(const uint32_t*)(w_r + cb + 8 * j + 2 * t);
        }
        float acc[32];
#pragma unroll
        for (int i = 0; i < 32; i++) acc[i] = 0.f;
        fence_regs(acc);
#pragma unroll 1
        for (int kb = 0; kb < 8; kb++) {
            mbar_wait(wbar + 8 * kb, 0);
            mbar_wait(obar + 8 * kb, 0);
            const uint64_t da = make_desc(sb + kb * 8192, 16, 1024, 1);
            const uint64_t db = make_desc(sb + K3_OFF_W + kb * 16384 + wg * 8192, 1024, 1024, 1);
            wg_fence();
#pragma unroll
            for (int k = 0; k < 4; k++) wgmma_k3_n64(acc, da + k * 2, db + k * 128, (kb | k) != 0);
            wg_commit();
        }
        wg_wait<0>();
        fence_regs(acc);
        float s0 = 0.f, s1 = 0.f, d0 = 0.f, d1 = 0.f, ws = 0.f;
#pragma unroll
        for (int j = 0; j < 8; j++) {
            hv[4 * j] = rbf(bf_lo(xr[2 * j]) + rbf(acc[4 * j]));
            hv[4 * j + 1] = rbf(bf_hi(xr[2 * j]) + rbf(acc[4 * j + 1]));
            hv[4 * j + 2] = rbf(bf_lo(xr[2 * j + 1]) + rbf(acc[4 * j + 2]));
            hv[4 * j + 3] = rbf(bf_hi(xr[2 * j + 1]) + rbf(acc[4 * j + 3]));
            const float wl = bf_lo(wr[j]), wh = bf_hi(wr[j]);
            s0 += hv[4 * j] + hv[4 * j + 1];
            s1 += hv[4 * j + 2] + hv[4 * j + 3];
            d0 = fmaf(hv[4 * j], wl, fmaf(hv[4 * j + 1], wh, d0));
            d1 = fmaf(hv[4 * j + 2], wl, fmaf(hv[4 * j + 3], wh, d1));
            ws += wl + wh;
        }
#pragma unroll
        for (int o = 1; o < 4; o <<= 1) {
            s0 += __shfl_xor_sync(0xffffffffu, s0, o);
            s1 += __shfl_xor_sync(0xffffffffu, s1, o);
            d0 += __shfl_xor_sync(0xffffffffu, d0, o);
            d1 += __shfl_xor_sync(0xffffffffu, d1, o);
            ws += __shfl_xor_sync(0xffffffffu, ws, o);
        }
        const float mu0 = s0 * (1.f / 64), mu1 = s1 * (1.f / 64);
        float q0 = 0.f, q1 = 0.f;
#pragma unroll
        for (int j = 0; j < 8; j++) {
            float a = hv[4 * j] - mu0, b = hv[4 * j + 1] - mu0, c = hv[4 * j + 2] - mu1, d = hv[4 * j + 3] - mu1;
            q0 = fmaf(a, a, fmaf(b, b, q0));
            q1 = fmaf(c, c, fmaf(d, d, q1));
        }
#pragma unroll
        for (int o = 1; o < 4; o <<= 1) {
            q0 += __shfl_xor_sync(0xffffffffu, q0, o);
            q1 += __shfl_xor_sync(0xffffffffu, q1, o);
        }
        const uint32_t loc = s_part + ((nt * 2 + wg) * 64 + wi * 16 + g) * 16;
        uint32_t rem;
        asm volatile("mapa.shared::cluster.u32 %0, %1, %2;" : "=r"(rem) : "r"(loc), "r"(t));
        asm volatile("st.shared::cluster.v4.f32 [%0], {%1, %2, %3, %4};" ::"r"(rem), "f"(mu0), "f"(q0), "f"(d0), "f"(ws) : "memory");
        asm volatile("st.shared::cluster.v4.f32 [%0], {%1, %2, %3, %4};" ::"r"(rem + 128), "f"(mu1), "f"(q1), "f"(d1), "f"(ws) : "memory");
    }
    asm volatile("barrier.cluster.arrive.release.aligned;" ::: "memory");
    asm volatile("barrier.cluster.wait.acquire.aligned;" ::: "memory");
    if (warp < 8) {
        float mean[2], den[2], rr[2];
#pragma unroll
        for (int u = 0; u < 2; u++) {
            const float4* pp = (const float4*)(sp + K3_OFF_MISC + 128) + wi * 16 + g + 8 * u;
            float4 v[8];
#pragma unroll
            for (int i = 0; i < 8; i++) v[i] = pp[i * 64];
            float mu = 0.f, hw = 0.f, wsum = 0.f, m2 = 0.f;
#pragma unroll
            for (int i = 0; i < 8; i++) { mu += v[i].x; hw += v[i].z; wsum += v[i].w; m2 += v[i].y; }
            mu *= 0.125f;
#pragma unroll
            for (int i = 0; i < 8; i++) { const float d = v[i].x - mu; m2 = fmaf(64.f * d, d, m2); }
            mean[u] = rbf(mu);
            den[u] = rbf(sqrtf(rbf(rbf(m2 * (1.f / DM)) + 1e-5f)));
            rr[u] = rbf((hw - mean[u] * wsum) / den[u]);
        }
        const float i0 = 1.f / den[0], i1 = 1.f / den[1];
        const uint32_t stg_o = sb + warp * 4096;
        const uint32_t stg_h = stg_o + 2048;
        const int srow = (lane & 7) + ((lane >> 3) & 1) * 8;
        const int sj = lane >> 4;
#pragma unroll
        for (int j = 0; j < 8; j += 2) {
            uint32_t ro[4], rh[4];
#pragma unroll
            for (int u = 0; u < 2; u++) {
                const int jj = j + u;
                const float a = hv[4 * jj], b = hv[4 * jj + 1], c = hv[4 * jj + 2], d = hv[4 * jj + 3];
                const float na = rbf(rbf(a - mean[0]) * i0), nb = rbf(rbf(b - mean[0]) * i0);
                const float nc = rbf(rbf(c - mean[1]) * i1), nd = rbf(rbf(d - mean[1]) * i1);
                ro[2 * u] = pack_bf16(a + na, b + nb);
                ro[2 * u + 1] = pack_bf16(c + nc, d + nd);
                rh[2 * u] = pack_bf16(a, b);
                rh[2 * u + 1] = pack_bf16(c, d);
            }
            const uint32_t off = srow * 128 + (((j + sj) ^ (srow & 7)) << 4);
            stmatrix_x4(stg_o + off, ro[0], ro[1], ro[2], ro[3]);
            stmatrix_x4(stg_h + off, rh[0], rh[1], rh[2], rh[3]);
        }
        __syncwarp();
#pragma unroll
        for (int i = 0; i < 4; i++) {
            const int row = i * 4 + (lane >> 3), ch = lane & 7;
            const uint32_t off = warp * 4096 + row * 128 + ((ch ^ (row & 7)) << 4);
            const uint4 vo = *(const uint4*)(sp + off);
            const uint4 vh = *(const uint4*)(sp + off + 2048);
            const size_t go = (size_t)(mt * 64 + wi * 16 + row) * DM + cb + ch * 8;
            *(uint4*)(out + go) = vo;
            *(uint4*)(g_h + go) = vh;
        }
        if (nt == 0 && wg == 0) {
            if (t == 0) {
                g_stat[r0] = make_float2(mean[0], den[0]);
                g_stat[r0 + 8] = make_float2(mean[1], den[1]);
                s_key[wi * 16 + g] = make_key(rr[0], r0);
                s_key[wi * 16 + g + 8] = make_key(rr[1], r0 + 8);
            }
            named_sync(1, 128);
            if (warp == 0) {
                unsigned long long a = s_key[lane], b = s_key[lane + 32];
                if (b > a) { const unsigned long long c = a; a = b; b = c; }
                warp_top2(a, b);
                if (lane == 0) { g_cand[mt * 2] = a; g_cand[mt * 2 + 1] = b; }
            }
        }
    }
}

__global__ void __launch_bounds__(128)
k4_moe(const __nv_bfloat16* __restrict__ w_gate, const __nv_bfloat16* __restrict__ w_up,
       const __nv_bfloat16* __restrict__ w_down, __nv_bfloat16* __restrict__ out) {
    __shared__ float s_red[4][64];
    __shared__ float s_a[2][16];
    __shared__ int s_last;
    const int tid = threadIdx.x, warp = tid >> 5, lane = tid & 31;
    const int f0 = blockIdx.x * 16;

    uint4 wg[8], wu[8];
    uint2 wd[16];
#pragma unroll
    for (int k = 0; k < 4; k++) {
        const uint4* pg = (const uint4*)(w_gate + (size_t)(4 * tid + k) * FF + f0);
        const uint4* pu = (const uint4*)(w_up + (size_t)(4 * tid + k) * FF + f0);
        wg[2 * k] = __ldg(pg); wg[2 * k + 1] = __ldg(pg + 1);
        wu[2 * k] = __ldg(pu); wu[2 * k + 1] = __ldg(pu + 1);
    }
#pragma unroll
    for (int f = 0; f < 16; f++) wd[f] = __ldg((const uint2*)(w_down + (size_t)(f0 + f) * DM + 4 * tid));

    pdl_wait();

    unsigned long long ka = g_cand[2 * lane], kb = g_cand[2 * lane + 1];
    warp_top2(ka, kb);
    const int idx[2] = {key_index(ka), key_index(kb)};
    float hx[2][4], xs[2][4];
#pragma unroll
    for (int u = 0; u < 2; u++) {
        const uint2 hv = *(const uint2*)(g_h + (size_t)idx[u] * DM + 4 * tid);
        const float2 st = g_stat[idx[u]];
        const float inv = 1.f / st.y;
        hx[u][0] = bf_lo(hv.x); hx[u][1] = bf_hi(hv.x); hx[u][2] = bf_lo(hv.y); hx[u][3] = bf_hi(hv.y);
#pragma unroll
        for (int k = 0; k < 4; k++) xs[u][k] = rbf(rbf(hx[u][k] - st.x) * inv);
    }
    float acc[64];
#pragma unroll
    for (int i = 0; i < 64; i++) acc[i] = 0.f;
#pragma unroll
    for (int k = 0; k < 4; k++) {
        const uint32_t gw[8] = {wg[2 * k].x, wg[2 * k].y, wg[2 * k].z, wg[2 * k].w, wg[2 * k + 1].x, wg[2 * k + 1].y, wg[2 * k + 1].z, wg[2 * k + 1].w};
        const uint32_t uw[8] = {wu[2 * k].x, wu[2 * k].y, wu[2 * k].z, wu[2 * k].w, wu[2 * k + 1].x, wu[2 * k + 1].y, wu[2 * k + 1].z, wu[2 * k + 1].w};
#pragma unroll
        for (int i = 0; i < 8; i++) {
            const float gl = bf_lo(gw[i]), gh = bf_hi(gw[i]), ul = bf_lo(uw[i]), uh = bf_hi(uw[i]);
#pragma unroll
            for (int u = 0; u < 2; u++) {
                acc[u * 32 + 2 * i] = fmaf(xs[u][k], gl, acc[u * 32 + 2 * i]);
                acc[u * 32 + 2 * i + 1] = fmaf(xs[u][k], gh, acc[u * 32 + 2 * i + 1]);
                acc[u * 32 + 16 + 2 * i] = fmaf(xs[u][k], ul, acc[u * 32 + 16 + 2 * i]);
                acc[u * 32 + 16 + 2 * i + 1] = fmaf(xs[u][k], uh, acc[u * 32 + 16 + 2 * i + 1]);
            }
        }
    }
#define K4_STEP(O, N)                                                          \
    {                                                                          \
        const bool up = (lane & (O)) != 0;                                     \
        _Pragma("unroll") for (int i = 0; i < (N); i++) {                      \
            const float send = up ? acc[i] : acc[i + (N)];                     \
            const float keep = up ? acc[i + (N)] : acc[i];                     \
            acc[i] = keep + __shfl_xor_sync(0xffffffffu, send, (O));           \
        }                                                                      \
    }
    K4_STEP(16, 32) K4_STEP(8, 16) K4_STEP(4, 8) K4_STEP(2, 4) K4_STEP(1, 2)
    {
        const int base = ((lane & 16) ? 32 : 0) + ((lane & 8) ? 16 : 0) + ((lane & 4) ? 8 : 0) + ((lane & 2) ? 4 : 0) + ((lane & 1) ? 2 : 0);
        s_red[warp][base] = acc[0];
        s_red[warp][base + 1] = acc[1];
    }
    __syncthreads();
    if (tid < 32) {
        const int u = tid >> 4, c = tid & 15;
        const float gsum = s_red[0][u * 32 + c] + s_red[1][u * 32 + c] + s_red[2][u * 32 + c] + s_red[3][u * 32 + c];
        const float usum = s_red[0][u * 32 + 16 + c] + s_red[1][u * 32 + 16 + c] + s_red[2][u * 32 + 16 + c] + s_red[3][u * 32 + 16 + c];
        const float gb = rbf(gsum);
        const float sg = rbf(gb / (1.f + __expf(-gb)));
        s_a[u][c] = rbf(sg * rbf(usum));
    }
    __syncthreads();
    float y[2][4] = {{0.f, 0.f, 0.f, 0.f}, {0.f, 0.f, 0.f, 0.f}};
#pragma unroll
    for (int f = 0; f < 16; f++) {
        const float w0 = bf_lo(wd[f].x), w1 = bf_hi(wd[f].x), w2 = bf_lo(wd[f].y), w3 = bf_hi(wd[f].y);
#pragma unroll
        for (int u = 0; u < 2; u++) {
            const float a = s_a[u][f];
            y[u][0] = fmaf(a, w0, y[u][0]); y[u][1] = fmaf(a, w1, y[u][1]);
            y[u][2] = fmaf(a, w2, y[u][2]); y[u][3] = fmaf(a, w3, y[u][3]);
        }
    }
#pragma unroll
    for (int u = 0; u < 2; u++)
        asm volatile("red.global.add.v4.f32 [%0], {%1, %2, %3, %4};" ::"l"(g_y + u * DM + 4 * tid), "f"(y[u][0]), "f"(y[u][1]), "f"(y[u][2]), "f"(y[u][3]) : "memory");
    __threadfence();
    __syncthreads();
    if (tid == 0) s_last = (atomicAdd(&g_cnt, 1u) == gridDim.x - 1);
    __syncthreads();
    if (s_last) {
        __threadfence();
        const float rv[2] = {key_value(ka), key_value(kb)};
#pragma unroll
        for (int u = 0; u < 2; u++) {
            const float4 yy = __ldcg((const float4*)(g_y + u * DM + 4 * tid));
            const float sig = rbf(1.f / (1.f + __expf(-rv[u])));
            const float yv[4] = {yy.x, yy.y, yy.z, yy.w};
            float o[4];
#pragma unroll
            for (int k = 0; k < 4; k++) o[k] = hx[u][k] + rbf(xs[u][k] + rbf(rbf(yv[k]) * sig));
            uint2 pk = make_uint2(pack_bf16(o[0], o[1]), pack_bf16(o[2], o[3]));
            *(uint2*)(out + (size_t)idx[u] * DM + 4 * tid) = pk;
        }
    }
}

typedef CUresult (*PFN_encodeTiled)(CUtensorMap*, CUtensorMapDataType, cuuint32_t, void*, const cuuint64_t*, const cuuint64_t*,
                                    const cuuint32_t*, const cuuint32_t*, CUtensorMapInterleave, CUtensorMapSwizzle,
                                    CUtensorMapL2promotion, CUtensorMapFloatOOBfill);

void make_map(PFN_encodeTiled enc, CUtensorMap* m, const void* ptr, uint64_t cols, uint64_t rows, uint32_t bcols, uint32_t brows) {
    cuuint64_t dims[2] = {cols, rows};
    cuuint64_t strides[1] = {cols * 2};
    cuuint32_t box[2] = {bcols, brows};
    cuuint32_t es[2] = {1, 1};
    enc(m, CU_TENSOR_MAP_DATA_TYPE_BFLOAT16, 2, const_cast<void*>(ptr), dims, strides, box, es, CU_TENSOR_MAP_INTERLEAVE_NONE,
        CU_TENSOR_MAP_SWIZZLE_128B, CU_TENSOR_MAP_L2_PROMOTION_L2_256B, CU_TENSOR_MAP_FLOAT_OOB_FILL_NONE);
}

template <typename... KArgs, typename... Args>
void launch(void (*kern)(KArgs...), int grid, int block, int smem, bool pdl, Args... args) {
    cudaLaunchConfig_t cfg = {};
    cfg.gridDim = dim3(grid);
    cfg.blockDim = dim3(block);
    cfg.dynamicSmemBytes = smem;
    cfg.stream = cudaStreamPerThread;
    cudaLaunchAttribute at[1];
    at[0].id = cudaLaunchAttributeProgrammaticStreamSerialization;
    at[0].val.programmaticStreamSerializationAllowed = 1;
    cfg.attrs = at;
    cfg.numAttrs = pdl ? 1 : 0;
    cudaLaunchKernelEx(&cfg, kern, KArgs(args)...);
}

}

extern "C" void kernel_launch(void* const* d_in, const int* in_sizes, int n_in, void* d_out, int out_size) {
    const __nv_bfloat16* x = (const __nv_bfloat16*)d_in[0];
    const __nv_bfloat16* wqkv = (const __nv_bfloat16*)d_in[1];
    const __nv_bfloat16* wo = (const __nv_bfloat16*)d_in[2];
    const __nv_bfloat16* w_r = (const __nv_bfloat16*)d_in[4];
    const __nv_bfloat16* w_gate = (const __nv_bfloat16*)d_in[5];
    const __nv_bfloat16* w_up = (const __nv_bfloat16*)d_in[6];
    const __nv_bfloat16* w_down = (const __nv_bfloat16*)d_in[7];
    __nv_bfloat16* out = (__nv_bfloat16*)d_out;

    static PFN_encodeTiled enc = nullptr;
    static void* g_o_ptr = nullptr;
    if (!enc) {
        cudaDriverEntryPointQueryResult qres;
        void* fn = nullptr;
        cudaGetDriverEntryPoint("cuTensorMapEncodeTiled", &fn, cudaEnableDefault, &qres);
        enc = (PFN_encodeTiled)fn;
        cudaGetSymbolAddress(&g_o_ptr, g_o);
        cudaFuncSetAttribute(k1_qkv, cudaFuncAttributeMaxDynamicSharedMemorySize, K1_SMEM);
        cudaFuncSetAttribute(k2_attn, cudaFuncAttributeMaxDynamicSharedMemorySize, K2_SMEM);
        cudaFuncSetAttribute(k3_proj, cudaFuncAttributeMaxDynamicSharedMemorySize, K3_SMEM);
    }
    CUtensorMap tm_x, tm_w, tm_o, tm_wo;
    make_map(enc, &tm_x, x, DM, SEQ, 64, 128);
    make_map(enc, &tm_w, wqkv, 3 * DM, DM, 64, 64);
    make_map(enc, &tm_o, g_o_ptr, DM, SEQ, 64, 64);
    make_map(enc, &tm_wo, wo, DM, DM, 64, 64);

    const bool pdl = true;
    launch(k1_qkv, 128, 544, K1_SMEM, false, tm_x, tm_w);
    launch(k2_attn, 128, 512, K2_SMEM, pdl);
    launch(k3_proj, 128, 288, K3_SMEM, pdl, tm_o, tm_wo, x, w_r, out);
    launch(k4_moe, 112, 128, 0, pdl, w_gate, w_up, w_down, out);
}
```

```cpp
#include <cuda_runtime.h>
#include <cuda_bf16.h>
#include <cuda.h>
#include <stdint.h>

namespace {

constexpr int SEQ = 2048, DM = 512, NH = 32, FF = 1792;

__device__ __align__(1024) uint8_t g_q[NH * 2 * SEQ * 16];
__device__ __align__(1024) uint8_t g_kv[NH * 8 * 16384];
__device__ float g_norm[16 * NH * 3];
__device__ __align__(1024) __nv_bfloat16 g_o[SEQ * DM];
__device__ __align__(1024) __nv_bfloat16 g_h[SEQ * DM];
__device__ float2 g_stat[SEQ];
__device__ unsigned long long g_cand[64];
__device__ __align__(16) float g_y[2 * DM];
__device__ unsigned int g_cnt;
__device__ __align__(16) float4 g_part[32 * 8 * 64];

#define TSTAMP(K, I)
#define TSTAMP0(K, I)
__device__ __forceinline__ uint32_t smem_u32(const void* p) { return (uint32_t)__cvta_generic_to_shared(p); }
__device__ __forceinline__ void wg_fence() { asm volatile("wgmma.fence.sync.aligned;" ::: "memory"); }
__device__ __forceinline__ void wg_commit() { asm volatile("wgmma.commit_group.sync.aligned;" ::: "memory"); }
template <int N> __device__ __forceinline__ void wg_wait() { asm volatile("wgmma.wait_group.sync.aligned %0;" ::"n"(N) : "memory"); }
template <int N> __device__ __forceinline__ void fence_regs(float (&r)[N]) {
#pragma unroll
    for (int i = 0; i < N; i++) asm volatile("" : "+f"(r[i])::"memory");
}
__device__ __forceinline__ uint64_t make_desc(uint32_t addr, uint32_t lbo, uint32_t sbo, uint32_t swz) {
    uint64_t d = 0;
    d |= (uint64_t)((addr & 0x3FFFF) >> 4);
    d |= (uint64_t)((lbo & 0x3FFFF) >> 4) << 16;
    d |= (uint64_t)((sbo & 0x3FFFF) >> 4) << 32;
    d |= (uint64_t)swz << 62;
    return d;
}
__device__ __forceinline__ void mbar_init(uint32_t bar, uint32_t cnt) {
    asm volatile("mbarrier.init.shared::cta.b64 [%0], %1;" ::"r"(bar), "r"(cnt) : "memory");
}
__device__ __forceinline__ void mbar_expect_tx(uint32_t bar, uint32_t bytes) {
    asm volatile("mbarrier.arrive.expect_tx.shared::cta.b64 _, [%0], %1;" ::"r"(bar), "r"(bytes) : "memory");
}
__device__ __forceinline__ void mbar_arrive(uint32_t bar) {
    asm volatile("mbarrier.arrive.shared::cta.b64 _, [%0];" ::"r"(bar) : "memory");
}
__device__ __forceinline__ void mbar_wait(uint32_t bar, uint32_t parity) {
    asm volatile(
        "{\n.reg .pred p;\nWAIT_%=:\n"
        "mbarrier.try_wait.parity.shared::cta.b64 p, [%0], %1;\n"
        "@p bra DONE_%=;\nbra WAIT_%=;\nDONE_%=:\n}\n" ::"r"(bar), "r"(parity) : "memory");
}
__device__ __forceinline__ void bulk_g2s(uint32_t dst, const void* src, uint32_t bytes, uint32_t bar) {
    asm volatile("cp.async.bulk.shared::cluster.global.mbarrier::complete_tx::bytes [%0], [%1], %2, [%3];" ::"r"(dst),
                 "l"(src), "r"(bytes), "r"(bar) : "memory");
}
__device__ __forceinline__ void bulk_s2g(void* dst, uint32_t src, uint32_t bytes) {
    asm volatile("cp.async.bulk.global.shared::cta.bulk_group [%0], [%1], %2;" ::"l"(dst), "r"(src), "r"(bytes) : "memory");
}
__device__ __forceinline__ void tma_load_2d(uint32_t dst, const CUtensorMap* tm, int c0, int c1, uint32_t bar) {
    asm volatile("cp.async.bulk.tensor.2d.shared::cluster.global.mbarrier::complete_tx::bytes [%0], [%1, {%3, %4}], [%2];" ::"r"(dst),
                 "l"(tm), "r"(bar), "r"(c0), "r"(c1) : "memory");
}
__device__ __forceinline__ void tma_load_2d_mc(uint32_t dst, const CUtensorMap* tm, int c0, int c1, uint32_t bar, uint16_t mask) {
    asm volatile("cp.async.bulk.tensor.2d.shared::cluster.global.mbarrier::complete_tx::bytes.multicast::cluster [%0], [%1, {%3, %4}], [%2], %5;" ::"r"(dst),
                 "l"(tm), "r"(bar), "r"(c0), "r"(c1), "h"(mask) : "memory");
}
__device__ __forceinline__ void mbar_arrive_cluster(uint32_t bar, uint32_t cta) {
    asm volatile("{\n.reg .b32 ra;\nmapa.shared::cluster.u32 ra, %0, %1;\nmbarrier.arrive.release.cluster.shared::cluster.b64 _, [ra];\n}" ::"r"(bar), "r"(cta) : "memory");
}
__device__ __forceinline__ void cluster_sync() {
    asm volatile("barrier.cluster.arrive.release.aligned;\nbarrier.cluster.wait.acquire.aligned;" ::: "memory");
}
__device__ __forceinline__ void prefetch_l2(const void* p, uint32_t bytes) {
    asm volatile("cp.async.bulk.prefetch.L2.global [%0], %1;" ::"l"(p), "r"(bytes) : "memory");
}
__device__ __forceinline__ void fence_proxy_async() { asm volatile("fence.proxy.async.shared::cta;" ::: "memory"); }
__device__ __forceinline__ void fence_barrier_init() { asm volatile("fence.mbarrier_init.release.cluster;" ::: "memory"); }
__device__ __forceinline__ void pdl_launch() { asm volatile("griddepcontrol.launch_dependents;" ::: "memory"); }
__device__ __forceinline__ void pdl_wait() { asm volatile("griddepcontrol.wait;" ::: "memory"); }
__device__ __forceinline__ void named_sync(int id, int n) { asm volatile("bar.sync %0, %1;" ::"r"(id), "r"(n) : "memory"); }
__device__ __forceinline__ void named_arrive(int id, int n) { asm volatile("bar.arrive %0, %1;" ::"r"(id), "r"(n) : "memory"); }

__device__ __forceinline__ float ex2f(float x) { float y; asm("ex2.approx.ftz.f32 %0, %1;" : "=f"(y) : "f"(x)); return y; }
__device__ __forceinline__ uint32_t pack_bf16(float lo, float hi) {
    uint32_t r; asm("cvt.rn.bf16x2.f32 %0, %1, %2;" : "=r"(r) : "f"(hi), "f"(lo)); return r;
}
__device__ __forceinline__ float bf_lo(uint32_t v) { return __uint_as_float(v << 16); }
__device__ __forceinline__ float bf_hi(uint32_t v) { return __uint_as_float(v & 0xFFFF0000u); }
__device__ __forceinline__ float rbf(float x) { return __bfloat162float(__float2bfloat16_rn(x)); }
__device__ __forceinline__ uint32_t fma_bf16x2(uint32_t a, uint32_t b, uint32_t c) {
    uint32_t r; asm("fma.rn.bf16x2 %0, %1, %2, %3;" : "=r"(r) : "r"(a), "r"(b), "r"(c)); return r;
}
__device__ __forceinline__ void stmatrix_x4(uint32_t addr, uint32_t r0, uint32_t r1, uint32_t r2, uint32_t r3) {
    asm volatile("stmatrix.sync.aligned.m8n8.x4.shared.b16 [%0], {%1, %2, %3, %4};" ::"r"(addr), "r"(r0), "r"(r1), "r"(r2), "r"(r3) : "memory");
}
__device__ __forceinline__ void stmatrix_x4_trans(uint32_t addr, uint32_t r0, uint32_t r1, uint32_t r2, uint32_t r3) {
    asm volatile("stmatrix.sync.aligned.m8n8.x4.trans.shared.b16 [%0], {%1, %2, %3, %4};" ::"r"(addr), "r"(r0), "r"(r1), "r"(r2), "r"(r3) : "memory");
}

__device__ __forceinline__ void wgmma_k1_n136(float (&d)[68], uint64_t desca, uint64_t descb, int scale_d) {
  asm volatile("{\n.reg .pred p;\nsetp.ne.b32 p, %70, 0;\n"
    "wgmma.mma_async.sync.aligned.m64n136k16.f32.bf16.bf16 "
    "{%0, %1, %2, %3, %4, %5, %6, %7, %8, %9, %10, %11, %12, %13, %14, %15, %16, %17, %18, %19, %20, %21, %22, %23, %24, %25, %26, %27, %28, %29, %30, %31, %32, %33, %34, %35, %36, %37, %38, %39, %40, %41, %42, %43, %44, %45, %46, %47, %48, %49, %50, %51, %52, %53, %54, %55, %56, %57, %58, %59, %60, %61, %62, %63, %64, %65, %66, %67}, "
    "%68, %69, p, 1, 1, 1, 0;\n}\n"
    : "+f"(d[0]), "+f"(d[1]), "+f"(d[2]), "+f"(d[3]), "+f"(d[4]), "+f"(d[5]), "+f"(d[6]), "+f"(d[7]), "+f"(d[8]), "+f"(d[9]), "+f"(d[10]), "+f"(d[11]), "+f"(d[12]), "+f"(d[13]), "+f"(d[14]), "+f"(d[15]), "+f"(d[16]), "+f"(d[17]), "+f"(d[18]), "+f"(d[19]), "+f"(d[20]), "+f"(d[21]), "+f"(d[22]), "+f"(d[23]), "+f"(d[24]), "+f"(d[25]), "+f"(d[26]), "+f"(d[27]), "+f"(d[28]), "+f"(d[29]), "+f"(d[30]), "+f"(d[31]), "+f"(d[32]), "+f"(d[33]), "+f"(d[34]), "+f"(d[35]), "+f"(d[36]), "+f"(d[37]), "+f"(d[38]), "+f"(d[39]), "+f"(d[40]), "+f"(d[41]), "+f"(d[42]), "+f"(d[43]), "+f"(d[44]), "+f"(d[45]), "+f"(d[46]), "+f"(d[47]), "+f"(d[48]), "+f"(d[49]), "+f"(d[50]), "+f"(d[51]), "+f"(d[52]), "+f"(d[53]), "+f"(d[54]), "+f"(d[55]), "+f"(d[56]), "+f"(d[57]), "+f"(d[58]), "+f"(d[59]), "+f"(d[60]), "+f"(d[61]), "+f"(d[62]), "+f"(d[63]), "+f"(d[64]), "+f"(d[65]), "+f"(d[66]), "+f"(d[67])
    : "l"(desca), "l"(descb), "r"(scale_d));
}
__device__ __forceinline__ void wgmma_qk_n64(float (&d)[32], uint32_t a0, uint32_t a1, uint32_t a2, uint32_t a3, uint64_t descb) {
  asm volatile("{\n.reg .pred p;\nsetp.ne.b32 p, 0, 0;\n"
    "wgmma.mma_async.sync.aligned.m64n64k16.f32.bf16.bf16 "
    "{%0, %1, %2, %3, %4, %5, %6, %7, %8, %9, %10, %11, %12, %13, %14, %15, %16, %17, %18, %19, %20, %21, %22, %23, %24, %25, %26, %27, %28, %29, %30, %31}, "
    "{%32, %33, %34, %35}, %36, p, 1, 1, 0;\n}\n"
    : "=f"(d[0]), "=f"(d[1]), "=f"(d[2]), "=f"(d[3]), "=f"(d[4]), "=f"(d[5]), "=f"(d[6]), "=f"(d[7]), "=f"(d[8]), "=f"(d[9]), "=f"(d[10]), "=f"(d[11]), "=f"(d[12]), "=f"(d[13]), "=f"(d[14]), "=f"(d[15]), "=f"(d[16]), "=f"(d[17]), "=f"(d[18]), "=f"(d[19]), "=f"(d[20]), "=f"(d[21]), "=f"(d[22]), "=f"(d[23]), "=f"(d[24]), "=f"(d[25]), "=f"(d[26]), "=f"(d[27]), "=f"(d[28]), "=f"(d[29]), "=f"(d[30]), "=f"(d[31])
    : "r"(a0), "r"(a1), "r"(a2), "r"(a3), "l"(descb));
}
__device__ __forceinline__ void wgmma_pv_n24(float (&d)[12], uint32_t a0, uint32_t a1, uint32_t a2, uint32_t a3, uint64_t descb) {
  asm volatile("{\n.reg .pred p;\nsetp.eq.b32 p, 0, 0;\n"
    "wgmma.mma_async.sync.aligned.m64n24k16.f32.bf16.bf16 "
    "{%0, %1, %2, %3, %4, %5, %6, %7, %8, %9, %10, %11}, "
    "{%12, %13, %14, %15}, %16, p, 1, 1, 1;\n}\n"
    : "+f"(d[0]), "+f"(d[1]), "+f"(d[2]), "+f"(d[3]), "+f"(d[4]), "+f"(d[5]), "+f"(d[6]), "+f"(d[7]), "+f"(d[8]), "+f"(d[9]), "+f"(d[10]), "+f"(d[11])
    : "r"(a0), "r"(a1), "r"(a2), "r"(a3), "l"(descb));
}
__device__ __forceinline__ void wgmma_k3_n64(float (&d)[32], uint64_t desca, uint64_t descb, int scale_d) {
  asm volatile("{\n.reg .pred p;\nsetp.ne.b32 p, %34, 0;\n"
    "wgmma.mma_async.sync.aligned.m64n64k16.f32.bf16.bf16 "
    "{%0, %1, %2, %3, %4, %5, %6, %7, %8, %9, %10, %11, %12, %13, %14, %15, %16, %17, %18, %19, %20, %21, %22, %23, %24, %25, %26, %27, %28, %29, %30, %31}, "
    "%32, %33, p, 1, 1, 0, 1;\n}\n"
    : "+f"(d[0]), "+f"(d[1]), "+f"(d[2]), "+f"(d[3]), "+f"(d[4]), "+f"(d[5]), "+f"(d[6]), "+f"(d[7]), "+f"(d[8]), "+f"(d[9]), "+f"(d[10]), "+f"(d[11]), "+f"(d[12]), "+f"(d[13]), "+f"(d[14]), "+f"(d[15]), "+f"(d[16]), "+f"(d[17]), "+f"(d[18]), "+f"(d[19]), "+f"(d[20]), "+f"(d[21]), "+f"(d[22]), "+f"(d[23]), "+f"(d[24]), "+f"(d[25]), "+f"(d[26]), "+f"(d[27]), "+f"(d[28]), "+f"(d[29]), "+f"(d[30]), "+f"(d[31])
    : "l"(desca), "l"(descb), "r"(scale_d));
}

constexpr int K1_XS = 17408;
constexpr int K1_WS = 24576;
constexpr int K1_NST = 3;
constexpr int K1_OFF_W = 8 * K1_XS;
constexpr int K1_OFF_MISC = K1_OFF_W + K1_NST * K1_WS;
constexpr int K1_SMEM = K1_OFF_MISC + 2048 + 1024;
constexpr float QSCALE = 0.25f * 1.4426950408889634f;

__global__ void __cluster_dims__(2, 1, 1) __launch_bounds__(544, 1)
k1_qkv(const __grid_constant__ CUtensorMap tm_x, const __grid_constant__ CUtensorMap tm_w) {
    extern __shared__ uint8_t smem_raw[];
    const uint32_t sraw = smem_u32(smem_raw);
    const uint32_t sb = (sraw + 1023) & ~1023u;
    uint8_t* sp = smem_raw + (sb - sraw);
    const uint32_t xbar = sb + K1_OFF_MISC;
    const uint32_t wfull = xbar + 64;
    const uint32_t wempty = wfull + 32;
    float* s_m = (float*)(sp + K1_OFF_MISC + 256);
    float* s_r = s_m + 128;

    const int tid = threadIdx.x, warp = tid >> 5, lane = tid & 31;
    const int crank = blockIdx.x & 1;
    const int mt = (blockIdx.x >> 4) * 2 + crank, nt = (blockIdx.x >> 1) & 7;
    if (tid == 0) TSTAMP0(0, 0);
    pdl_launch();
    if (tid == 0) {
        for (int i = 0; i < 8; i++) mbar_init(xbar + 8 * i, 1);
        for (int i = 0; i < K1_NST; i++) { mbar_init(wfull + 8 * i, 1); mbar_init(wempty + 8 * i, 6); }
        fence_barrier_init();
    }
    if (tid < 512) {
        *(uint4*)(sp + (tid >> 6) * K1_XS + 16384 + (tid & 63) * 16) =
            make_uint4(0x3F803F80u, 0x3F803F80u, 0x3F803F80u, 0x3F803F80u);
    }
    if (blockIdx.x == 0) {
        for (int i = tid; i < 2 * DM; i += 544) g_y[i] = 0.f;
        if (tid == 0) g_cnt = 0;
    }
    if (tid < 128) g_part[blockIdx.x * 128 + tid] = make_float4(0.f, 0.f, 0.f, 0.f);
    fence_proxy_async();
    __syncthreads();
    cluster_sync();

    if (warp == 16) {
        if (lane == 0) {
            for (int kb = 0; kb < 8; kb++) {
                mbar_expect_tx(xbar + 8 * kb, 16384);
                tma_load_2d(sb + kb * K1_XS, &tm_x, kb * 64, mt * 128, xbar + 8 * kb);
                const int s = kb % K1_NST;
                if (kb >= K1_NST) continue;
                mbar_expect_tx(wfull + 8 * s, K1_WS);
                for (int p = 0; p < 3; p++)
                    tma_load_2d_mc(sb + K1_OFF_W + s * K1_WS + p * 8192 + crank * 4096, &tm_w, p * 512 + nt * 64, kb * 64 + crank * 32,
                                   wfull + 8 * s, (uint16_t)3);
            }
            for (int kb = K1_NST; kb < 8; kb++) {
                const int s = kb % K1_NST;
                mbar_wait(wempty + 8 * s, ((kb / K1_NST) - 1) & 1);
                mbar_expect_tx(wfull + 8 * s, K1_WS);
                for (int p = 0; p < 3; p++)
                    tma_load_2d_mc(sb + K1_OFF_W + s * K1_WS + p * 8192 + crank * 4096, &tm_w, p * 512 + nt * 64, kb * 64 + crank * 32,
                                   wfull + 8 * s, (uint16_t)3);
            }
        }
    } else if (warp >= 12) {
        const int r = tid - 384;
        float x0 = 0.f, s1 = 0.f, s2 = 0.f;
#pragma unroll 1
        for (int kb = 0; kb < 8; kb++) {
            mbar_wait(xbar + 8 * kb, 0);
            const uint8_t* rowp = sp + kb * K1_XS + r * 128;
            if (kb == 0) x0 = bf_lo(*(const uint32_t*)(rowp + ((r & 7) << 4)));
#pragma unroll
            for (int c = 0; c < 8; c++) {
                const uint4 v = *(const uint4*)(rowp + ((c ^ (r & 7)) << 4));
                const uint32_t w[4] = {v.x, v.y, v.z, v.w};
#pragma unroll
                for (int i = 0; i < 4; i++) {
                    const float a = bf_lo(w[i]) - x0, b = bf_hi(w[i]) - x0;
                    s1 += a; s2 = fmaf(a, a, s2);
                    s1 += b; s2 = fmaf(b, b, s2);
                }
            }
        }
        const float md = s1 * (1.f / DM);
        const float mean = x0 + md;
        const float var = fmaxf(s2 * (1.f / DM) - md * md, 0.f);
        const float den = rbf(sqrtf(rbf(rbf(var) + 1e-5f)));
        s_m[r] = rbf(mean);
        s_r[r] = 1.f / den;
        named_arrive(1, 512);
    } else {
        const int part = warp >> 2, hw = warp & 3;
        float acc[68];
#pragma unroll
        for (int i = 0; i < 68; i++) acc[i] = 0.f;
        fence_regs(acc);
#pragma unroll 1
        for (int kb = 0; kb < 8; kb++) {
            const int s = kb % K1_NST;
            mbar_wait(xbar + 8 * kb, 0);
            mbar_wait(wfull + 8 * s, (kb / K1_NST) & 1);
            const uint64_t da = make_desc(sb + K1_OFF_W + s * K1_WS + part * 8192, 1024, 1024, 1);
            const uint64_t db = make_desc(sb + kb * K1_XS, 16, 1024, 1);
            wg_fence();
#pragma unroll
            for (int k = 0; k < 4; k++) wgmma_k1_n136(acc, da + k * 128, db + k * 2, (kb | k) != 0);
            wg_commit();
            if (kb > 0) {
                wg_wait<1>();
                if (kb <= 8 - K1_NST && (tid & 127) < 2) mbar_arrive_cluster(wempty + 8 * ((kb - 1) % K1_NST), tid & 1);
            }
        }
        wg_wait<0>();
        fence_regs(acc);
        if (tid == 0) TSTAMP0(0, 1);
        named_sync(1, 512);
        if (tid == 0) TSTAMP0(0, 2);

        const int t = lane & 3;
        const float cs0 = acc[64], cs1 = acc[66];
        const float sc = (part == 0) ? QSCALE : 1.f;
        const uint32_t stg = sb + K1_OFF_W + (hw >> 1) * K1_WS + part * 8192 + (hw & 1) * 4096;
        const uint32_t st_addr = stg + ((lane >> 3) & 1) * 2048 + ((lane >> 4) * 8 + (lane & 7)) * 16;
#pragma unroll
        for (int j = 0; j < 16; j += 2) {
            uint32_t rr[4];
#pragma unroll
            for (int u = 0; u < 2; u++) {
                const int jj = j + u;
                const float2 m2 = *(const float2*)(s_m + 8 * jj + 2 * t);
                const float2 r2 = *(const float2*)(s_r + 8 * jj + 2 * t);
                const float ra = r2.x * sc, rb = r2.y * sc;
                rr[2 * u] = pack_bf16((acc[4 * jj] - m2.x * cs0) * ra, (acc[4 * jj + 1] - m2.y * cs0) * rb);
                rr[2 * u + 1] = pack_bf16((acc[4 * jj + 2] - m2.x * cs1) * ra, (acc[4 * jj + 3] - m2.y * cs1) * rb);
            }
            stmatrix_x4_trans(st_addr + j * 128, rr[0], rr[1], rr[2], rr[3]);
        }
        __syncwarp();
        float nmax = 0.f;
#pragma unroll
        for (int i = 0; i < 4; i++) {
            const int tok = lane + 32 * i;
            const uint4 a = *(const uint4*)(sp + (stg - sb) + tok * 16);
            const uint4 b = *(const uint4*)(sp + (stg - sb) + 2048 + tok * 16);
            const uint32_t w[8] = {a.x, a.y, a.z, a.w, b.x, b.y, b.z, b.w};
            float n2 = 0.f;
#pragma unroll
            for (int q = 0; q < 8; q++) {
                const float lo = bf_lo(w[q]), hi = bf_hi(w[q]);
                n2 = fmaf(lo, lo, n2); n2 = fmaf(hi, hi, n2);
            }
            nmax = (n2 > nmax || n2 != n2) ? n2 : nmax;
        }
#pragma unroll
        for (int o = 16; o > 0; o >>= 1) {
            const float v = __shfl_xor_sync(0xffffffffu, nmax, o);
            nmax = (v > nmax || v != v) ? v : nmax;
        }
        fence_proxy_async();
        __syncwarp();
        if (lane == 0) {
            const int head = nt * 4 + hw;
            g_norm[(mt * NH + head) * 3 + part] = nmax;
            uint8_t* dst;
            uint32_t hstride;
            if (part == 0) { dst = g_q + (size_t)head * 65536 + mt * 2048; hstride = 32768; }
            else { dst = g_kv + (size_t)head * 131072 + (mt >> 1) * 16384 + (part - 1) * 8192 + (mt & 1) * 2048; hstride = 4096; }
            bulk_s2g(dst, stg, 2048);
            bulk_s2g(dst + hstride, stg + 2048, 2048);
            asm volatile("cp.async.bulk.commit_group;" ::: "memory");
            asm volatile("cp.async.bulk.wait_group.read 0;" ::: "memory");
            if (tid == 0) TSTAMP0(0, 3);
        }
    }
}

constexpr int K2_CH_G = 16384, K2_CH_S = 20480, K2_NCH = 8;
constexpr int K2_SMEM = K2_NCH * K2_CH_S + 128 + 1024;

__device__ __forceinline__ uint32_t exp2_pair_poly(float s0, float s1) {
    const float KB = 65536.0f + 127.0f;
    const float t0 = s0 + KB, t1 = s1 + KB;
    const uint32_t w = __byte_perm(__float_as_uint(t0), __float_as_uint(t1), 0x5410);
    uint32_t z;
    asm("lop3.b32 %0, %1, %2, %3, 0xEA;" : "=r"(z) : "r"(w), "r"(0x007F007Fu), "r"(0x3F803F80u));
    uint32_t p = fma_bf16x2(0x3eab3eabu, z, 0xbc73bc73u);
    p = fma_bf16x2(p, z, 0x3f2f3f2fu);
    return p + w - z;
}
constexpr uint32_t K2_EMASK = 0x5757u;
template <int LO, int HI>
__device__ __forceinline__ void softmax_part(const float (&s)[32], uint32_t (&p)[16]) {
#pragma unroll
    for (int i = LO; i < HI; i++) {
        if ((K2_EMASK >> i) & 1) p[i] = exp2_pair_poly(s[2 * i], s[2 * i + 1]);
        else p[i] = pack_bf16(ex2f(s[2 * i]), ex2f(s[2 * i + 1]));
    }
}
#define K2_PV(P, OFF)                                                                              \
    _Pragma("unroll") for (int kk = 0; kk < 4; kk++)                                               \
        wgmma_pv_n24(o, P[4 * kk], P[4 * kk + 1], P[4 * kk + 2], P[4 * kk + 3], dv + ((OFF) + kk * 16));

__global__ void __launch_bounds__(512, 1)
k2_attn(const uint8_t* __restrict__ wo, const uint8_t* __restrict__ w_gate, const uint8_t* __restrict__ w_up, const uint8_t* __restrict__ w_down) {
    extern __shared__ uint8_t smem_raw[];
    const uint32_t sraw = smem_u32(smem_raw);
    const uint32_t sb = (sraw + 1023) & ~1023u;
    uint8_t* sp = smem_raw + (sb - sraw);
    const uint32_t bars = sb + K2_NCH * K2_CH_S;
    const int tid = threadIdx.x;
    const int head = blockIdx.x >> 2, quarter = blockIdx.x & 3;
    if (tid == 0) TSTAMP0(1, 0);
    pdl_launch();
    if (tid == 0) {
        for (int c = 0; c < K2_NCH; c++) mbar_init(bars + 8 * c, 1);
        fence_barrier_init();
    }
    if (tid == 32) {
        prefetch_l2(wo + blockIdx.x * 4096, 4096);
        prefetch_l2(w_gate + blockIdx.x * 14336, 14336);
        prefetch_l2(w_up + blockIdx.x * 14336, 14336);
        prefetch_l2(w_down + blockIdx.x * 14336, 14336);
    }
    for (int i = tid; i < K2_NCH * 256; i += 512)
        *(uint4*)(sp + (i >> 8) * K2_CH_S + 16384 + (i & 255) * 16) =
            make_uint4(0x3F803F80u, 0x3F803F80u, 0x3F803F80u, 0x3F803F80u);
    fence_proxy_async();
    __syncthreads();
    pdl_wait();
    if (tid == 0) TSTAMP0(1, 1);
    if (tid == 0) {
        const uint8_t* src = g_kv + (size_t)head * (K2_NCH * K2_CH_G);
        for (int c = 0; c < K2_NCH; c++) {
            mbar_expect_tx(bars + 8 * c, K2_CH_G);
            bulk_g2s(sb + c * K2_CH_S, src + c * K2_CH_G, K2_CH_G, bars + 8 * c);
        }
    }
    const int wg = tid >> 7, warp = (tid >> 5) & 3, lane = tid & 31, g = lane >> 2, t = lane & 3;

    bool fast;
    {
        const int m16 = lane & 15;
        float kn = g_norm[(m16 * NH + head) * 3 + 1];
        float vn = g_norm[(m16 * NH + head) * 3 + 2];
        float qn = g_norm[((quarter * 4 + (lane & 3)) * NH + head) * 3 + 0];
        bool bad = !(kn < 1e30f) || !(vn < 1e30f) || !(qn < 1e30f);
#pragma unroll
        for (int o = 8; o > 0; o >>= 1) {
            kn = fmaxf(kn, __shfl_xor_sync(0xffffffffu, kn, o));
            qn = fmaxf(qn, __shfl_xor_sync(0xffffffffu, qn, o));
        }
        bad = __any_sync(0xffffffffu, bad);
        fast = !bad && (qn * kn <= 3500.f);
    }
    const uint64_t dk0 = make_desc(sb, 4096, 128, 0);
    const uint64_t dv0 = make_desc(sb + 8192, 128, 4096, 0);

#pragma unroll 1
    for (int pass = 0; pass < 2; pass++) {
        const int row0 = quarter * 512 + pass * 256 + wg * 64 + warp * 16 + g;
        uint32_t qa[4];
        {
            const uint8_t* qb = g_q + (size_t)head * 65536 + row0 * 16 + t * 4;
            qa[0] = *(const uint32_t*)(qb);
            qa[1] = *(const uint32_t*)(qb + 128);
            qa[2] = *(const uint32_t*)(qb + 32768);
            qa[3] = *(const uint32_t*)(qb + 32768 + 128);
        }
        float o[12];
#pragma unroll
        for (int i = 0; i < 12; i++) o[i] = 0.f;
        fence_regs(o);
        if (fast) {
#pragma unroll 1
            for (int c = 0; c < K2_NCH; c++) {
                const uint64_t dk = dk0 + (uint64_t)(c * (K2_CH_S >> 4));
                const uint64_t dv = dv0 + (uint64_t)(c * (K2_CH_S >> 4));
                float s0[32], s1[32], s2[32], s3[32];
                uint32_t p0[16], p1[16], p2[16], p3[16];
                mbar_wait(bars + 8 * c, 0);
                wg_wait<1>();
                wg_fence();
                wgmma_qk_n64(s0, qa[0], qa[1], qa[2], qa[3], dk);
                wg_commit();
                wg_wait<1>();
                wg_fence();
                wgmma_qk_n64(s1, qa[0], qa[1], qa[2], qa[3], dk + 64);
                wg_commit();
                wg_wait<1>();
                fence_regs(s0);
                softmax_part<0, 16>(s0, p0);
                wg_fence();
                K2_PV(p0, 0);
                wg_commit();
                wg_wait<1>();
                fence_regs(s1);
                softmax_part<0, 8>(s1, p1);
                wg_wait<0>();
                wg_fence();
                wgmma_qk_n64(s2, qa[0], qa[1], qa[2], qa[3], dk + 128);
                wg_commit();
                softmax_part<8, 16>(s1, p1);
                wg_fence();
                K2_PV(p1, 64);
                wg_commit();
                wg_wait<1>();
                fence_regs(s2);
                softmax_part<0, 8>(s2, p2);
                wg_wait<0>();
                wg_fence();
                wgmma_qk_n64(s3, qa[0], qa[1], qa[2], qa[3], dk + 192);
                wg_commit();
                softmax_part<8, 16>(s2, p2);
                wg_fence();
                K2_PV(p2, 128);
                wg_commit();
                wg_wait<1>();
                fence_regs(s3);
                softmax_part<0, 16>(s3, p3);
                wg_fence();
                K2_PV(p3, 192);
                wg_commit();
            }
            wg_wait<0>();
            fence_regs(o);
        } else {
            float m0 = -INFINITY, m1 = -INFINITY;
#pragma unroll 1
            for (int b = 0; b < 32; b++) {
                const int c = b >> 2;
                const uint64_t dk = dk0 + (uint64_t)(c * (K2_CH_S >> 4) + (b & 3) * 64);
                const uint64_t dv = dv0 + (uint64_t)(c * (K2_CH_S >> 4) + (b & 3) * 64);
                float s[32];
                uint32_t p[16];
                mbar_wait(bars + 8 * c, 0);
                wg_fence();
                wgmma_qk_n64(s, qa[0], qa[1], qa[2], qa[3], dk);
                wg_commit();
                wg_wait<0>();
                fence_regs(s);
                float x0 = s[0], x1 = s[2];
#pragma unroll
                for (int j = 0; j < 8; j++) {
                    x0 = fmaxf(x0, fmaxf(s[4 * j], s[4 * j + 1]));
                    x1 = fmaxf(x1, fmaxf(s[4 * j + 2], s[4 * j + 3]));
                }
                x0 = fmaxf(x0, __shfl_xor_sync(0xffffffffu, x0, 1));
                x0 = fmaxf(x0, __shfl_xor_sync(0xffffffffu, x0, 2));
                x1 = fmaxf(x1, __shfl_xor_sync(0xffffffffu, x1, 1));
                x1 = fmaxf(x1, __shfl_xor_sync(0xffffffffu, x1, 2));
                const float n0 = fmaxf(m0, x0), n1 = fmaxf(m1, x1);
                const float c0 = ex2f(m0 - n0), c1 = ex2f(m1 - n1);
                m0 = n0; m1 = n1;
#pragma unroll
                for (int j = 0; j < 3; j++) {
                    o[4 * j] *= c0; o[4 * j + 1] *= c0; o[4 * j + 2] *= c1; o[4 * j + 3] *= c1;
                }
#pragma unroll
                for (int j = 0; j < 8; j++) {
                    p[2 * j] = pack_bf16(ex2f(s[4 * j] - n0), ex2f(s[4 * j + 1] - n0));
                    p[2 * j + 1] = pack_bf16(ex2f(s[4 * j + 2] - n1), ex2f(s[4 * j + 3] - n1));
                }
                fence_regs(o);
                wg_fence();
                K2_PV(p, 0);
                wg_commit();
                wg_wait<0>();
                fence_regs(o);
            }
        }
        const float inv0 = 1.f / o[8], inv1 = 1.f / o[10];
        uint32_t* out0 = (uint32_t*)(g_o + (size_t)row0 * DM + head * 16);
        uint32_t* out1 = (uint32_t*)(g_o + (size_t)(row0 + 8) * DM + head * 16);
        out0[t] = pack_bf16(o[0] * inv0, o[1] * inv0);
        out0[4 + t] = pack_bf16(o[4] * inv0, o[5] * inv0);
        out1[t] = pack_bf16(o[2] * inv1, o[3] * inv1);
        out1[4 + t] = pack_bf16(o[6] * inv1, o[7] * inv1);
        if (tid == 0) TSTAMP0(1, 2 + pass);
    }
}

constexpr int K3_OFF_W = 65536;
constexpr int K3_OFF_MISC = K3_OFF_W + 131072;
constexpr int K3_SMEM = K3_OFF_MISC + 128 + 512 + 1024;

__device__ __forceinline__ unsigned long long make_key(float r_bf, int idx) {
    uint32_t u = __float_as_uint(r_bf);
    u = (u & 0x80000000u) ? ~u : (u | 0x80000000u);
    return ((unsigned long long)u << 32) | (uint32_t)(0x7FFFFFFF - idx);
}
__device__ __forceinline__ float key_value(unsigned long long k) {
    uint32_t u = (uint32_t)(k >> 32);
    u = (u & 0x80000000u) ? (u & 0x7FFFFFFFu) : ~u;
    return __uint_as_float(u);
}
__device__ __forceinline__ int key_index(unsigned long long k) { return 0x7FFFFFFF - (int)(uint32_t)k; }
__device__ __forceinline__ void warp_top2(unsigned long long& a, unsigned long long& b) {
#pragma unroll
    for (int o = 16; o > 0; o >>= 1) {
        const unsigned long long c = __shfl_xor_sync(0xffffffffu, a, o);
        const unsigned long long d = __shfl_xor_sync(0xffffffffu, b, o);
        const unsigned long long hi = a > c ? a : c, lo = a > c ? c : a;
        const unsigned long long m = b > d ? b : d;
        a = hi;
        b = lo > m ? lo : m;
    }
}

__global__ void __launch_bounds__(288, 1)
k3_proj(const __grid_constant__ CUtensorMap tm_o, const __grid_constant__ CUtensorMap tm_wo,
        const __nv_bfloat16* __restrict__ x, const __nv_bfloat16* __restrict__ w_r, __nv_bfloat16* __restrict__ out) {
    extern __shared__ uint8_t smem_raw[];
    const uint32_t sraw = smem_u32(smem_raw);
    const uint32_t sb = (sraw + 1023) & ~1023u;
    uint8_t* sp = smem_raw + (sb - sraw);
    const uint32_t obar = sb + K3_OFF_MISC;
    const uint32_t wbar = obar + 64;
    unsigned long long* s_key = (unsigned long long*)(sp + K3_OFF_MISC + 128);

    const int tid = threadIdx.x, warp = tid >> 5, lane = tid & 31;
    const int mt = blockIdx.x >> 2, nt = blockIdx.x & 3;
    if (tid == 0) TSTAMP0(2, 0);

    pdl_launch();
    if (tid == 0) {
        for (int i = 0; i < 16; i++) mbar_init(obar + 8 * i, 1);
        fence_barrier_init();
    }
    __syncthreads();

    if (warp == 8) {
        if (lane == 0) {
            for (int kb = 0; kb < 8; kb++) {
                mbar_expect_tx(wbar + 8 * kb, 16384);
                tma_load_2d(sb + K3_OFF_W + kb * 16384, &tm_wo, nt * 128, kb * 64, wbar + 8 * kb);
                tma_load_2d(sb + K3_OFF_W + kb * 16384 + 8192, &tm_wo, nt * 128 + 64, kb * 64, wbar + 8 * kb);
            }
            pdl_wait();
            TSTAMP0(2, 1);
            for (int kb = 0; kb < 8; kb++) {
                mbar_expect_tx(obar + 8 * kb, 8192);
                tma_load_2d(sb + kb * 8192, &tm_o, kb * 64, mt * 64, obar + 8 * kb);
            }
        }
        return;
    }
    const int wg = warp >> 2, wi = warp & 3, g = lane >> 2, t = lane & 3;
    const int r0 = mt * 64 + wi * 16 + g;
    const int cb = nt * 128 + wg * 64;
    uint32_t xr[16], wr[8];
#pragma unroll
    for (int j = 0; j < 8; j++) {
        xr[2 * j] = *(const uint32_t*)(x + (size_t)r0 * DM + cb + 8 * j + 2 * t);
        xr[2 * j + 1] = *(const uint32_t*)(x + (size_t)(r0 + 8) * DM + cb + 8 * j + 2 * t);
        wr[j] = *(const uint32_t*)(w_r + cb + 8 * j + 2 * t);
    }
    float wsum = 0.f;
    {
        const uint4 a = *(const uint4*)(w_r + lane * 16), b = *(const uint4*)(w_r + lane * 16 + 8);
        const uint32_t w[8] = {a.x, a.y, a.z, a.w, b.x, b.y, b.z, b.w};
#pragma unroll
        for (int i = 0; i < 8; i++) wsum += bf_lo(w[i]) + bf_hi(w[i]);
#pragma unroll
        for (int o = 16; o > 0; o >>= 1) wsum += __shfl_xor_sync(0xffffffffu, wsum, o);
    }
    float acc[32];
#pragma unroll
    for (int i = 0; i < 32; i++) acc[i] = 0.f;
    fence_regs(acc);
#pragma unroll 1
    for (int kb = 0; kb < 8; kb++) {
        mbar_wait(wbar + 8 * kb, 0);
        mbar_wait(obar + 8 * kb, 0);
        const uint64_t da = make_desc(sb + kb * 8192, 16, 1024, 1);
        const uint64_t db = make_desc(sb + K3_OFF_W + kb * 16384 + wg * 8192, 1024, 1024, 1);
        wg_fence();
#pragma unroll
        for (int k = 0; k < 4; k++) wgmma_k3_n64(acc, da + k * 2, db + k * 128, (kb | k) != 0);
        wg_commit();
    }
    wg_wait<0>();
    fence_regs(acc);
    if (tid == 0) TSTAMP0(2, 2);
    float hv[32];
    float s0 = 0.f, s1 = 0.f, d0 = 0.f, d1 = 0.f;
#pragma unroll
    for (int j = 0; j < 8; j++) {
        hv[4 * j] = rbf(bf_lo(xr[2 * j]) + rbf(acc[4 * j]));
        hv[4 * j + 1] = rbf(bf_hi(xr[2 * j]) + rbf(acc[4 * j + 1]));
        hv[4 * j + 2] = rbf(bf_lo(xr[2 * j + 1]) + rbf(acc[4 * j + 2]));
        hv[4 * j + 3] = rbf(bf_hi(xr[2 * j + 1]) + rbf(acc[4 * j + 3]));
        const float wl = bf_lo(wr[j]), wh = bf_hi(wr[j]);
        s0 += hv[4 * j] + hv[4 * j + 1];
        s1 += hv[4 * j + 2] + hv[4 * j + 3];
        d0 = fmaf(hv[4 * j], wl, fmaf(hv[4 * j + 1], wh, d0));
        d1 = fmaf(hv[4 * j + 2], wl, fmaf(hv[4 * j + 3], wh, d1));
    }
#pragma unroll
    for (int o = 1; o < 4; o <<= 1) {
        s0 += __shfl_xor_sync(0xffffffffu, s0, o);
        s1 += __shfl_xor_sync(0xffffffffu, s1, o);
        d0 += __shfl_xor_sync(0xffffffffu, d0, o);
        d1 += __shfl_xor_sync(0xffffffffu, d1, o);
    }
    const float mu0 = s0 * (1.f / 64), mu1 = s1 * (1.f / 64);
    float q0 = 0.f, q1 = 0.f;
#pragma unroll
    for (int j = 0; j < 8; j++) {
        float a = hv[4 * j] - mu0, b = hv[4 * j + 1] - mu0, c = hv[4 * j + 2] - mu1, d = hv[4 * j + 3] - mu1;
        q0 = fmaf(a, a, fmaf(b, b, q0));
        q1 = fmaf(c, c, fmaf(d, d, q1));
    }
#pragma unroll
    for (int o = 1; o < 4; o <<= 1) {
        q0 += __shfl_xor_sync(0xffffffffu, q0, o);
        q1 += __shfl_xor_sync(0xffffffffu, q1, o);
    }
    float4* part = g_part + (size_t)mt * 512 + wi * 16 + g;
    if (t < 2) {
        float4* dst = part + (nt * 2 + wg) * 64 + t * 8;
        const float a = t ? mu1 : mu0, b = t ? q1 : q0, c = t ? d1 : d0;
        asm volatile("st.relaxed.gpu.global.v4.f32 [%0], {%1, %2, %3, %4};" ::"l"(dst), "f"(a), "f"(b), "f"(c), "f"(1.0f) : "memory");
    }
    named_sync(2, 256);
    const uint32_t stg_o = sb + warp * 4096;
    const uint32_t stg_h = stg_o + 2048;
    const int srow = (lane & 7) + ((lane >> 3) & 1) * 8;
    const int sj = lane >> 4;
#pragma unroll
    for (int j = 0; j < 8; j += 2) {
        const uint32_t off = srow * 128 + (((j + sj) ^ (srow & 7)) << 4);
        stmatrix_x4(stg_h + off, pack_bf16(hv[4 * j], hv[4 * j + 1]), pack_bf16(hv[4 * j + 2], hv[4 * j + 3]),
                    pack_bf16(hv[4 * j + 4], hv[4 * j + 5]), pack_bf16(hv[4 * j + 6], hv[4 * j + 7]));
    }
    __syncwarp();
#pragma unroll
    for (int i = 0; i < 4; i++) {
        const int row = i * 4 + (lane >> 3), ch = lane & 7;
        const uint4 vh = *(const uint4*)(sp + warp * 4096 + 2048 + row * 128 + ((ch ^ (row & 7)) << 4));
        *(uint4*)(g_h + (size_t)(mt * 64 + wi * 16 + row) * DM + cb + ch * 8) = vh;
    }
    float mean[2], den[2], rr[2];
    {
        float4 v[4];
        int spins = 0;
        while (true) {
#pragma unroll
            for (int i = 0; i < 4; i++) {
                const float4* p = part + (t + (i & 1) * 4) * 64 + (i >> 1) * 8;
                asm volatile("ld.relaxed.gpu.global.v4.f32 {%0, %1, %2, %3}, [%4];" : "=f"(v[i].x), "=f"(v[i].y), "=f"(v[i].z), "=f"(v[i].w) : "l"(p) : "memory");
            }
            const bool ok = (v[0].w != 0.f) && (v[1].w != 0.f) && (v[2].w != 0.f) && (v[3].w != 0.f);
            if (__all_sync(0xffffffffu, ok) || ++spins > (1 << 22)) break;
        }
#pragma unroll
        for (int u = 0; u < 2; u++) {
            float mu = v[2 * u].x + v[2 * u + 1].x, m2 = v[2 * u].y + v[2 * u + 1].y, hw = v[2 * u].z + v[2 * u + 1].z;
#pragma unroll
            for (int o = 1; o < 4; o <<= 1) {
                mu += __shfl_xor_sync(0xffffffffu, mu, o);
                m2 += __shfl_xor_sync(0xffffffffu, m2, o);
                hw += __shfl_xor_sync(0xffffffffu, hw, o);
            }
            mu *= 0.125f;
            const float da = v[2 * u].x - mu, db = v[2 * u + 1].x - mu;
            float dd = 64.f * (da * da + db * db);
#pragma unroll
            for (int o = 1; o < 4; o <<= 1) dd += __shfl_xor_sync(0xffffffffu, dd, o);
            m2 += dd;
            mean[u] = rbf(mu);
            den[u] = rbf(sqrtf(rbf(rbf(m2 * (1.f / DM)) + 1e-5f)));
            rr[u] = rbf((hw - mean[u] * wsum) / den[u]);
        }
    }
    if (tid == 0) TSTAMP0(2, 3);
    const float i0 = 1.f / den[0], i1 = 1.f / den[1];
#pragma unroll
    for (int j = 0; j < 8; j += 2) {
        uint32_t ro[4];
#pragma unroll
        for (int u = 0; u < 2; u++) {
            const int jj = j + u;
            const float a = hv[4 * jj], b = hv[4 * jj + 1], c = hv[4 * jj + 2], d = hv[4 * jj + 3];
            const float na = rbf(rbf(a - mean[0]) * i0), nb = rbf(rbf(b - mean[0]) * i0);
            const float nc = rbf(rbf(c - mean[1]) * i1), nd = rbf(rbf(d - mean[1]) * i1);
            ro[2 * u] = pack_bf16(a + na, b + nb);
            ro[2 * u + 1] = pack_bf16(c + nc, d + nd);
        }
        const uint32_t off = srow * 128 + (((j + sj) ^ (srow & 7)) << 4);
        stmatrix_x4(stg_o + off, ro[0], ro[1], ro[2], ro[3]);
    }
    __syncwarp();
#pragma unroll
    for (int i = 0; i < 4; i++) {
        const int row = i * 4 + (lane >> 3), ch = lane & 7;
        const uint4 vo = *(const uint4*)(sp + warp * 4096 + row * 128 + ((ch ^ (row & 7)) << 4));
        *(uint4*)(out + (size_t)(mt * 64 + wi * 16 + row) * DM + cb + ch * 8) = vo;
    }
    if (tid == 0) TSTAMP0(2, 4);
    if (nt == 0 && wg == 0) {
        if (t == 0) {
            g_stat[r0] = make_float2(mean[0], den[0]);
            g_stat[r0 + 8] = make_float2(mean[1], den[1]);
            s_key[wi * 16 + g] = make_key(rr[0], r0);
            s_key[wi * 16 + g + 8] = make_key(rr[1], r0 + 8);
        }
        named_sync(1, 128);
        if (warp == 0) {
            unsigned long long a = s_key[lane], b = s_key[lane + 32];
            if (b > a) { const unsigned long long c = a; a = b; b = c; }
            warp_top2(a, b);
            if (lane == 0) { g_cand[mt * 2] = a; g_cand[mt * 2 + 1] = b; }
        }
    }
}

__global__ void __launch_bounds__(256)
k4_moe(const __nv_bfloat16* __restrict__ w_gate, const __nv_bfloat16* __restrict__ w_up,
       const __nv_bfloat16* __restrict__ w_down, __nv_bfloat16* __restrict__ out) {
    __shared__ float s_gu[2][32];
    const int tid = threadIdx.x, warp = tid >> 5, lane = tid & 31;
    const int f0 = blockIdx.x * 16;
    if (tid == 0) TSTAMP0(3, 0);

    uint2 wgu[16];
    uint32_t wd[16];
    {
        const __nv_bfloat16* base = (warp < 4 ? w_gate : w_up) + (size_t)(16 * lane) * FF + f0 + (warp & 3) * 4;
#pragma unroll
        for (int k = 0; k < 16; k++) wgu[k] = __ldg((const uint2*)(base + (size_t)k * FF));
#pragma unroll
        for (int f = 0; f < 16; f++) wd[f] = __ldg((const uint32_t*)(w_down + (size_t)(f0 + f) * DM + 2 * tid));
    }
    pdl_wait();
    if (tid == 0) TSTAMP0(3, 1);

    unsigned long long ka = g_cand[2 * lane], kb = g_cand[2 * lane + 1];
    warp_top2(ka, kb);
    const int idx[2] = {key_index(ka), key_index(kb)};
    float acc[8];
    float hx[2][2], xo[2][2];
#pragma unroll
    for (int i = 0; i < 8; i++) acc[i] = 0.f;
#pragma unroll
    for (int u = 0; u < 2; u++) {
        const uint4* hp = (const uint4*)(g_h + (size_t)idx[u] * DM + 16 * lane);
        const uint4 ha = hp[0], hb = hp[1];
        const uint32_t ho = *(const uint32_t*)(g_h + (size_t)idx[u] * DM + 2 * tid);
        const float2 st = g_stat[idx[u]];
        const float inv = 1.f / st.y;
        const uint32_t hw[8] = {ha.x, ha.y, ha.z, ha.w, hb.x, hb.y, hb.z, hb.w};
#pragma unroll
        for (int k = 0; k < 8; k++) {
            const float x0 = rbf(rbf(bf_lo(hw[k]) - st.x) * inv), x1 = rbf(rbf(bf_hi(hw[k]) - st.x) * inv);
            const uint2 wa = wgu[2 * k], wb = wgu[2 * k + 1];
            acc[u * 4 + 0] = fmaf(x0, bf_lo(wa.x), fmaf(x1, bf_lo(wb.x), acc[u * 4 + 0]));
            acc[u * 4 + 1] = fmaf(x0, bf_hi(wa.x), fmaf(x1, bf_hi(wb.x), acc[u * 4 + 1]));
            acc[u * 4 + 2] = fmaf(x0, bf_lo(wa.y), fmaf(x1, bf_lo(wb.y), acc[u * 4 + 2]));
            acc[u * 4 + 3] = fmaf(x0, bf_hi(wa.y), fmaf(x1, bf_hi(wb.y), acc[u * 4 + 3]));
        }
        hx[u][0] = bf_lo(ho); hx[u][1] = bf_hi(ho);
        xo[u][0] = rbf(rbf(hx[u][0] - st.x) * inv); xo[u][1] = rbf(rbf(hx[u][1] - st.x) * inv);
    }
#define K4_STEP(O, N)                                                          \
    {                                                                          \
        const bool up = (lane & (O)) != 0;                                     \
        _Pragma("unroll") for (int i = 0; i < (N); i++) {                      \
            const float send = up ? acc[i] : acc[i + (N)];                     \
            const float keep = up ? acc[i + (N)] : acc[i];                     \
            acc[i] = keep + __shfl_xor_sync(0xffffffffu, send, (O));           \
        }                                                                      \
    }
    K4_STEP(16, 4) K4_STEP(8, 2) K4_STEP(4, 1)
    acc[0] += __shfl_xor_sync(0xffffffffu, acc[0], 2);
    acc[0] += __shfl_xor_sync(0xffffffffu, acc[0], 1);
    if ((lane & 3) == 0) {
        const int v = ((lane & 16) ? 4 : 0) + ((lane & 8) ? 2 : 0) + ((lane & 4) ? 1 : 0);
        s_gu[v >> 2][warp * 4 + (v & 3)] = acc[0];
    }
    __syncthreads();
    float y[2][2] = {{0.f, 0.f}, {0.f, 0.f}};
    {
        const int u = lane >> 4, c = lane & 15;
        const float gb = rbf(s_gu[u][c]);
        const float sg = rbf(gb / (1.f + __expf(-gb)));
        const float a = rbf(sg * rbf(s_gu[u][16 + c]));
#pragma unroll
        for (int f = 0; f < 16; f++) {
            const float a0 = __shfl_sync(0xffffffffu, a, f), a1 = __shfl_sync(0xffffffffu, a, 16 + f);
            const float w0 = bf_lo(wd[f]), w1 = bf_hi(wd[f]);
            y[0][0] = fmaf(a0, w0, y[0][0]); y[0][1] = fmaf(a0, w1, y[0][1]);
            y[1][0] = fmaf(a1, w0, y[1][0]); y[1][1] = fmaf(a1, w1, y[1][1]);
        }
    }
#pragma unroll
    for (int u = 0; u < 2; u++)
        asm volatile("red.global.add.v2.f32 [%0], {%1, %2};" ::"l"(g_y + u * DM + 2 * tid), "f"(y[u][0]), "f"(y[u][1]) : "memory");
    if (tid == 0) TSTAMP0(3, 2);
    __syncthreads();
    if (tid == 0) asm volatile("red.release.gpu.global.add.u32 [%0], 1;" ::"l"(&g_cnt) : "memory");
    if (tid == 0) TSTAMP0(3, 3);
    if (blockIdx.x == gridDim.x - 1) {
        if (tid == 0) {
            unsigned int c; int spins = 0;
            do { asm volatile("ld.acquire.gpu.global.u32 %0, [%1];" : "=r"(c) : "l"(&g_cnt) : "memory"); } while (c < gridDim.x && ++spins < (1 << 22));
        }
        __syncthreads();
        const float rv[2] = {key_value(ka), key_value(kb)};
#pragma unroll
        for (int u = 0; u < 2; u++) {
            const float2 yy = __ldcg((const float2*)(g_y + u * DM + 2 * tid));
            const float sig = rbf(1.f / (1.f + __expf(-rv[u])));
            const float o0 = hx[u][0] + rbf(xo[u][0] + rbf(rbf(yy.x) * sig));
            const float o1 = hx[u][1] + rbf(xo[u][1] + rbf(rbf(yy.y) * sig));
            *(uint32_t*)(out + (size_t)idx[u] * DM + 2 * tid) = pack_bf16(o0, o1);
        }
        if (tid == 0) TSTAMP0(3, 4);
    }
}

typedef CUresult (*PFN_encodeTiled)(CUtensorMap*, CUtensorMapDataType, cuuint32_t, void*, const cuuint64_t*, const cuuint64_t*,
                                    const cuuint32_t*, const cuuint32_t*, CUtensorMapInterleave, CUtensorMapSwizzle,
                                    CUtensorMapL2promotion, CUtensorMapFloatOOBfill);

void make_map(PFN_encodeTiled enc, CUtensorMap* m, const void* ptr, uint64_t cols, uint64_t rows, uint32_t bcols, uint32_t brows) {
    cuuint64_t dims[2] = {cols, rows};
    cuuint64_t strides[1] = {cols * 2};
    cuuint32_t box[2] = {bcols, brows};
    cuuint32_t es[2] = {1, 1};
    enc(m, CU_TENSOR_MAP_DATA_TYPE_BFLOAT16, 2, const_cast<void*>(ptr), dims, strides, box, es, CU_TENSOR_MAP_INTERLEAVE_NONE,
        CU_TENSOR_MAP_SWIZZLE_128B, CU_TENSOR_MAP_L2_PROMOTION_L2_256B, CU_TENSOR_MAP_FLOAT_OOB_FILL_NONE);
}

template <typename... KArgs, typename... Args>
void launch(void (*kern)(KArgs...), int grid, int block, int smem, bool pdl, Args... args) {
    cudaLaunchConfig_t cfg = {};
    cfg.gridDim = dim3(grid);
    cfg.blockDim = dim3(block);
    cfg.dynamicSmemBytes = smem;
    cfg.stream = cudaStreamPerThread;
    cudaLaunchAttribute at[1];
    at[0].id = cudaLaunchAttributeProgrammaticStreamSerialization;
    at[0].val.programmaticStreamSerializationAllowed = 1;
    cfg.attrs = at;
    cfg.numAttrs = pdl ? 1 : 0;
    cudaLaunchKernelEx(&cfg, kern, KArgs(args)...);
}

}

extern "C" void kernel_launch(void* const* d_in, const int* in_sizes, int n_in, void* d_out, int out_size) {
    const __nv_bfloat16* x = (const __nv_bfloat16*)d_in[0];
    const __nv_bfloat16* wqkv = (const __nv_bfloat16*)d_in[1];
    const __nv_bfloat16* wo = (const __nv_bfloat16*)d_in[2];
    const __nv_bfloat16* w_r = (const __nv_bfloat16*)d_in[4];
    const __nv_bfloat16* w_gate = (const __nv_bfloat16*)d_in[5];
    const __nv_bfloat16* w_up = (const __nv_bfloat16*)d_in[6];
    const __nv_bfloat16* w_down = (const __nv_bfloat16*)d_in[7];
    __nv_bfloat16* out = (__nv_bfloat16*)d_out;

    static PFN_encodeTiled enc = nullptr;
    static void* g_o_ptr = nullptr;
    if (!enc) {
        cudaDriverEntryPointQueryResult qres;
        void* fn = nullptr;
        cudaGetDriverEntryPoint("cuTensorMapEncodeTiled", &fn, cudaEnableDefault, &qres);
        enc = (PFN_encodeTiled)fn;
        cudaGetSymbolAddress(&g_o_ptr, g_o);
        cudaFuncSetAttribute(k1_qkv, cudaFuncAttributeMaxDynamicSharedMemorySize, K1_SMEM);
        cudaFuncSetAttribute(k2_attn, cudaFuncAttributeMaxDynamicSharedMemorySize, K2_SMEM);
        cudaFuncSetAttribute(k3_proj, cudaFuncAttributeMaxDynamicSharedMemorySize, K3_SMEM);
    }
    CUtensorMap tm_x, tm_w, tm_o, tm_wo;
    make_map(enc, &tm_x, x, DM, SEQ, 64, 128);
    make_map(enc, &tm_w, wqkv, 3 * DM, DM, 64, 32);
    make_map(enc, &tm_o, g_o_ptr, DM, SEQ, 64, 64);
    make_map(enc, &tm_wo, wo, DM, DM, 64, 64);

    const bool pdl = true;
    launch(k1_qkv, 128, 544, K1_SMEM, false, tm_x, tm_w);
    launch(k2_attn, 128, 512, K2_SMEM, pdl, (const uint8_t*)wo, (const uint8_t*)w_gate, (const uint8_t*)w_up, (const uint8_t*)w_down);
    launch(k3_proj, 128, 288, K3_SMEM, pdl, tm_o, tm_wo, x, w_r, out);
    launch(k4_moe, 112, 256, 0, pdl, w_gate, w_up, w_down, out);
}
```

```cpp
#include <cuda_runtime.h>
#include <cuda_bf16.h>
#include <cuda.h>
#include <stdint.h>

namespace {

constexpr int SEQ = 2048, DM = 512, NH = 32, FF = 1792;

__device__ __align__(1024) uint8_t g_q[NH * 2 * SEQ * 16];
__device__ __align__(1024) uint8_t g_kv[NH * 8 * 16384];
__device__ float g_norm[16 * NH * 3];
__device__ __align__(1024) __nv_bfloat16 g_o[SEQ * DM];
__device__ __align__(1024) __nv_bfloat16 g_h[SEQ * DM];
__device__ float2 g_stat[SEQ];
__device__ unsigned long long g_cand[64];
__device__ __align__(16) float g_y[2 * DM];
__device__ unsigned int g_cnt;
__device__ __align__(16) float4 g_part[32 * 8 * 64];

#define TSTAMP(K, I)
#define TSTAMP0(K, I)
__device__ __forceinline__ uint32_t smem_u32(const void* p) { return (uint32_t)__cvta_generic_to_shared(p); }
__device__ __forceinline__ void wg_fence() { asm volatile("wgmma.fence.sync.aligned;" ::: "memory"); }
__device__ __forceinline__ void wg_commit() { asm volatile("wgmma.commit_group.sync.aligned;" ::: "memory"); }
template <int N> __device__ __forceinline__ void wg_wait() { asm volatile("wgmma.wait_group.sync.aligned %0;" ::"n"(N) : "memory"); }
template <int N> __device__ __forceinline__ void fence_regs(float (&r)[N]) {
#pragma unroll
    for (int i = 0; i < N; i++) asm volatile("" : "+f"(r[i])::"memory");
}
__device__ __forceinline__ uint64_t make_desc(uint32_t addr, uint32_t lbo, uint32_t sbo, uint32_t swz) {
    uint64_t d = 0;
    d |= (uint64_t)((addr & 0x3FFFF) >> 4);
    d |= (uint64_t)((lbo & 0x3FFFF) >> 4) << 16;
    d |= (uint64_t)((sbo & 0x3FFFF) >> 4) << 32;
    d |= (uint64_t)swz << 62;
    return d;
}
__device__ __forceinline__ void mbar_init(uint32_t bar, uint32_t cnt) {
    asm volatile("mbarrier.init.shared::cta.b64 [%0], %1;" ::"r"(bar), "r"(cnt) : "memory");
}
__device__ __forceinline__ void mbar_expect_tx(uint32_t bar, uint32_t bytes) {
    asm volatile("mbarrier.arrive.expect_tx.shared::cta.b64 _, [%0], %1;" ::"r"(bar), "r"(bytes) : "memory");
}
__device__ __forceinline__ void mbar_arrive(uint32_t bar) {
    asm volatile("mbarrier.arrive.shared::cta.b64 _, [%0];" ::"r"(bar) : "memory");
}
__device__ __forceinline__ void mbar_wait(uint32_t bar, uint32_t parity) {
    asm volatile(
        "{\n.reg .pred p;\nWAIT_%=:\n"
        "mbarrier.try_wait.parity.shared::cta.b64 p, [%0], %1;\n"
        "@p bra DONE_%=;\nbra WAIT_%=;\nDONE_%=:\n}\n" ::"r"(bar), "r"(parity) : "memory");
}
__device__ __forceinline__ void bulk_g2s(uint32_t dst, const void* src, uint32_t bytes, uint32_t bar) {
    asm volatile("cp.async.bulk.shared::cluster.global.mbarrier::complete_tx::bytes [%0], [%1], %2, [%3];" ::"r"(dst),
                 "l"(src), "r"(bytes), "r"(bar) : "memory");
}
__device__ __forceinline__ void bulk_s2g(void* dst, uint32_t src, uint32_t bytes) {
    asm volatile("cp.async.bulk.global.shared::cta.bulk_group [%0], [%1], %2;" ::"l"(dst), "r"(src), "r"(bytes) : "memory");
}
__device__ __forceinline__ void tma_load_2d(uint32_t dst, const CUtensorMap* tm, int c0, int c1, uint32_t bar) {
    asm volatile("cp.async.bulk.tensor.2d.shared::cluster.global.mbarrier::complete_tx::bytes [%0], [%1, {%3, %4}], [%2];" ::"r"(dst),
                 "l"(tm), "r"(bar), "r"(c0), "r"(c1) : "memory");
}
__device__ __forceinline__ void tma_load_3d(uint32_t dst, const CUtensorMap* tm, int c0, int c1, int c2, uint32_t bar) {
    asm volatile("cp.async.bulk.tensor.3d.shared::cluster.global.mbarrier::complete_tx::bytes [%0], [%1, {%3, %4, %5}], [%2];" ::"r"(dst),
                 "l"(tm), "r"(bar), "r"(c0), "r"(c1), "r"(c2) : "memory");
}
__device__ __forceinline__ void tma_load_2d_mc(uint32_t dst, const CUtensorMap* tm, int c0, int c1, uint32_t bar, uint16_t mask) {
    asm volatile("cp.async.bulk.tensor.2d.shared::cluster.global.mbarrier::complete_tx::bytes.multicast::cluster [%0], [%1, {%3, %4}], [%2], %5;" ::"r"(dst),
                 "l"(tm), "r"(bar), "r"(c0), "r"(c1), "h"(mask) : "memory");
}
__device__ __forceinline__ void mbar_arrive_cluster(uint32_t bar, uint32_t cta) {
    asm volatile("{\n.reg .b32 ra;\nmapa.shared::cluster.u32 ra, %0, %1;\nmbarrier.arrive.release.cluster.shared::cluster.b64 _, [ra];\n}" ::"r"(bar), "r"(cta) : "memory");
}
__device__ __forceinline__ void cluster_sync() {
    asm volatile("barrier.cluster.arrive.release.aligned;\nbarrier.cluster.wait.acquire.aligned;" ::: "memory");
}
__device__ __forceinline__ void prefetch_l2(const void* p, uint32_t bytes) {
    asm volatile("cp.async.bulk.prefetch.L2.global [%0], %1;" ::"l"(p), "r"(bytes) : "memory");
}
__device__ __forceinline__ void fence_proxy_async() { asm volatile("fence.proxy.async.shared::cta;" ::: "memory"); }
__device__ __forceinline__ void fence_barrier_init() { asm volatile("fence.mbarrier_init.release.cluster;" ::: "memory"); }
__device__ __forceinline__ void pdl_launch() { asm volatile("griddepcontrol.launch_dependents;" ::: "memory"); }
__device__ __forceinline__ void pdl_wait() { asm volatile("griddepcontrol.wait;" ::: "memory"); }
__device__ __forceinline__ void named_sync(int id, int n) { asm volatile("bar.sync %0, %1;" ::"r"(id), "r"(n) : "memory"); }
__device__ __forceinline__ void named_arrive(int id, int n) { asm volatile("bar.arrive %0, %1;" ::"r"(id), "r"(n) : "memory"); }

__device__ __forceinline__ float ex2f(float x) { float y; asm("ex2.approx.ftz.f32 %0, %1;" : "=f"(y) : "f"(x)); return y; }
__device__ __forceinline__ uint32_t pack_bf16(float lo, float hi) {
    uint32_t r; asm("cvt.rn.bf16x2.f32 %0, %1, %2;" : "=r"(r) : "f"(hi), "f"(lo)); return r;
}
__device__ __forceinline__ float bf_lo(uint32_t v) { return __uint_as_float(v << 16); }
__device__ __forceinline__ float bf_hi(uint32_t v) { return __uint_as_float(v & 0xFFFF0000u); }
__device__ __forceinline__ float rbf(float x) { return __bfloat162float(__float2bfloat16_rn(x)); }
__device__ __forceinline__ uint32_t fma_bf16x2(uint32_t a, uint32_t b, uint32_t c) {
    uint32_t r; asm("fma.rn.bf16x2 %0, %1, %2, %3;" : "=r"(r) : "r"(a), "r"(b), "r"(c)); return r;
}
__device__ __forceinline__ void stmatrix_x4(uint32_t addr, uint32_t r0, uint32_t r1, uint32_t r2, uint32_t r3) {
    asm volatile("stmatrix.sync.aligned.m8n8.x4.shared.b16 [%0], {%1, %2, %3, %4};" ::"r"(addr), "r"(r0), "r"(r1), "r"(r2), "r"(r3) : "memory");
}
__device__ __forceinline__ void stmatrix_x4_trans(uint32_t addr, uint32_t r0, uint32_t r1, uint32_t r2, uint32_t r3) {
    asm volatile("stmatrix.sync.aligned.m8n8.x4.trans.shared.b16 [%0], {%1, %2, %3, %4};" ::"r"(addr), "r"(r0), "r"(r1), "r"(r2), "r"(r3) : "memory");
}

__device__ __forceinline__ void wgmma_k1_n136(float (&d)[68], uint64_t desca, uint64_t descb, int scale_d) {
  asm volatile("{\n.reg .pred p;\nsetp.ne.b32 p, %70, 0;\n"
    "wgmma.mma_async.sync.aligned.m64n136k16.f32.bf16.bf16 "
    "{%0, %1, %2, %3, %4, %5, %6, %7, %8, %9, %10, %11, %12, %13, %14, %15, %16, %17, %18, %19, %20, %21, %22, %23, %24, %25, %26, %27, %28, %29, %30, %31, %32, %33, %34, %35, %36, %37, %38, %39, %40, %41, %42, %43, %44, %45, %46, %47, %48, %49, %50, %51, %52, %53, %54, %55, %56, %57, %58, %59, %60, %61, %62, %63, %64, %65, %66, %67}, "
    "%68, %69, p, 1, 1, 1, 0;\n}\n"
    : "+f"(d[0]), "+f"(d[1]), "+f"(d[2]), "+f"(d[3]), "+f"(d[4]), "+f"(d[5]), "+f"(d[6]), "+f"(d[7]), "+f"(d[8]), "+f"(d[9]), "+f"(d[10]), "+f"(d[11]), "+f"(d[12]), "+f"(d[13]), "+f"(d[14]), "+f"(d[15]), "+f"(d[16]), "+f"(d[17]), "+f"(d[18]), "+f"(d[19]), "+f"(d[20]), "+f"(d[21]), "+f"(d[22]), "+f"(d[23]), "+f"(d[24]), "+f"(d[25]), "+f"(d[26]), "+f"(d[27]), "+f"(d[28]), "+f"(d[29]), "+f"(d[30]), "+f"(d[31]), "+f"(d[32]), "+f"(d[33]), "+f"(d[34]), "+f"(d[35]), "+f"(d[36]), "+f"(d[37]), "+f"(d[38]), "+f"(d[39]), "+f"(d[40]), "+f"(d[41]), "+f"(d[42]), "+f"(d[43]), "+f"(d[44]), "+f"(d[45]), "+f"(d[46]), "+f"(d[47]), "+f"(d[48]), "+f"(d[49]), "+f"(d[50]), "+f"(d[51]), "+f"(d[52]), "+f"(d[53]), "+f"(d[54]), "+f"(d[55]), "+f"(d[56]), "+f"(d[57]), "+f"(d[58]), "+f"(d[59]), "+f"(d[60]), "+f"(d[61]), "+f"(d[62]), "+f"(d[63]), "+f"(d[64]), "+f"(d[65]), "+f"(d[66]), "+f"(d[67])
    : "l"(desca), "l"(descb), "r"(scale_d));
}
__device__ __forceinline__ void wgmma_qk_n64(float (&d)[32], uint32_t a0, uint32_t a1, uint32_t a2, uint32_t a3, uint64_t descb) {
  asm volatile("{\n.reg .pred p;\nsetp.ne.b32 p, 0, 0;\n"
    "wgmma.mma_async.sync.aligned.m64n64k16.f32.bf16.bf16 "
    "{%0, %1, %2, %3, %4, %5, %6, %7, %8, %9, %10, %11, %12, %13, %14, %15, %16, %17, %18, %19, %20, %21, %22, %23, %24, %25, %26, %27, %28, %29, %30, %31}, "
    "{%32, %33, %34, %35}, %36, p, 1, 1, 0;\n}\n"
    : "=f"(d[0]), "=f"(d[1]), "=f"(d[2]), "=f"(d[3]), "=f"(d[4]), "=f"(d[5]), "=f"(d[6]), "=f"(d[7]), "=f"(d[8]), "=f"(d[9]), "=f"(d[10]), "=f"(d[11]), "=f"(d[12]), "=f"(d[13]), "=f"(d[14]), "=f"(d[15]), "=f"(d[16]), "=f"(d[17]), "=f"(d[18]), "=f"(d[19]), "=f"(d[20]), "=f"(d[21]), "=f"(d[22]), "=f"(d[23]), "=f"(d[24]), "=f"(d[25]), "=f"(d[26]), "=f"(d[27]), "=f"(d[28]), "=f"(d[29]), "=f"(d[30]), "=f"(d[31])
    : "r"(a0), "r"(a1), "r"(a2), "r"(a3), "l"(descb));
}
__device__ __forceinline__ void wgmma_pv_n24(float (&d)[12], uint32_t a0, uint32_t a1, uint32_t a2, uint32_t a3, uint64_t descb) {
  asm volatile("{\n.reg .pred p;\nsetp.eq.b32 p, 0, 0;\n"
    "wgmma.mma_async.sync.aligned.m64n24k16.f32.bf16.bf16 "
    "{%0, %1, %2, %3, %4, %5, %6, %7, %8, %9, %10, %11}, "
    "{%12, %13, %14, %15}, %16, p, 1, 1, 1;\n}\n"
    : "+f"(d[0]), "+f"(d[1]), "+f"(d[2]), "+f"(d[3]), "+f"(d[4]), "+f"(d[5]), "+f"(d[6]), "+f"(d[7]), "+f"(d[8]), "+f"(d[9]), "+f"(d[10]), "+f"(d[11])
    : "r"(a0), "r"(a1), "r"(a2), "r"(a3), "l"(descb));
}
__device__ __forceinline__ void wgmma_k3_n64(float (&d)[32], uint64_t desca, uint64_t descb, int scale_d) {
  asm volatile("{\n.reg .pred p;\nsetp.ne.b32 p, %34, 0;\n"
    "wgmma.mma_async.sync.aligned.m64n64k16.f32.bf16.bf16 "
    "{%0, %1, %2, %3, %4, %5, %6, %7, %8, %9, %10, %11, %12, %13, %14, %15, %16, %17, %18, %19, %20, %21, %22, %23, %24, %25, %26, %27, %28, %29, %30, %31}, "
    "%32, %33, p, 1, 1, 0, 1;\n}\n"
    : "+f"(d[0]), "+f"(d[1]), "+f"(d[2]), "+f"(d[3]), "+f"(d[4]), "+f"(d[5]), "+f"(d[6]), "+f"(d[7]), "+f"(d[8]), "+f"(d[9]), "+f"(d[10]), "+f"(d[11]), "+f"(d[12]), "+f"(d[13]), "+f"(d[14]), "+f"(d[15]), "+f"(d[16]), "+f"(d[17]), "+f"(d[18]), "+f"(d[19]), "+f"(d[20]), "+f"(d[21]), "+f"(d[22]), "+f"(d[23]), "+f"(d[24]), "+f"(d[25]), "+f"(d[26]), "+f"(d[27]), "+f"(d[28]), "+f"(d[29]), "+f"(d[30]), "+f"(d[31])
    : "l"(desca), "l"(descb), "r"(scale_d));
}

constexpr int K1_XS = 17408;
constexpr int K1_WS = 24576;
constexpr int K1_ST = K1_XS + K1_WS;
constexpr int K1_NST = 5;
constexpr int K1_OFF_MISC = K1_NST * K1_ST;
constexpr int K1_SMEM = K1_OFF_MISC + 2048 + 1024;
constexpr float QSCALE = 0.25f * 1.4426950408889634f;

__global__ void __launch_bounds__(544, 1)
k1_qkv(const __grid_constant__ CUtensorMap tm_x, const __grid_constant__ CUtensorMap tm_w) {
    extern __shared__ uint8_t smem_raw[];
    const uint32_t sraw = smem_u32(smem_raw);
    const uint32_t sb = (sraw + 1023) & ~1023u;
    uint8_t* sp = smem_raw + (sb - sraw);
    const uint32_t full = sb + K1_OFF_MISC;
    const uint32_t empty = full + 64;
    float* s_m = (float*)(sp + K1_OFF_MISC + 256);
    float* s_r = s_m + 128;

    const int tid = threadIdx.x, warp = tid >> 5, lane = tid & 31;
    const int mt = blockIdx.x >> 3, nt = blockIdx.x & 7;
    if (tid == 0) TSTAMP0(0, 0);
    pdl_launch();
    if (tid == 0) {
        for (int i = 0; i < K1_NST; i++) { mbar_init(full + 8 * i, 1); mbar_init(empty + 8 * i, 4); }
        fence_barrier_init();
    }
    if (tid < K1_NST * 64) {
        *(uint4*)(sp + (tid >> 6) * K1_ST + 16384 + (tid & 63) * 16) =
            make_uint4(0x3F803F80u, 0x3F803F80u, 0x3F803F80u, 0x3F803F80u);
    }
    fence_proxy_async();
    __syncthreads();

    if (warp == 16) {
        if (lane == 0) {
            for (int kb = 0; kb < 8; kb++) {
                const int s = kb % K1_NST;
                if (kb >= K1_NST) mbar_wait(empty + 8 * s, 0);
                mbar_expect_tx(full + 8 * s, 16384 + K1_WS);
                tma_load_2d(sb + s * K1_ST, &tm_x, kb * 64, mt * 128, full + 8 * s);
                tma_load_3d(sb + s * K1_ST + K1_XS, &tm_w, nt * 64, kb * 64, 0, full + 8 * s);
            }
        } else if (lane == 1) {
            if (blockIdx.x == 0) g_cnt = 0;
        }
        if (blockIdx.x == 0) for (int i = lane; i < 2 * DM; i += 32) g_y[i] = 0.f;
        for (int i = lane; i < 128; i += 32) g_part[blockIdx.x * 128 + i] = make_float4(0.f, 0.f, 0.f, 0.f);
    } else if (warp >= 12) {
        const int r = tid - 384;
        float x0 = 0.f, s1 = 0.f, s2 = 0.f;
#pragma unroll 1
        for (int kb = 0; kb < 8; kb++) {
            const int s = kb % K1_NST;
            mbar_wait(full + 8 * s, (kb / K1_NST) & 1);
            const uint8_t* rowp = sp + s * K1_ST + r * 128;
            if (kb == 0) x0 = bf_lo(*(const uint32_t*)(rowp + ((r & 7) << 4)));
#pragma unroll
            for (int c = 0; c < 8; c++) {
                const uint4 v = *(const uint4*)(rowp + ((c ^ (r & 7)) << 4));
                const uint32_t w[4] = {v.x, v.y, v.z, v.w};
#pragma unroll
                for (int i = 0; i < 4; i++) {
                    const float a = bf_lo(w[i]) - x0, b = bf_hi(w[i]) - x0;
                    s1 += a; s2 = fmaf(a, a, s2);
                    s1 += b; s2 = fmaf(b, b, s2);
                }
            }
            if (kb < 8 - K1_NST) {
                named_sync(3, 128);
                if (r == 0) mbar_arrive(empty + 8 * s);
            }
        }
        const float md = s1 * (1.f / DM);
        const float mean = x0 + md;
        const float var = fmaxf(s2 * (1.f / DM) - md * md, 0.f);
        const float den = rbf(sqrtf(rbf(rbf(var) + 1e-5f)));
        s_m[r] = rbf(mean);
        s_r[r] = 1.f / den;
        named_arrive(1, 512);
    } else {
        const int part = warp >> 2, hw = warp & 3;
        float acc[68];
#pragma unroll
        for (int i = 0; i < 68; i++) acc[i] = 0.f;
        fence_regs(acc);
#pragma unroll 1
        for (int kb = 0; kb < 8; kb++) {
            const int s = kb % K1_NST;
            mbar_wait(full + 8 * s, (kb / K1_NST) & 1);
            const uint64_t da = make_desc(sb + s * K1_ST + K1_XS + part * 8192, 1024, 1024, 1);
            const uint64_t db = make_desc(sb + s * K1_ST, 16, 1024, 1);
            wg_fence();
#pragma unroll
            for (int k = 0; k < 4; k++) wgmma_k1_n136(acc, da + k * 128, db + k * 2, (kb | k) != 0);
            wg_commit();
            if (kb > 0 && kb <= 8 - K1_NST) {
                wg_wait<1>();
                if ((tid & 127) == 0) mbar_arrive(empty + 8 * (kb - 1));
            }
        }
        wg_wait<0>();
        fence_regs(acc);
        if (tid == 0) TSTAMP0(0, 1);
        named_sync(1, 512);
        if (tid == 0) TSTAMP0(0, 2);

        const int t = lane & 3;
        const float cs0 = acc[64], cs1 = acc[66];
        const float sc = (part == 0) ? QSCALE : 1.f;
        const uint32_t stg = sb + (hw >> 1) * K1_ST + K1_XS + part * 8192 + (hw & 1) * 4096;
        const uint32_t st_addr = stg + ((lane >> 3) & 1) * 2048 + ((lane >> 4) * 8 + (lane & 7)) * 16;
#pragma unroll
        for (int j = 0; j < 16; j += 2) {
            uint32_t rr[4];
#pragma unroll
            for (int u = 0; u < 2; u++) {
                const int jj = j + u;
                const float2 m2 = *(const float2*)(s_m + 8 * jj + 2 * t);
                const float2 r2 = *(const float2*)(s_r + 8 * jj + 2 * t);
                const float ra = r2.x * sc, rb = r2.y * sc;
                rr[2 * u] = pack_bf16((acc[4 * jj] - m2.x * cs0) * ra, (acc[4 * jj + 1] - m2.y * cs0) * rb);
                rr[2 * u + 1] = pack_bf16((acc[4 * jj + 2] - m2.x * cs1) * ra, (acc[4 * jj + 3] - m2.y * cs1) * rb);
            }
            stmatrix_x4_trans(st_addr + j * 128, rr[0], rr[1], rr[2], rr[3]);
        }
        __syncwarp();
        float nmax = 0.f;
#pragma unroll
        for (int i = 0; i < 4; i++) {
            const int tok = lane + 32 * i;
            const uint4 a = *(const uint4*)(sp + (stg - sb) + tok * 16);
            const uint4 b = *(const uint4*)(sp + (stg - sb) + 2048 + tok * 16);
            const uint32_t w[8] = {a.x, a.y, a.z, a.w, b.x, b.y, b.z, b.w};
            float n2 = 0.f;
#pragma unroll
            for (int q = 0; q < 8; q++) {
                const float lo = bf_lo(w[q]), hi = bf_hi(w[q]);
                n2 = fmaf(lo, lo, n2); n2 = fmaf(hi, hi, n2);
            }
            nmax = (n2 > nmax || n2 != n2) ? n2 : nmax;
        }
#pragma unroll
        for (int o = 16; o > 0; o >>= 1) {
            const float v = __shfl_xor_sync(0xffffffffu, nmax, o);
            nmax = (v > nmax || v != v) ? v : nmax;
        }
        fence_proxy_async();
        __syncwarp();
        if (lane == 0) {
            const int head = nt * 4 + hw;
            g_norm[(mt * NH + head) * 3 + part] = nmax;
            uint8_t* dst;
            uint32_t hstride;
            if (part == 0) { dst = g_q + (size_t)head * 65536 + mt * 2048; hstride = 32768; }
            else { dst = g_kv + (size_t)head * 131072 + (mt >> 1) * 16384 + (part - 1) * 8192 + (mt & 1) * 2048; hstride = 4096; }
            bulk_s2g(dst, stg, 2048);
            bulk_s2g(dst + hstride, stg + 2048, 2048);
            asm volatile("cp.async.bulk.commit_group;" ::: "memory");
            asm volatile("cp.async.bulk.wait_group.read 0;" ::: "memory");
            if (tid == 0) TSTAMP0(0, 3);
        }
    }
}

constexpr int K2_CH_G = 16384, K2_CH_S = 20480, K2_NCH = 8;
constexpr int K2_SMEM = K2_NCH * K2_CH_S + 128 + 1024;

__device__ __forceinline__ uint32_t exp2_pair_poly(float s0, float s1) {
    const float KB = 65536.0f + 127.0f;
    const float t0 = s0 + KB, t1 = s1 + KB;
    const uint32_t w = __byte_perm(__float_as_uint(t0), __float_as_uint(t1), 0x5410);
    uint32_t z;
    asm("lop3.b32 %0, %1, %2, %3, 0xEA;" : "=r"(z) : "r"(w), "r"(0x007F007Fu), "r"(0x3F803F80u));
    uint32_t p = fma_bf16x2(0x3eab3eabu, z, 0xbc73bc73u);
    p = fma_bf16x2(p, z, 0x3f2f3f2fu);
    return p + w - z;
}
constexpr uint32_t K2_EMASK = 0x5757u;
template <int LO, int HI>
__device__ __forceinline__ void softmax_part(const float (&s)[32], uint32_t (&p)[16]) {
#pragma unroll
    for (int i = LO; i < HI; i++) {
        if ((K2_EMASK >> i) & 1) p[i] = exp2_pair_poly(s[2 * i], s[2 * i + 1]);
        else p[i] = pack_bf16(ex2f(s[2 * i]), ex2f(s[2 * i + 1]));
    }
}
#define K2_PV(P, OFF)                                                                              \
    _Pragma("unroll") for (int kk = 0; kk < 4; kk++)                                               \
        wgmma_pv_n24(o, P[4 * kk], P[4 * kk + 1], P[4 * kk + 2], P[4 * kk + 3], dv + ((OFF) + kk * 16));

__global__ void __launch_bounds__(512, 1)
k2_attn(const uint8_t* __restrict__ wo, const uint8_t* __restrict__ w_gate, const uint8_t* __restrict__ w_up, const uint8_t* __restrict__ w_down) {
    extern __shared__ uint8_t smem_raw[];
    const uint32_t sraw = smem_u32(smem_raw);
    const uint32_t sb = (sraw + 1023) & ~1023u;
    uint8_t* sp = smem_raw + (sb - sraw);
    const uint32_t bars = sb + K2_NCH * K2_CH_S;
    const int tid = threadIdx.x;
    const int head = blockIdx.x >> 2, quarter = blockIdx.x & 3;
    if (tid == 0) TSTAMP0(1, 0);
    pdl_launch();
    if (tid == 0) {
        for (int c = 0; c < K2_NCH; c++) mbar_init(bars + 8 * c, 1);
        fence_barrier_init();
    }
    if (tid == 32) {
        prefetch_l2(wo + blockIdx.x * 4096, 4096);
        prefetch_l2(w_gate + blockIdx.x * 14336, 14336);
        prefetch_l2(w_up + blockIdx.x * 14336, 14336);
        prefetch_l2(w_down + blockIdx.x * 14336, 14336);
    }
    for (int i = tid; i < K2_NCH * 256; i += 512)
        *(uint4*)(sp + (i >> 8) * K2_CH_S + 16384 + (i & 255) * 16) =
            make_uint4(0x3F803F80u, 0x3F803F80u, 0x3F803F80u, 0x3F803F80u);
    fence_proxy_async();
    __syncthreads();
    pdl_wait();
    if (tid == 0) TSTAMP0(1, 1);
    if (tid == 0) {
        const uint8_t* src = g_kv + (size_t)head * (K2_NCH * K2_CH_G);
        for (int c = 0; c < K2_NCH; c++) {
            mbar_expect_tx(bars + 8 * c, K2_CH_G);
            bulk_g2s(sb + c * K2_CH_S, src + c * K2_CH_G, K2_CH_G, bars + 8 * c);
        }
    }
    const int wg = tid >> 7, warp = (tid >> 5) & 3, lane = tid & 31, g = lane >> 2, t = lane & 3;

    bool fast;
    {
        const int m16 = lane & 15;
        float kn = g_norm[(m16 * NH + head) * 3 + 1];
        float vn = g_norm[(m16 * NH + head) * 3 + 2];
        float qn = g_norm[((quarter * 4 + (lane & 3)) * NH + head) * 3 + 0];
        bool bad = !(kn < 1e30f) || !(vn < 1e30f) || !(qn < 1e30f);
#pragma unroll
        for (int o = 8; o > 0; o >>= 1) {
            kn = fmaxf(kn, __shfl_xor_sync(0xffffffffu, kn, o));
            qn = fmaxf(qn, __shfl_xor_sync(0xffffffffu, qn, o));
        }
        bad = __any_sync(0xffffffffu, bad);
        fast = !bad && (qn * kn <= 3500.f);
    }
    const uint64_t dk0 = make_desc(sb, 4096, 128, 0);
    const uint64_t dv0 = make_desc(sb + 8192, 128, 4096, 0);

#pragma unroll 1
    for (int pass = 0; pass < 2; pass++) {
        const int row0 = quarter * 512 + pass * 256 + wg * 64 + warp * 16 + g;
        uint32_t qa[4];
        {
            const uint8_t* qb = g_q + (size_t)head * 65536 + row0 * 16 + t * 4;
            qa[0] = *(const uint32_t*)(qb);
            qa[1] = *(const uint32_t*)(qb + 128);
            qa[2] = *(const uint32_t*)(qb + 32768);
            qa[3] = *(const uint32_t*)(qb + 32768 + 128);
        }
        float o[12];
#pragma unroll
        for (int i = 0; i < 12; i++) o[i] = 0.f;
        fence_regs(o);
        if (fast) {
#pragma unroll 1
            for (int c = 0; c < K2_NCH; c++) {
                const uint64_t dk = dk0 + (uint64_t)(c * (K2_CH_S >> 4));
                const uint64_t dv = dv0 + (uint64_t)(c * (K2_CH_S >> 4));
                float s0[32], s1[32], s2[32], s3[32];
                uint32_t p0[16], p1[16], p2[16], p3[16];
                mbar_wait(bars + 8 * c, 0);
                wg_wait<1>();
                wg_fence();
                wgmma_qk_n64(s0, qa[0], qa[1], qa[2], qa[3], dk);
                wg_commit();
                wg_wait<1>();
                wg_fence();
                wgmma_qk_n64(s1, qa[0], qa[1], qa[2], qa[3], dk + 64);
                wg_commit();
                wg_wait<1>();
                fence_regs(s0);
                softmax_part<0, 16>(s0, p0);
                wg_fence();
                K2_PV(p0, 0);
                wg_commit();
                wg_wait<1>();
                fence_regs(s1);
                softmax_part<0, 8>(s1, p1);
                wg_wait<0>();
                wg_fence();
                wgmma_qk_n64(s2, qa[0], qa[1], qa[2], qa[3], dk + 128);
                wg_commit();
                softmax_part<8, 16>(s1, p1);
                wg_fence();
                K2_PV(p1, 64);
                wg_commit();
                wg_wait<1>();
                fence_regs(s2);
                softmax_part<0, 8>(s2, p2);
                wg_wait<0>();
                wg_fence();
                wgmma_qk_n64(s3, qa[0], qa[1], qa[2], qa[3], dk + 192);
                wg_commit();
                softmax_part<8, 16>(s2, p2);
                wg_fence();
                K2_PV(p2, 128);
                wg_commit();
                wg_wait<1>();
                fence_regs(s3);
                softmax_part<0, 16>(s3, p3);
                wg_fence();
                K2_PV(p3, 192);
                wg_commit();
            }
            wg_wait<0>();
            fence_regs(o);
        } else {
            float m0 = -INFINITY, m1 = -INFINITY;
#pragma unroll 1
            for (int b = 0; b < 32; b++) {
                const int c = b >> 2;
                const uint64_t dk = dk0 + (uint64_t)(c * (K2_CH_S >> 4) + (b & 3) * 64);
                const uint64_t dv = dv0 + (uint64_t)(c * (K2_CH_S >> 4) + (b & 3) * 64);
                float s[32];
                uint32_t p[16];
                mbar_wait(bars + 8 * c, 0);
                wg_fence();
                wgmma_qk_n64(s, qa[0], qa[1], qa[2], qa[3], dk);
                wg_commit();
                wg_wait<0>();
                fence_regs(s);
                float x0 = s[0], x1 = s[2];
#pragma unroll
                for (int j = 0; j < 8; j++) {
                    x0 = fmaxf(x0, fmaxf(s[4 * j], s[4 * j + 1]));
                    x1 = fmaxf(x1, fmaxf(s[4 * j + 2], s[4 * j + 3]));
                }
                x0 = fmaxf(x0, __shfl_xor_sync(0xffffffffu, x0, 1));
                x0 = fmaxf(x0, __shfl_xor_sync(0xffffffffu, x0, 2));
                x1 = fmaxf(x1, __shfl_xor_sync(0xffffffffu, x1, 1));
                x1 = fmaxf(x1, __shfl_xor_sync(0xffffffffu, x1, 2));
                const float n0 = fmaxf(m0, x0), n1 = fmaxf(m1, x1);
                const float c0 = ex2f(m0 - n0), c1 = ex2f(m1 - n1);
                m0 = n0; m1 = n1;
#pragma unroll
                for (int j = 0; j < 3; j++) {
                    o[4 * j] *= c0; o[4 * j + 1] *= c0; o[4 * j + 2] *= c1; o[4 * j + 3] *= c1;
                }
#pragma unroll
                for (int j = 0; j < 8; j++) {
                    p[2 * j] = pack_bf16(ex2f(s[4 * j] - n0), ex2f(s[4 * j + 1] - n0));
                    p[2 * j + 1] = pack_bf16(ex2f(s[4 * j + 2] - n1), ex2f(s[4 * j + 3] - n1));
                }
                fence_regs(o);
                wg_fence();
                K2_PV(p, 0);
                wg_commit();
                wg_wait<0>();
                fence_regs(o);
            }
        }
        const float inv0 = 1.f / o[8], inv1 = 1.f / o[10];
        uint32_t* out0 = (uint32_t*)(g_o + (size_t)row0 * DM + head * 16);
        uint32_t* out1 = (uint32_t*)(g_o + (size_t)(row0 + 8) * DM + head * 16);
        out0[t] = pack_bf16(o[0] * inv0, o[1] * inv0);
        out0[4 + t] = pack_bf16(o[4] * inv0, o[5] * inv0);
        out1[t] = pack_bf16(o[2] * inv1, o[3] * inv1);
        out1[4 + t] = pack_bf16(o[6] * inv1, o[7] * inv1);
        if (tid == 0) TSTAMP0(1, 2 + pass);
    }
}

constexpr int K3_OFF_W = 65536;
constexpr int K3_OFF_MISC = K3_OFF_W + 131072;
constexpr int K3_SMEM = K3_OFF_MISC + 128 + 512 + 1024;

__device__ __forceinline__ unsigned long long make_key(float r_bf, int idx) {
    uint32_t u = __float_as_uint(r_bf);
    u = (u & 0x80000000u) ? ~u : (u | 0x80000000u);
    return ((unsigned long long)u << 32) | (uint32_t)(0x7FFFFFFF - idx);
}
__device__ __forceinline__ float key_value(unsigned long long k) {
    uint32_t u = (uint32_t)(k >> 32);
    u = (u & 0x80000000u) ? (u & 0x7FFFFFFFu) : ~u;
    return __uint_as_float(u);
}
__device__ __forceinline__ int key_index(unsigned long long k) { return 0x7FFFFFFF - (int)(uint32_t)k; }
__device__ __forceinline__ void warp_top2(unsigned long long& a, unsigned long long& b) {
#pragma unroll
    for (int o = 16; o > 0; o >>= 1) {
        const unsigned long long c = __shfl_xor_sync(0xffffffffu, a, o);
        const unsigned long long d = __shfl_xor_sync(0xffffffffu, b, o);
        const unsigned long long hi = a > c ? a : c, lo = a > c ? c : a;
        const unsigned long long m = b > d ? b : d;
        a = hi;
        b = lo > m ? lo : m;
    }
}

__global__ void __launch_bounds__(288, 1)
k3_proj(const __grid_constant__ CUtensorMap tm_o, const __grid_constant__ CUtensorMap tm_wo,
        const __nv_bfloat16* __restrict__ x, const __nv_bfloat16* __restrict__ w_r, __nv_bfloat16* __restrict__ out) {
    extern __shared__ uint8_t smem_raw[];
    const uint32_t sraw = smem_u32(smem_raw);
    const uint32_t sb = (sraw + 1023) & ~1023u;
    uint8_t* sp = smem_raw + (sb - sraw);
    const uint32_t obar = sb + K3_OFF_MISC;
    const uint32_t wbar = obar + 64;
    unsigned long long* s_key = (unsigned long long*)(sp + K3_OFF_MISC + 128);

    const int tid = threadIdx.x, warp = tid >> 5, lane = tid & 31;
    const int mt = blockIdx.x >> 2, nt = blockIdx.x & 3;
    if (tid == 0) TSTAMP0(2, 0);

    pdl_launch();
    if (tid == 0) {
        for (int i = 0; i < 16; i++) mbar_init(obar + 8 * i, 1);
        fence_barrier_init();
    }
    __syncthreads();

    if (warp == 8) {
        if (lane == 0) {
            for (int kb = 0; kb < 8; kb++) {
                mbar_expect_tx(wbar + 8 * kb, 16384);
                tma_load_3d(sb + K3_OFF_W + kb * 16384, &tm_wo, 0, kb * 64, nt * 2, wbar + 8 * kb);
            }
            pdl_wait();
            TSTAMP0(2, 1);
            for (int k2 = 0; k2 < 4; k2++) {
                mbar_expect_tx(obar + 8 * k2, 16384);
                tma_load_3d(sb + k2 * 16384, &tm_o, 0, mt * 64, k2 * 2, obar + 8 * k2);
            }
        }
        return;
    }
    const int wg = warp >> 2, wi = warp & 3, g = lane >> 2, t = lane & 3;
    const int r0 = mt * 64 + wi * 16 + g;
    const int cb = nt * 128 + wg * 64;
    uint32_t xr[16], wr[8];
#pragma unroll
    for (int j = 0; j < 8; j++) {
        xr[2 * j] = *(const uint32_t*)(x + (size_t)r0 * DM + cb + 8 * j + 2 * t);
        xr[2 * j + 1] = *(const uint32_t*)(x + (size_t)(r0 + 8) * DM + cb + 8 * j + 2 * t);
        wr[j] = *(const uint32_t*)(w_r + cb + 8 * j + 2 * t);
    }
    float wsum = 0.f;
    {
        const uint4 a = *(const uint4*)(w_r + lane * 16), b = *(const uint4*)(w_r + lane * 16 + 8);
        const uint32_t w[8] = {a.x, a.y, a.z, a.w, b.x, b.y, b.z, b.w};
#pragma unroll
        for (int i = 0; i < 8; i++) wsum += bf_lo(w[i]) + bf_hi(w[i]);
#pragma unroll
        for (int o = 16; o > 0; o >>= 1) wsum += __shfl_xor_sync(0xffffffffu, wsum, o);
    }
    float acc[32];
#pragma unroll
    for (int i = 0; i < 32; i++) acc[i] = 0.f;
    fence_regs(acc);
#pragma unroll 1
    for (int kb = 0; kb < 8; kb++) {
        mbar_wait(wbar + 8 * kb, 0);
        mbar_wait(obar + 8 * (kb >> 1), 0);
        const uint64_t da = make_desc(sb + kb * 8192, 16, 1024, 1);
        const uint64_t db = make_desc(sb + K3_OFF_W + kb * 16384 + wg * 8192, 1024, 1024, 1);
        wg_fence();
#pragma unroll
        for (int k = 0; k < 4; k++) wgmma_k3_n64(acc, da + k * 2, db + k * 128, (kb | k) != 0);
        wg_commit();
    }
    wg_wait<0>();
    fence_regs(acc);
    if (tid == 0) TSTAMP0(2, 2);
    float hv[32];
    float s0 = 0.f, s1 = 0.f, d0 = 0.f, d1 = 0.f;
#pragma unroll
    for (int j = 0; j < 8; j++) {
        hv[4 * j] = rbf(bf_lo(xr[2 * j]) + rbf(acc[4 * j]));
        hv[4 * j + 1] = rbf(bf_hi(xr[2 * j]) + rbf(acc[4 * j + 1]));
        hv[4 * j + 2] = rbf(bf_lo(xr[2 * j + 1]) + rbf(acc[4 * j + 2]));
        hv[4 * j + 3] = rbf(bf_hi(xr[2 * j + 1]) + rbf(acc[4 * j + 3]));
        const float wl = bf_lo(wr[j]), wh = bf_hi(wr[j]);
        s0 += hv[4 * j] + hv[4 * j + 1];
        s1 += hv[4 * j + 2] + hv[4 * j + 3];
        d0 = fmaf(hv[4 * j], wl, fmaf(hv[4 * j + 1], wh, d0));
        d1 = fmaf(hv[4 * j + 2], wl, fmaf(hv[4 * j + 3], wh, d1));
    }
#pragma unroll
    for (int o = 1; o < 4; o <<= 1) {
        s0 += __shfl_xor_sync(0xffffffffu, s0, o);
        s1 += __shfl_xor_sync(0xffffffffu, s1, o);
        d0 += __shfl_xor_sync(0xffffffffu, d0, o);
        d1 += __shfl_xor_sync(0xffffffffu, d1, o);
    }
    const float mu0 = s0 * (1.f / 64), mu1 = s1 * (1.f / 64);
    float q0 = 0.f, q1 = 0.f;
#pragma unroll
    for (int j = 0; j < 8; j++) {
        float a = hv[4 * j] - mu0, b = hv[4 * j + 1] - mu0, c = hv[4 * j + 2] - mu1, d = hv[4 * j + 3] - mu1;
        q0 = fmaf(a, a, fmaf(b, b, q0));
        q1 = fmaf(c, c, fmaf(d, d, q1));
    }
#pragma unroll
    for (int o = 1; o < 4; o <<= 1) {
        q0 += __shfl_xor_sync(0xffffffffu, q0, o);
        q1 += __shfl_xor_sync(0xffffffffu, q1, o);
    }
    float4* part = g_part + (size_t)mt * 512 + wi * 16 + g;
    if (t < 2) {
        float4* dst = part + (nt * 2 + wg) * 64 + t * 8;
        const float a = t ? mu1 : mu0, b = t ? q1 : q0, c = t ? d1 : d0;
        asm volatile("st.relaxed.gpu.global.v4.f32 [%0], {%1, %2, %3, %4};" ::"l"(dst), "f"(a), "f"(b), "f"(c), "f"(1.0f) : "memory");
    }
    named_sync(2, 256);
    const uint32_t stg_o = sb + warp * 4096;
    const uint32_t stg_h = stg_o + 2048;
    const int srow = (lane & 7) + ((lane >> 3) & 1) * 8;
    const int sj = lane >> 4;
#pragma unroll
    for (int j = 0; j < 8; j += 2) {
        const uint32_t off = srow * 128 + (((j + sj) ^ (srow & 7)) << 4);
        stmatrix_x4(stg_h + off, pack_bf16(hv[4 * j], hv[4 * j + 1]), pack_bf16(hv[4 * j + 2], hv[4 * j + 3]),
                    pack_bf16(hv[4 * j + 4], hv[4 * j + 5]), pack_bf16(hv[4 * j + 6], hv[4 * j + 7]));
    }
    __syncwarp();
#pragma unroll
    for (int i = 0; i < 4; i++) {
        const int row = i * 4 + (lane >> 3), ch = lane & 7;
        const uint4 vh = *(const uint4*)(sp + warp * 4096 + 2048 + row * 128 + ((ch ^ (row & 7)) << 4));
        *(uint4*)(g_h + (size_t)(mt * 64 + wi * 16 + row) * DM + cb + ch * 8) = vh;
    }
    float mean[2], den[2], rr[2];
    {
        float4 v[4];
        int spins = 0;
        while (true) {
#pragma unroll
            for (int i = 0; i < 4; i++) {
                const float4* p = part + (t + (i & 1) * 4) * 64 + (i >> 1) * 8;
                asm volatile("ld.relaxed.gpu.global.v4.f32 {%0, %1, %2, %3}, [%4];" : "=f"(v[i].x), "=f"(v[i].y), "=f"(v[i].z), "=f"(v[i].w) : "l"(p) : "memory");
            }
            const bool ok = (v[0].w != 0.f) && (v[1].w != 0.f) && (v[2].w != 0.f) && (v[3].w != 0.f);
            if (__all_sync(0xffffffffu, ok) || ++spins > (1 << 22)) break;
        }
#pragma unroll
        for (int u = 0; u < 2; u++) {
            float mu = v[2 * u].x + v[2 * u + 1].x, m2 = v[2 * u].y + v[2 * u + 1].y, hw = v[2 * u].z + v[2 * u + 1].z;
#pragma unroll
            for (int o = 1; o < 4; o <<= 1) {
                mu += __shfl_xor_sync(0xffffffffu, mu, o);
                m2 += __shfl_xor_sync(0xffffffffu, m2, o);
                hw += __shfl_xor_sync(0xffffffffu, hw, o);
            }
            mu *= 0.125f;
            const float da = v[2 * u].x - mu, db = v[2 * u + 1].x - mu;
            float dd = 64.f * (da * da + db * db);
#pragma unroll
            for (int o = 1; o < 4; o <<= 1) dd += __shfl_xor_sync(0xffffffffu, dd, o);
            m2 += dd;
            mean[u] = rbf(mu);
            den[u] = rbf(sqrtf(rbf(rbf(m2 * (1.f / DM)) + 1e-5f)));
            rr[u] = rbf((hw - mean[u] * wsum) / den[u]);
        }
    }
    if (tid == 0) TSTAMP0(2, 3);
    const float i0 = 1.f / den[0], i1 = 1.f / den[1];
#pragma unroll
    for (int j = 0; j < 8; j += 2) {
        uint32_t ro[4];
#pragma unroll
        for (int u = 0; u < 2; u++) {
            const int jj = j + u;
            const float a = hv[4 * jj], b = hv[4 * jj + 1], c = hv[4 * jj + 2], d = hv[4 * jj + 3];
            const float na = rbf(rbf(a - mean[0]) * i0), nb = rbf(rbf(b - mean[0]) * i0);
            const float nc = rbf(rbf(c - mean[1]) * i1), nd = rbf(rbf(d - mean[1]) * i1);
            ro[2 * u] = pack_bf16(a + na, b + nb);
            ro[2 * u + 1] = pack_bf16(c + nc, d + nd);
        }
        const uint32_t off = srow * 128 + (((j + sj) ^ (srow & 7)) << 4);
        stmatrix_x4(stg_o + off, ro[0], ro[1], ro[2], ro[3]);
    }
    __syncwarp();
#pragma unroll
    for (int i = 0; i < 4; i++) {
        const int row = i * 4 + (lane >> 3), ch = lane & 7;
        const uint4 vo = *(const uint4*)(sp + warp * 4096 + row * 128 + ((ch ^ (row & 7)) << 4));
        *(uint4*)(out + (size_t)(mt * 64 + wi * 16 + row) * DM + cb + ch * 8) = vo;
    }
    if (tid == 0) TSTAMP0(2, 4);
    if (nt == 0 && wg == 0) {
        if (t == 0) {
            g_stat[r0] = make_float2(mean[0], den[0]);
            g_stat[r0 + 8] = make_float2(mean[1], den[1]);
            s_key[wi * 16 + g] = make_key(rr[0], r0);
            s_key[wi * 16 + g + 8] = make_key(rr[1], r0 + 8);
        }
        named_sync(1, 128);
        if (warp == 0) {
            unsigned long long a = s_key[lane], b = s_key[lane + 32];
            if (b > a) { const unsigned long long c = a; a = b; b = c; }
            warp_top2(a, b);
            if (lane == 0) { g_cand[mt * 2] = a; g_cand[mt * 2 + 1] = b; }
        }
    }
}

__global__ void __launch_bounds__(256)
k4_moe(const __nv_bfloat16* __restrict__ w_gate, const __nv_bfloat16* __restrict__ w_up,
       const __nv_bfloat16* __restrict__ w_down, __nv_bfloat16* __restrict__ out) {
    __shared__ float s_gu[2][32];
    const int tid = threadIdx.x, warp = tid >> 5, lane = tid & 31;
    const int f0 = blockIdx.x * 16;
    if (tid == 0) TSTAMP0(3, 0);

    uint2 wgu[16];
    uint32_t wd[16];
    {
        const __nv_bfloat16* base = (warp < 4 ? w_gate : w_up) + (size_t)(16 * lane) * FF + f0 + (warp & 3) * 4;
#pragma unroll
        for (int k = 0; k < 16; k++) wgu[k] = __ldg((const uint2*)(base + (size_t)k * FF));
#pragma unroll
        for (int f = 0; f < 16; f++) wd[f] = __ldg((const uint32_t*)(w_down + (size_t)(f0 + f) * DM + 2 * tid));
    }
    pdl_wait();
    if (tid == 0) TSTAMP0(3, 1);

    unsigned long long ka = g_cand[2 * lane], kb = g_cand[2 * lane + 1];
    warp_top2(ka, kb);
    const int idx[2] = {key_index(ka), key_index(kb)};
    float acc[8];
    float hx[2][2], xo[2][2];
#pragma unroll
    for (int i = 0; i < 8; i++) acc[i] = 0.f;
#pragma unroll
    for (int u = 0; u < 2; u++) {
        const uint4* hp = (const uint4*)(g_h + (size_t)idx[u] * DM + 16 * lane);
        const uint4 ha = hp[0], hb = hp[1];
        const uint32_t ho = *(const uint32_t*)(g_h + (size_t)idx[u] * DM + 2 * tid);
        const float2 st = g_stat[idx[u]];
        const float inv = 1.f / st.y;
        const uint32_t hw[8] = {ha.x, ha.y, ha.z, ha.w, hb.x, hb.y, hb.z, hb.w};
#pragma unroll
        for (int k = 0; k < 8; k++) {
            const float x0 = rbf(rbf(bf_lo(hw[k]) - st.x) * inv), x1 = rbf(rbf(bf_hi(hw[k]) - st.x) * inv);
            const uint2 wa = wgu[2 * k], wb = wgu[2 * k + 1];
            acc[u * 4 + 0] = fmaf(x0, bf_lo(wa.x), fmaf(x1, bf_lo(wb.x), acc[u * 4 + 0]));
            acc[u * 4 + 1] = fmaf(x0, bf_hi(wa.x), fmaf(x1, bf_hi(wb.x), acc[u * 4 + 1]));
            acc[u * 4 + 2] = fmaf(x0, bf_lo(wa.y), fmaf(x1, bf_lo(wb.y), acc[u * 4 + 2]));
            acc[u * 4 + 3] = fmaf(x0, bf_hi(wa.y), fmaf(x1, bf_hi(wb.y), acc[u * 4 + 3]));
        }
        hx[u][0] = bf_lo(ho); hx[u][1] = bf_hi(ho);
        xo[u][0] = rbf(rbf(hx[u][0] - st.x) * inv); xo[u][1] = rbf(rbf(hx[u][1] - st.x) * inv);
    }
#define K4_STEP(O, N)                                                          \
    {                                                                          \
        const bool up = (lane & (O)) != 0;                                     \
        _Pragma("unroll") for (int i = 0; i < (N); i++) {                      \
            const float send = up ? acc[i] : acc[i + (N)];                     \
            const float keep = up ? acc[i + (N)] : acc[i];                     \
            acc[i] = keep + __shfl_xor_sync(0xffffffffu, send, (O));           \
        }                                                                      \
    }
    K4_STEP(16, 4) K4_STEP(8, 2) K4_STEP(4, 1)
    acc[0] += __shfl_xor_sync(0xffffffffu, acc[0], 2);
    acc[0] += __shfl_xor_sync(0xffffffffu, acc[0], 1);
    if ((lane & 3) == 0) {
        const int v = ((lane & 16) ? 4 : 0) + ((lane & 8) ? 2 : 0) + ((lane & 4) ? 1 : 0);
        s_gu[v >> 2][warp * 4 + (v & 3)] = acc[0];
    }
    __syncthreads();
    float y[2][2] = {{0.f, 0.f}, {0.f, 0.f}};
    {
        const int u = lane >> 4, c = lane & 15;
        const float gb = rbf(s_gu[u][c]);
        const float sg = rbf(gb / (1.f + __expf(-gb)));
        const float a = rbf(sg * rbf(s_gu[u][16 + c]));
#pragma unroll
        for (int f = 0; f < 16; f++) {
            const float a0 = __shfl_sync(0xffffffffu, a, f), a1 = __shfl_sync(0xffffffffu, a, 16 + f);
            const float w0 = bf_lo(wd[f]), w1 = bf_hi(wd[f]);
            y[0][0] = fmaf(a0, w0, y[0][0]); y[0][1] = fmaf(a0, w1, y[0][1]);
            y[1][0] = fmaf(a1, w0, y[1][0]); y[1][1] = fmaf(a1, w1, y[1][1]);
        }
    }
#pragma unroll
    for (int u = 0; u < 2; u++)
        asm volatile("red.global.add.v2.f32 [%0], {%1, %2};" ::"l"(g_y + u * DM + 2 * tid), "f"(y[u][0]), "f"(y[u][1]) : "memory");
    if (tid == 0) TSTAMP0(3, 2);
    __syncthreads();
    if (tid == 0) asm volatile("red.release.gpu.global.add.u32 [%0], 1;" ::"l"(&g_cnt) : "memory");
    if (tid == 0) TSTAMP0(3, 3);
    if (blockIdx.x == gridDim.x - 1) {
        if (tid == 0) {
            unsigned int c; int spins = 0;
            do { asm volatile("ld.acquire.gpu.global.u32 %0, [%1];" : "=r"(c) : "l"(&g_cnt) : "memory"); } while (c < gridDim.x && ++spins < (1 << 22));
        }
        __syncthreads();
        const float rv[2] = {key_value(ka), key_value(kb)};
#pragma unroll
        for (int u = 0; u < 2; u++) {
            const float2 yy = __ldcg((const float2*)(g_y + u * DM + 2 * tid));
            const float sig = rbf(1.f / (1.f + __expf(-rv[u])));
            const float o0 = hx[u][0] + rbf(xo[u][0] + rbf(rbf(yy.x) * sig));
            const float o1 = hx[u][1] + rbf(xo[u][1] + rbf(rbf(yy.y) * sig));
            *(uint32_t*)(out + (size_t)idx[u] * DM + 2 * tid) = pack_bf16(o0, o1);
        }
        if (tid == 0) TSTAMP0(3, 4);
    }
}

typedef CUresult (*PFN_encodeTiled)(CUtensorMap*, CUtensorMapDataType, cuuint32_t, void*, const cuuint64_t*, const cuuint64_t*,
                                    const cuuint32_t*, const cuuint32_t*, CUtensorMapInterleave, CUtensorMapSwizzle,
                                    CUtensorMapL2promotion, CUtensorMapFloatOOBfill);

void make_map(PFN_encodeTiled enc, CUtensorMap* m, const void* ptr, uint64_t cols, uint64_t rows, uint32_t bcols, uint32_t brows) {
    cuuint64_t dims[2] = {cols, rows};
    cuuint64_t strides[1] = {cols * 2};
    cuuint32_t box[2] = {bcols, brows};
    cuuint32_t es[2] = {1, 1};
    enc(m, CU_TENSOR_MAP_DATA_TYPE_BFLOAT16, 2, const_cast<void*>(ptr), dims, strides, box, es, CU_TENSOR_MAP_INTERLEAVE_NONE,
        CU_TENSOR_MAP_SWIZZLE_128B, CU_TENSOR_MAP_L2_PROMOTION_L2_256B, CU_TENSOR_MAP_FLOAT_OOB_FILL_NONE);
}

void make_map3(PFN_encodeTiled enc, CUtensorMap* m, const void* ptr, uint64_t d0, uint64_t rows, uint64_t d2, uint64_t row_stride_bytes,
               uint64_t d2_stride_bytes, uint32_t b0, uint32_t b1, uint32_t b2) {
    cuuint64_t dims[3] = {d0, rows, d2};
    cuuint64_t strides[2] = {row_stride_bytes, d2_stride_bytes};
    cuuint32_t box[3] = {b0, b1, b2};
    cuuint32_t es[3] = {1, 1, 1};
    enc(m, CU_TENSOR_MAP_DATA_TYPE_BFLOAT16, 3, const_cast<void*>(ptr), dims, strides, box, es, CU_TENSOR_MAP_INTERLEAVE_NONE,
        CU_TENSOR_MAP_SWIZZLE_128B, CU_TENSOR_MAP_L2_PROMOTION_L2_256B, CU_TENSOR_MAP_FLOAT_OOB_FILL_NONE);
}

template <typename... KArgs, typename... Args>
void launch(void (*kern)(KArgs...), int grid, int block, int smem, bool pdl, Args... args) {
    cudaLaunchConfig_t cfg = {};
    cfg.gridDim = dim3(grid);
    cfg.blockDim = dim3(block);
    cfg.dynamicSmemBytes = smem;
    cfg.stream = cudaStreamPerThread;
    cudaLaunchAttribute at[1];
    at[0].id = cudaLaunchAttributeProgrammaticStreamSerialization;
    at[0].val.programmaticStreamSerializationAllowed = 1;
    cfg.attrs = at;
    cfg.numAttrs = pdl ? 1 : 0;
    cudaLaunchKernelEx(&cfg, kern, KArgs(args)...);
}

}

extern "C" void kernel_launch(void* const* d_in, const int* in_sizes, int n_in, void* d_out, int out_size) {
    const __nv_bfloat16* x = (const __nv_bfloat16*)d_in[0];
    const __nv_bfloat16* wqkv = (const __nv_bfloat16*)d_in[1];
    const __nv_bfloat16* wo = (const __nv_bfloat16*)d_in[2];
    const __nv_bfloat16* w_r = (const __nv_bfloat16*)d_in[4];
    const __nv_bfloat16* w_gate = (const __nv_bfloat16*)d_in[5];
    const __nv_bfloat16* w_up = (const __nv_bfloat16*)d_in[6];
    const __nv_bfloat16* w_down = (const __nv_bfloat16*)d_in[7];
    __nv_bfloat16* out = (__nv_bfloat16*)d_out;

    static PFN_encodeTiled enc = nullptr;
    static void* g_o_ptr = nullptr;
    if (!enc) {
        cudaDriverEntryPointQueryResult qres;
        void* fn = nullptr;
        cudaGetDriverEntryPoint("cuTensorMapEncodeTiled", &fn, cudaEnableDefault, &qres);
        enc = (PFN_encodeTiled)fn;
        cudaGetSymbolAddress(&g_o_ptr, g_o);
        cudaFuncSetAttribute(k1_qkv, cudaFuncAttributeMaxDynamicSharedMemorySize, K1_SMEM);
        cudaFuncSetAttribute(k2_attn, cudaFuncAttributeMaxDynamicSharedMemorySize, K2_SMEM);
        cudaFuncSetAttribute(k3_proj, cudaFuncAttributeMaxDynamicSharedMemorySize, K3_SMEM);
    }
    CUtensorMap tm_x, tm_w, tm_o, tm_wo;
    make_map(enc, &tm_x, x, DM, SEQ, 64, 128);
    make_map3(enc, &tm_w, wqkv, DM, DM, 3, 3 * DM * 2, DM * 2, 64, 64, 3);
    make_map3(enc, &tm_o, g_o_ptr, 64, SEQ, 8, DM * 2, 128, 64, 64, 2);
    make_map3(enc, &tm_wo, wo, 64, DM, 8, DM * 2, 128, 64, 64, 2);

    const bool pdl = true;
    launch(k1_qkv, 128, 544, K1_SMEM, false, tm_x, tm_w);
    launch(k2_attn, 128, 512, K2_SMEM, pdl, (const uint8_t*)wo, (const uint8_t*)w_gate, (const uint8_t*)w_up, (const uint8_t*)w_down);
    launch(k3_proj, 128, 288, K3_SMEM, pdl, tm_o, tm_wo, x, w_r, out);
    launch(k4_moe, 112, 256, 0, pdl, w_gate, w_up, w_down, out);
}
```

```cpp
#include <cuda_runtime.h>
#include <cuda_bf16.h>
#include <cuda.h>
#include <stdint.h>

namespace {

constexpr int SEQ = 2048, DM = 512, NH = 32, FF = 1792;

__device__ __align__(1024) uint8_t g_q[NH * 2 * SEQ * 16];
__device__ __align__(1024) uint8_t g_kv[NH * 8 * 16384];
__device__ float g_norm[16 * NH * 3];
__device__ __align__(1024) __nv_bfloat16 g_o[SEQ * DM];
__device__ __align__(1024) __nv_bfloat16 g_h[SEQ * DM];
__device__ float2 g_stat[SEQ];
__device__ unsigned long long g_cand[64];
__device__ __align__(16) float g_y[2 * DM];
__device__ unsigned int g_cnt;
__device__ unsigned int g_epoch;
__device__ __align__(16) float4 g_ln1[SEQ];
__device__ __align__(16) float4 g_part[32 * 8 * 64];

#define TSTAMP(K, I)
#define TSTAMP0(K, I)
__device__ __forceinline__ uint32_t smem_u32(const void* p) { return (uint32_t)__cvta_generic_to_shared(p); }
__device__ __forceinline__ void wg_fence() { asm volatile("wgmma.fence.sync.aligned;" ::: "memory"); }
__device__ __forceinline__ void wg_commit() { asm volatile("wgmma.commit_group.sync.aligned;" ::: "memory"); }
template <int N> __device__ __forceinline__ void wg_wait() { asm volatile("wgmma.wait_group.sync.aligned %0;" ::"n"(N) : "memory"); }
template <int N> __device__ __forceinline__ void fence_regs(float (&r)[N]) {
#pragma unroll
    for (int i = 0; i < N; i++) asm volatile("" : "+f"(r[i])::"memory");
}
__device__ __forceinline__ uint64_t make_desc(uint32_t addr, uint32_t lbo, uint32_t sbo, uint32_t swz) {
    uint64_t d = 0;
    d |= (uint64_t)((addr & 0x3FFFF) >> 4);
    d |= (uint64_t)((lbo & 0x3FFFF) >> 4) << 16;
    d |= (uint64_t)((sbo & 0x3FFFF) >> 4) << 32;
    d |= (uint64_t)swz << 62;
    return d;
}
__device__ __forceinline__ void mbar_init(uint32_t bar, uint32_t cnt) {
    asm volatile("mbarrier.init.shared::cta.b64 [%0], %1;" ::"r"(bar), "r"(cnt) : "memory");
}
__device__ __forceinline__ void mbar_expect_tx(uint32_t bar, uint32_t bytes) {
    asm volatile("mbarrier.arrive.expect_tx.shared::cta.b64 _, [%0], %1;" ::"r"(bar), "r"(bytes) : "memory");
}
__device__ __forceinline__ void mbar_arrive(uint32_t bar) {
    asm volatile("mbarrier.arrive.shared::cta.b64 _, [%0];" ::"r"(bar) : "memory");
}
__device__ __forceinline__ void mbar_wait(uint32_t bar, uint32_t parity) {
    asm volatile(
        "{\n.reg .pred p;\nWAIT_%=:\n"
        "mbarrier.try_wait.parity.shared::cta.b64 p, [%0], %1;\n"
        "@p bra DONE_%=;\nbra WAIT_%=;\nDONE_%=:\n}\n" ::"r"(bar), "r"(parity) : "memory");
}
__device__ __forceinline__ void bulk_g2s(uint32_t dst, const void* src, uint32_t bytes, uint32_t bar) {
    asm volatile("cp.async.bulk.shared::cluster.global.mbarrier::complete_tx::bytes [%0], [%1], %2, [%3];" ::"r"(dst),
                 "l"(src), "r"(bytes), "r"(bar) : "memory");
}
__device__ __forceinline__ void bulk_s2g(void* dst, uint32_t src, uint32_t bytes) {
    asm volatile("cp.async.bulk.global.shared::cta.bulk_group [%0], [%1], %2;" ::"l"(dst), "r"(src), "r"(bytes) : "memory");
}
__device__ __forceinline__ void tma_load_2d(uint32_t dst, const CUtensorMap* tm, int c0, int c1, uint32_t bar) {
    asm volatile("cp.async.bulk.tensor.2d.shared::cluster.global.mbarrier::complete_tx::bytes [%0], [%1, {%3, %4}], [%2];" ::"r"(dst),
                 "l"(tm), "r"(bar), "r"(c0), "r"(c1) : "memory");
}
__device__ __forceinline__ void tma_load_3d(uint32_t dst, const CUtensorMap* tm, int c0, int c1, int c2, uint32_t bar) {
    asm volatile("cp.async.bulk.tensor.3d.shared::cluster.global.mbarrier::complete_tx::bytes [%0], [%1, {%3, %4, %5}], [%2];" ::"r"(dst),
                 "l"(tm), "r"(bar), "r"(c0), "r"(c1), "r"(c2) : "memory");
}
__device__ __forceinline__ void tma_load_2d_mc(uint32_t dst, const CUtensorMap* tm, int c0, int c1, uint32_t bar, uint16_t mask) {
    asm volatile("cp.async.bulk.tensor.2d.shared::cluster.global.mbarrier::complete_tx::bytes.multicast::cluster [%0], [%1, {%3, %4}], [%2], %5;" ::"r"(dst),
                 "l"(tm), "r"(bar), "r"(c0), "r"(c1), "h"(mask) : "memory");
}
__device__ __forceinline__ void mbar_arrive_cluster(uint32_t bar, uint32_t cta) {
    asm volatile("{\n.reg .b32 ra;\nmapa.shared::cluster.u32 ra, %0, %1;\nmbarrier.arrive.release.cluster.shared::cluster.b64 _, [ra];\n}" ::"r"(bar), "r"(cta) : "memory");
}
__device__ __forceinline__ void cluster_sync() {
    asm volatile("barrier.cluster.arrive.release.aligned;\nbarrier.cluster.wait.acquire.aligned;" ::: "memory");
}
__device__ __forceinline__ void prefetch_l2(const void* p, uint32_t bytes) {
    asm volatile("cp.async.bulk.prefetch.L2.global [%0], %1;" ::"l"(p), "r"(bytes) : "memory");
}
__device__ __forceinline__ void fence_proxy_async() { asm volatile("fence.proxy.async.shared::cta;" ::: "memory"); }
__device__ __forceinline__ void fence_barrier_init() { asm volatile("fence.mbarrier_init.release.cluster;" ::: "memory"); }
__device__ __forceinline__ void pdl_launch() { asm volatile("griddepcontrol.launch_dependents;" ::: "memory"); }
__device__ __forceinline__ void pdl_wait() { asm volatile("griddepcontrol.wait;" ::: "memory"); }
__device__ __forceinline__ void named_sync(int id, int n) { asm volatile("bar.sync %0, %1;" ::"r"(id), "r"(n) : "memory"); }
__device__ __forceinline__ void named_arrive(int id, int n) { asm volatile("bar.arrive %0, %1;" ::"r"(id), "r"(n) : "memory"); }

__device__ __forceinline__ float ex2f(float x) { float y; asm("ex2.approx.ftz.f32 %0, %1;" : "=f"(y) : "f"(x)); return y; }
__device__ __forceinline__ uint32_t pack_bf16(float lo, float hi) {
    uint32_t r; asm("cvt.rn.bf16x2.f32 %0, %1, %2;" : "=r"(r) : "f"(hi), "f"(lo)); return r;
}
__device__ __forceinline__ float bf_lo(uint32_t v) { return __uint_as_float(v << 16); }
__device__ __forceinline__ float bf_hi(uint32_t v) { return __uint_as_float(v & 0xFFFF0000u); }
__device__ __forceinline__ float rbf(float x) { return __bfloat162float(__float2bfloat16_rn(x)); }
__device__ __forceinline__ uint32_t fma_bf16x2(uint32_t a, uint32_t b, uint32_t c) {
    uint32_t r; asm("fma.rn.bf16x2 %0, %1, %2, %3;" : "=r"(r) : "r"(a), "r"(b), "r"(c)); return r;
}
__device__ __forceinline__ void stmatrix_x4(uint32_t addr, uint32_t r0, uint32_t r1, uint32_t r2, uint32_t r3) {
    asm volatile("stmatrix.sync.aligned.m8n8.x4.shared.b16 [%0], {%1, %2, %3, %4};" ::"r"(addr), "r"(r0), "r"(r1), "r"(r2), "r"(r3) : "memory");
}
__device__ __forceinline__ void stmatrix_x4_trans(uint32_t addr, uint32_t r0, uint32_t r1, uint32_t r2, uint32_t r3) {
    asm volatile("stmatrix.sync.aligned.m8n8.x4.trans.shared.b16 [%0], {%1, %2, %3, %4};" ::"r"(addr), "r"(r0), "r"(r1), "r"(r2), "r"(r3) : "memory");
}

__device__ __forceinline__ void wgmma_k1_n136(float (&d)[68], uint64_t desca, uint64_t descb, int scale_d) {
  asm volatile("{\n.reg .pred p;\nsetp.ne.b32 p, %70, 0;\n"
    "wgmma.mma_async.sync.aligned.m64n136k16.f32.bf16.bf16 "
    "{%0, %1, %2, %3, %4, %5, %6, %7, %8, %9, %10, %11, %12, %13, %14, %15, %16, %17, %18, %19, %20, %21, %22, %23, %24, %25, %26, %27, %28, %29, %30, %31, %32, %33, %34, %35, %36, %37, %38, %39, %40, %41, %42, %43, %44, %45, %46, %47, %48, %49, %50, %51, %52, %53, %54, %55, %56, %57, %58, %59, %60, %61, %62, %63, %64, %65, %66, %67}, "
    "%68, %69, p, 1, 1, 1, 0;\n}\n"
    : "+f"(d[0]), "+f"(d[1]), "+f"(d[2]), "+f"(d[3]), "+f"(d[4]), "+f"(d[5]), "+f"(d[6]), "+f"(d[7]), "+f"(d[8]), "+f"(d[9]), "+f"(d[10]), "+f"(d[11]), "+f"(d[12]), "+f"(d[13]), "+f"(d[14]), "+f"(d[15]), "+f"(d[16]), "+f"(d[17]), "+f"(d[18]), "+f"(d[19]), "+f"(d[20]), "+f"(d[21]), "+f"(d[22]), "+f"(d[23]), "+f"(d[24]), "+f"(d[25]), "+f"(d[26]), "+f"(d[27]), "+f"(d[28]), "+f"(d[29]), "+f"(d[30]), "+f"(d[31]), "+f"(d[32]), "+f"(d[33]), "+f"(d[34]), "+f"(d[35]), "+f"(d[36]), "+f"(d[37]), "+f"(d[38]), "+f"(d[39]), "+f"(d[40]), "+f"(d[41]), "+f"(d[42]), "+f"(d[43]), "+f"(d[44]), "+f"(d[45]), "+f"(d[46]), "+f"(d[47]), "+f"(d[48]), "+f"(d[49]), "+f"(d[50]), "+f"(d[51]), "+f"(d[52]), "+f"(d[53]), "+f"(d[54]), "+f"(d[55]), "+f"(d[56]), "+f"(d[57]), "+f"(d[58]), "+f"(d[59]), "+f"(d[60]), "+f"(d[61]), "+f"(d[62]), "+f"(d[63]), "+f"(d[64]), "+f"(d[65]), "+f"(d[66]), "+f"(d[67])
    : "l"(desca), "l"(descb), "r"(scale_d));
}
__device__ __forceinline__ void wgmma_qk_n64(float (&d)[32], uint32_t a0, uint32_t a1, uint32_t a2, uint32_t a3, uint64_t descb) {
  asm volatile("{\n.reg .pred p;\nsetp.ne.b32 p, 0, 0;\n"
    "wgmma.mma_async.sync.aligned.m64n64k16.f32.bf16.bf16 "
    "{%0, %1, %2, %3, %4, %5, %6, %7, %8, %9, %10, %11, %12, %13, %14, %15, %16, %17, %18, %19, %20, %21, %22, %23, %24, %25, %26, %27, %28, %29, %30, %31}, "
    "{%32, %33, %34, %35}, %36, p, 1, 1, 0;\n}\n"
    : "=f"(d[0]), "=f"(d[1]), "=f"(d[2]), "=f"(d[3]), "=f"(d[4]), "=f"(d[5]), "=f"(d[6]), "=f"(d[7]), "=f"(d[8]), "=f"(d[9]), "=f"(d[10]), "=f"(d[11]), "=f"(d[12]), "=f"(d[13]), "=f"(d[14]), "=f"(d[15]), "=f"(d[16]), "=f"(d[17]), "=f"(d[18]), "=f"(d[19]), "=f"(d[20]), "=f"(d[21]), "=f"(d[22]), "=f"(d[23]), "=f"(d[24]), "=f"(d[25]), "=f"(d[26]), "=f"(d[27]), "=f"(d[28]), "=f"(d[29]), "=f"(d[30]), "=f"(d[31])
    : "r"(a0), "r"(a1), "r"(a2), "r"(a3), "l"(descb));
}
__device__ __forceinline__ void wgmma_pv_n24(float (&d)[12], uint32_t a0, uint32_t a1, uint32_t a2, uint32_t a3, uint64_t descb) {
  asm volatile("{\n.reg .pred p;\nsetp.eq.b32 p, 0, 0;\n"
    "wgmma.mma_async.sync.aligned.m64n24k16.f32.bf16.bf16 "
    "{%0, %1, %2, %3, %4, %5, %6, %7, %8, %9, %10, %11}, "
    "{%12, %13, %14, %15}, %16, p, 1, 1, 1;\n}\n"
    : "+f"(d[0]), "+f"(d[1]), "+f"(d[2]), "+f"(d[3]), "+f"(d[4]), "+f"(d[5]), "+f"(d[6]), "+f"(d[7]), "+f"(d[8]), "+f"(d[9]), "+f"(d[10]), "+f"(d[11])
    : "r"(a0), "r"(a1), "r"(a2), "r"(a3), "l"(descb));
}
__device__ __forceinline__ void wgmma_k3_n64(float (&d)[32], uint64_t desca, uint64_t descb, int scale_d) {
  asm volatile("{\n.reg .pred p;\nsetp.ne.b32 p, %34, 0;\n"
    "wgmma.mma_async.sync.aligned.m64n64k16.f32.bf16.bf16 "
    "{%0, %1, %2, %3, %4, %5, %6, %7, %8, %9, %10, %11, %12, %13, %14, %15, %16, %17, %18, %19, %20, %21, %22, %23, %24, %25, %26, %27, %28, %29, %30, %31}, "
    "%32, %33, p, 1, 1, 0, 1;\n}\n"
    : "+f"(d[0]), "+f"(d[1]), "+f"(d[2]), "+f"(d[3]), "+f"(d[4]), "+f"(d[5]), "+f"(d[6]), "+f"(d[7]), "+f"(d[8]), "+f"(d[9]), "+f"(d[10]), "+f"(d[11]), "+f"(d[12]), "+f"(d[13]), "+f"(d[14]), "+f"(d[15]), "+f"(d[16]), "+f"(d[17]), "+f"(d[18]), "+f"(d[19]), "+f"(d[20]), "+f"(d[21]), "+f"(d[22]), "+f"(d[23]), "+f"(d[24]), "+f"(d[25]), "+f"(d[26]), "+f"(d[27]), "+f"(d[28]), "+f"(d[29]), "+f"(d[30]), "+f"(d[31])
    : "l"(desca), "l"(descb), "r"(scale_d));
}

constexpr int K1_XS = 17408;
constexpr int K1_WS = 24576;
constexpr int K1_ST = K1_XS + K1_WS;
constexpr int K1_NST = 5;
constexpr int K1_OFF_MISC = K1_NST * K1_ST;
constexpr int K1_SMEM = K1_OFF_MISC + 2048 + 1024;
constexpr float QSCALE = 0.25f * 1.4426950408889634f;

__global__ void __launch_bounds__(544, 1)
k1_qkv(const __grid_constant__ CUtensorMap tm_x, const __grid_constant__ CUtensorMap tm_w, const __nv_bfloat16* __restrict__ x) {
    extern __shared__ uint8_t smem_raw[];
    const uint32_t sraw = smem_u32(smem_raw);
    const uint32_t sb = (sraw + 1023) & ~1023u;
    uint8_t* sp = smem_raw + (sb - sraw);
    const uint32_t full = sb + K1_OFF_MISC;
    const uint32_t empty = full + 64;
    float* s_m = (float*)(sp + K1_OFF_MISC + 256);
    float* s_r = s_m + 128;

    const int tid = threadIdx.x, warp = tid >> 5, lane = tid & 31;
    const int mt = blockIdx.x >> 3, nt = blockIdx.x & 7;
    if (tid == 0) TSTAMP0(0, 0);
    pdl_launch();
    if (tid == 0) {
        for (int i = 0; i < K1_NST; i++) { mbar_init(full + 8 * i, 1); mbar_init(empty + 8 * i, 3); }
        fence_barrier_init();
    }
    if (tid < K1_NST * 64) {
        *(uint4*)(sp + (tid >> 6) * K1_ST + 16384 + (tid & 63) * 16) =
            make_uint4(0x3F803F80u, 0x3F803F80u, 0x3F803F80u, 0x3F803F80u);
    }
    fence_proxy_async();
    __syncthreads();

    if (warp == 16) {
        if (lane == 0) {
            for (int kb = 0; kb < 8; kb++) {
                const int s = kb % K1_NST;
                if (kb >= K1_NST) mbar_wait(empty + 8 * s, 0);
                mbar_expect_tx(full + 8 * s, 16384 + K1_WS);
                tma_load_2d(sb + s * K1_ST, &tm_x, kb * 64, mt * 128, full + 8 * s);
                tma_load_3d(sb + s * K1_ST + K1_XS, &tm_w, nt * 64, kb * 64, 0, full + 8 * s);
            }
        } else if (lane == 1) {
            if (blockIdx.x == 0) g_cnt = 0;
        }
        if (blockIdx.x == 0) for (int i = lane; i < 2 * DM; i += 32) g_y[i] = 0.f;
        for (int i = lane; i < 128; i += 32) g_part[blockIdx.x * 128 + i] = make_float4(0.f, 0.f, 0.f, 0.f);
    } else if (warp >= 12) {
        const int r = tid - 384;
        const unsigned int tag = *(volatile unsigned int*)&g_epoch + 1u;
        {
            const int row = mt * 128 + nt * 16 + (r >> 3);
            const uint4* xp = (const uint4*)(x + (size_t)row * DM) + (r & 7);
            uint4 v[8];
#pragma unroll
            for (int i = 0; i < 8; i++) v[i] = __ldg(xp + i * 8);
            float s1 = 0.f;
#pragma unroll
            for (int i = 0; i < 8; i++)
                s1 += ((bf_lo(v[i].x) + bf_hi(v[i].x)) + (bf_lo(v[i].y) + bf_hi(v[i].y))) + ((bf_lo(v[i].z) + bf_hi(v[i].z)) + (bf_lo(v[i].w) + bf_hi(v[i].w)));
#pragma unroll
            for (int o = 1; o < 8; o <<= 1) s1 += __shfl_xor_sync(0xffffffffu, s1, o);
            const float mean = s1 * (1.f / DM);
            float q0 = 0.f, q1 = 0.f;
#pragma unroll
            for (int i = 0; i < 8; i++) {
                const uint32_t w[4] = {v[i].x, v[i].y, v[i].z, v[i].w};
#pragma unroll
                for (int j = 0; j < 4; j++) {
                    const float a = bf_lo(w[j]) - mean, b = bf_hi(w[j]) - mean;
                    q0 = fmaf(a, a, q0); q1 = fmaf(b, b, q1);
                }
            }
            float q = q0 + q1;
#pragma unroll
            for (int o = 1; o < 8; o <<= 1) q += __shfl_xor_sync(0xffffffffu, q, o);
            const float den = rbf(sqrtf(rbf(rbf(q * (1.f / DM)) + 1e-5f)));
            if ((r & 7) == 0)
                asm volatile("st.relaxed.gpu.global.v4.f32 [%0], {%1, %2, %3, %4};" ::"l"(g_ln1 + row), "f"(rbf(mean)), "f"(1.f / den),
                             "f"(__uint_as_float(tag)), "f"(0.f) : "memory");
        }
        if (r == 0) TSTAMP0(0, 6);
        {
            float4 v;
            int spins = 0;
            do {
                asm volatile("ld.relaxed.gpu.global.v4.f32 {%0, %1, %2, %3}, [%4];" : "=f"(v.x), "=f"(v.y), "=f"(v.z), "=f"(v.w) : "l"(g_ln1 + mt * 128 + r) : "memory");
            } while (__float_as_uint(v.z) != tag && ++spins < (1 << 22));
            s_m[r] = v.x;
            s_r[r] = v.y;
        }
        if (r == 0) TSTAMP0(0, 7);
        named_arrive(1, 512);
    } else {
        const int part = warp >> 2, hw = warp & 3;
        float acc[68];
#pragma unroll
        for (int i = 0; i < 68; i++) acc[i] = 0.f;
        fence_regs(acc);
#pragma unroll 1
        for (int kb = 0; kb < 8; kb++) {
            const int s = kb % K1_NST;
            mbar_wait(full + 8 * s, (kb / K1_NST) & 1);
            const uint64_t da = make_desc(sb + s * K1_ST + K1_XS + part * 8192, 1024, 1024, 1);
            const uint64_t db = make_desc(sb + s * K1_ST, 16, 1024, 1);
            wg_fence();
#pragma unroll
            for (int k = 0; k < 4; k++) wgmma_k1_n136(acc, da + k * 128, db + k * 2, (kb | k) != 0);
            wg_commit();
            if (kb > 0 && kb <= 8 - K1_NST) {
                wg_wait<1>();
                if ((tid & 127) == 0) mbar_arrive(empty + 8 * (kb - 1));
            }
        }
        wg_wait<0>();
        fence_regs(acc);
        if (tid == 0) TSTAMP0(0, 1);
        named_sync(1, 512);
        if (tid == 0) TSTAMP0(0, 2);

        const int t = lane & 3;
        const float cs0 = acc[64], cs1 = acc[66];
        const float sc = (part == 0) ? QSCALE : 1.f;
        const uint32_t stg = sb + (hw >> 1) * K1_ST + K1_XS + part * 8192 + (hw & 1) * 4096;
        const uint32_t st_addr = stg + ((lane >> 3) & 1) * 2048 + ((lane >> 4) * 8 + (lane & 7)) * 16;
#pragma unroll
        for (int j = 0; j < 16; j += 2) {
            uint32_t rr[4];
#pragma unroll
            for (int u = 0; u < 2; u++) {
                const int jj = j + u;
                const float2 m2 = *(const float2*)(s_m + 8 * jj + 2 * t);
                const float2 r2 = *(const float2*)(s_r + 8 * jj + 2 * t);
                const float ra = r2.x * sc, rb = r2.y * sc;
                rr[2 * u] = pack_bf16((acc[4 * jj] - m2.x * cs0) * ra, (acc[4 * jj + 1] - m2.y * cs0) * rb);
                rr[2 * u + 1] = pack_bf16((acc[4 * jj + 2] - m2.x * cs1) * ra, (acc[4 * jj + 3] - m2.y * cs1) * rb);
            }
            stmatrix_x4_trans(st_addr + j * 128, rr[0], rr[1], rr[2], rr[3]);
        }
        __syncwarp();
        if (tid == 0) TSTAMP0(0, 4);
        float nmax = 0.f;
#pragma unroll
        for (int i = 0; i < 4; i++) {
            const int tok = lane + 32 * i;
            const uint4 a = *(const uint4*)(sp + (stg - sb) + tok * 16);
            const uint4 b = *(const uint4*)(sp + (stg - sb) + 2048 + tok * 16);
            const uint32_t w[8] = {a.x, a.y, a.z, a.w, b.x, b.y, b.z, b.w};
            float n2 = 0.f;
#pragma unroll
            for (int q = 0; q < 8; q++) {
                const float lo = bf_lo(w[q]), hi = bf_hi(w[q]);
                n2 = fmaf(lo, lo, n2); n2 = fmaf(hi, hi, n2);
            }
            nmax = (n2 > nmax || n2 != n2) ? n2 : nmax;
        }
#pragma unroll
        for (int o = 16; o > 0; o >>= 1) {
            const float v = __shfl_xor_sync(0xffffffffu, nmax, o);
            nmax = (v > nmax || v != v) ? v : nmax;
        }
        if (tid == 0) TSTAMP0(0, 5);
        fence_proxy_async();
        __syncwarp();
        if (lane == 0) {
            const int head = nt * 4 + hw;
            g_norm[(mt * NH + head) * 3 + part] = nmax;
            uint8_t* dst;
            uint32_t hstride;
            if (part == 0) { dst = g_q + (size_t)head * 65536 + mt * 2048; hstride = 32768; }
            else { dst = g_kv + (size_t)head * 131072 + (mt >> 1) * 16384 + (part - 1) * 8192 + (mt & 1) * 2048; hstride = 4096; }
            bulk_s2g(dst, stg, 2048);
            bulk_s2g(dst + hstride, stg + 2048, 2048);
            asm volatile("cp.async.bulk.commit_group;" ::: "memory");
            asm volatile("cp.async.bulk.wait_group.read 0;" ::: "memory");
            if (tid == 0) TSTAMP0(0, 3);
        }
    }
}

constexpr int K2_CH_G = 16384, K2_CH_S = 20480, K2_NCH = 8;
constexpr int K2_SMEM = K2_NCH * K2_CH_S + 128 + 1024;

__device__ __forceinline__ uint32_t exp2_pair_poly(float s0, float s1) {
    const float KB = 65536.0f + 127.0f;
    const float t0 = s0 + KB, t1 = s1 + KB;
    const uint32_t w = __byte_perm(__float_as_uint(t0), __float_as_uint(t1), 0x5410);
    uint32_t z;
    asm("lop3.b32 %0, %1, %2, %3, 0xEA;" : "=r"(z) : "r"(w), "r"(0x007F007Fu), "r"(0x3F803F80u));
    uint32_t p = fma_bf16x2(0x3eab3eabu, z, 0xbc73bc73u);
    p = fma_bf16x2(p, z, 0x3f2f3f2fu);
    return p + w - z;
}
constexpr uint32_t K2_EMASK = 0x5757u;
template <int LO, int HI>
__device__ __forceinline__ void softmax_part(const float (&s)[32], uint32_t (&p)[16]) {
#pragma unroll
    for (int i = LO; i < HI; i++) {
        if ((K2_EMASK >> i) & 1) p[i] = exp2_pair_poly(s[2 * i], s[2 * i + 1]);
        else p[i] = pack_bf16(ex2f(s[2 * i]), ex2f(s[2 * i + 1]));
    }
}
#define K2_PV(P, OFF)                                                                              \
    _Pragma("unroll") for (int kk = 0; kk < 4; kk++)                                               \
        wgmma_pv_n24(o, P[4 * kk], P[4 * kk + 1], P[4 * kk + 2], P[4 * kk + 3], dv + ((OFF) + kk * 16));

__global__ void __launch_bounds__(512, 1)
k2_attn(const uint8_t* __restrict__ wo, const uint8_t* __restrict__ w_gate, const uint8_t* __restrict__ w_up, const uint8_t* __restrict__ w_down) {
    extern __shared__ uint8_t smem_raw[];
    const uint32_t sraw = smem_u32(smem_raw);
    const uint32_t sb = (sraw + 1023) & ~1023u;
    uint8_t* sp = smem_raw + (sb - sraw);
    const uint32_t bars = sb + K2_NCH * K2_CH_S;
    const int tid = threadIdx.x;
    const int head = blockIdx.x >> 2, quarter = blockIdx.x & 3;
    if (tid == 0) TSTAMP0(1, 0);
    pdl_launch();
    if (tid == 0) {
        for (int c = 0; c < K2_NCH; c++) mbar_init(bars + 8 * c, 1);
        fence_barrier_init();
    }
    if (tid == 32) {
        prefetch_l2(wo + blockIdx.x * 4096, 4096);
        prefetch_l2(w_gate + blockIdx.x * 14336, 14336);
        prefetch_l2(w_up + blockIdx.x * 14336, 14336);
        prefetch_l2(w_down + blockIdx.x * 14336, 14336);
    }
    for (int i = tid; i < K2_NCH * 256; i += 512)
        *(uint4*)(sp + (i >> 8) * K2_CH_S + 16384 + (i & 255) * 16) =
            make_uint4(0x3F803F80u, 0x3F803F80u, 0x3F803F80u, 0x3F803F80u);
    fence_proxy_async();
    __syncthreads();
    pdl_wait();
    if (tid == 0) TSTAMP0(1, 1);
    if (tid == 0) {
        const uint8_t* src = g_kv + (size_t)head * (K2_NCH * K2_CH_G);
        for (int c = 0; c < K2_NCH; c++) {
            mbar_expect_tx(bars + 8 * c, K2_CH_G);
            bulk_g2s(sb + c * K2_CH_S, src + c * K2_CH_G, K2_CH_G, bars + 8 * c);
        }
    }
    const int wg = tid >> 7, warp = (tid >> 5) & 3, lane = tid & 31, g = lane >> 2, t = lane & 3;

    bool fast;
    {
        const int m16 = lane & 15;
        float kn = g_norm[(m16 * NH + head) * 3 + 1];
        float vn = g_norm[(m16 * NH + head) * 3 + 2];
        float qn = g_norm[((quarter * 4 + (lane & 3)) * NH + head) * 3 + 0];
        bool bad = !(kn < 1e30f) || !(vn < 1e30f) || !(qn < 1e30f);
#pragma unroll
        for (int o = 8; o > 0; o >>= 1) {
            kn = fmaxf(kn, __shfl_xor_sync(0xffffffffu, kn, o));
            qn = fmaxf(qn, __shfl_xor_sync(0xffffffffu, qn, o));
        }
        bad = __any_sync(0xffffffffu, bad);
        fast = !bad && (qn * kn <= 3500.f);
    }
    const uint64_t dk0 = make_desc(sb, 4096, 128, 0);
    const uint64_t dv0 = make_desc(sb + 8192, 128, 4096, 0);

#pragma unroll 1
    for (int pass = 0; pass < 2; pass++) {
        const int row0 = quarter * 512 + pass * 256 + wg * 64 + warp * 16 + g;
        uint32_t qa[4];
        {
            const uint8_t* qb = g_q + (size_t)head * 65536 + row0 * 16 + t * 4;
            qa[0] = *(const uint32_t*)(qb);
            qa[1] = *(const uint32_t*)(qb + 128);
            qa[2] = *(const uint32_t*)(qb + 32768);
            qa[3] = *(const uint32_t*)(qb + 32768 + 128);
        }
        float o[12];
#pragma unroll
        for (int i = 0; i < 12; i++) o[i] = 0.f;
        fence_regs(o);
        if (fast) {
#pragma unroll 1
            for (int c = 0; c < K2_NCH; c++) {
                const uint64_t dk = dk0 + (uint64_t)(c * (K2_CH_S >> 4));
                const uint64_t dv = dv0 + (uint64_t)(c * (K2_CH_S >> 4));
                float s0[32], s1[32], s2[32], s3[32];
                uint32_t p0[16], p1[16], p2[16], p3[16];
                mbar_wait(bars + 8 * c, 0);
                wg_wait<1>();
                wg_fence();
                wgmma_qk_n64(s0, qa[0], qa[1], qa[2], qa[3], dk);
                wg_commit();
                wg_wait<1>();
                wg_fence();
                wgmma_qk_n64(s1, qa[0], qa[1], qa[2], qa[3], dk + 64);
                wg_commit();
                wg_wait<1>();
                fence_regs(s0);
                softmax_part<0, 16>(s0, p0);
                wg_fence();
                K2_PV(p0, 0);
                wg_commit();
                wg_wait<1>();
                fence_regs(s1);
                softmax_part<0, 8>(s1, p1);
                wg_wait<0>();
                wg_fence();
                wgmma_qk_n64(s2, qa[0], qa[1], qa[2], qa[3], dk + 128);
                wg_commit();
                softmax_part<8, 16>(s1, p1);
                wg_fence();
                K2_PV(p1, 64);
                wg_commit();
                wg_wait<1>();
                fence_regs(s2);
                softmax_part<0, 8>(s2, p2);
                wg_wait<0>();
                wg_fence();
                wgmma_qk_n64(s3, qa[0], qa[1], qa[2], qa[3], dk + 192);
                wg_commit();
                softmax_part<8, 16>(s2, p2);
                wg_fence();
                K2_PV(p2, 128);
                wg_commit();
                wg_wait<1>();
                fence_regs(s3);
                softmax_part<0, 16>(s3, p3);
                wg_fence();
                K2_PV(p3, 192);
                wg_commit();
            }
            wg_wait<0>();
            fence_regs(o);
        } else {
            float m0 = -INFINITY, m1 = -INFINITY;
#pragma unroll 1
            for (int b = 0; b < 32; b++) {
                const int c = b >> 2;
                const uint64_t dk = dk0 + (uint64_t)(c * (K2_CH_S >> 4) + (b & 3) * 64);
                const uint64_t dv = dv0 + (uint64_t)(c * (K2_CH_S >> 4) + (b & 3) * 64);
                float s[32];
                uint32_t p[16];
                mbar_wait(bars + 8 * c, 0);
                wg_fence();
                wgmma_qk_n64(s, qa[0], qa[1], qa[2], qa[3], dk);
                wg_commit();
                wg_wait<0>();
                fence_regs(s);
                float x0 = s[0], x1 = s[2];
#pragma unroll
                for (int j = 0; j < 8; j++) {
                    x0 = fmaxf(x0, fmaxf(s[4 * j], s[4 * j + 1]));
                    x1 = fmaxf(x1, fmaxf(s[4 * j + 2], s[4 * j + 3]));
                }
                x0 = fmaxf(x0, __shfl_xor_sync(0xffffffffu, x0, 1));
                x0 = fmaxf(x0, __shfl_xor_sync(0xffffffffu, x0, 2));
                x1 = fmaxf(x1, __shfl_xor_sync(0xffffffffu, x1, 1));
                x1 = fmaxf(x1, __shfl_xor_sync(0xffffffffu, x1, 2));
                const float n0 = fmaxf(m0, x0), n1 = fmaxf(m1, x1);
                const float c0 = ex2f(m0 - n0), c1 = ex2f(m1 - n1);
                m0 = n0; m1 = n1;
#pragma unroll
                for (int j = 0; j < 3; j++) {
                    o[4 * j] *= c0; o[4 * j + 1] *= c0; o[4 * j + 2] *= c1; o[4 * j + 3] *= c1;
                }
#pragma unroll
                for (int j = 0; j < 8; j++) {
                    p[2 * j] = pack_bf16(ex2f(s[4 * j] - n0), ex2f(s[4 * j + 1] - n0));
                    p[2 * j + 1] = pack_bf16(ex2f(s[4 * j + 2] - n1), ex2f(s[4 * j + 3] - n1));
                }
                fence_regs(o);
                wg_fence();
                K2_PV(p, 0);
                wg_commit();
                wg_wait<0>();
                fence_regs(o);
            }
        }
        const float inv0 = 1.f / o[8], inv1 = 1.f / o[10];
        uint32_t* out0 = (uint32_t*)(g_o + (size_t)row0 * DM + head * 16);
        uint32_t* out1 = (uint32_t*)(g_o + (size_t)(row0 + 8) * DM + head * 16);
        out0[t] = pack_bf16(o[0] * inv0, o[1] * inv0);
        out0[4 + t] = pack_bf16(o[4] * inv0, o[5] * inv0);
        out1[t] = pack_bf16(o[2] * inv1, o[3] * inv1);
        out1[4 + t] = pack_bf16(o[6] * inv1, o[7] * inv1);
        if (tid == 0) TSTAMP0(1, 2 + pass);
    }
}

constexpr int K3_OFF_W = 65536;
constexpr int K3_OFF_MISC = K3_OFF_W + 131072;
constexpr int K3_SMEM = K3_OFF_MISC + 128 + 512 + 1024;

__device__ __forceinline__ unsigned long long make_key(float r_bf, int idx) {
    uint32_t u = __float_as_uint(r_bf);
    u = (u & 0x80000000u) ? ~u : (u | 0x80000000u);
    return ((unsigned long long)u << 32) | (uint32_t)(0x7FFFFFFF - idx);
}
__device__ __forceinline__ float key_value(unsigned long long k) {
    uint32_t u = (uint32_t)(k >> 32);
    u = (u & 0x80000000u) ? (u & 0x7FFFFFFFu) : ~u;
    return __uint_as_float(u);
}
__device__ __forceinline__ int key_index(unsigned long long k) { return 0x7FFFFFFF - (int)(uint32_t)k; }
__device__ __forceinline__ void warp_top2(unsigned long long& a, unsigned long long& b) {
#pragma unroll
    for (int o = 16; o > 0; o >>= 1) {
        const unsigned long long c = __shfl_xor_sync(0xffffffffu, a, o);
        const unsigned long long d = __shfl_xor_sync(0xffffffffu, b, o);
        const unsigned long long hi = a > c ? a : c, lo = a > c ? c : a;
        const unsigned long long m = b > d ? b : d;
        a = hi;
        b = lo > m ? lo : m;
    }
}

__global__ void __launch_bounds__(288, 1)
k3_proj(const __grid_constant__ CUtensorMap tm_o, const __grid_constant__ CUtensorMap tm_wo,
        const __nv_bfloat16* __restrict__ x, const __nv_bfloat16* __restrict__ w_r, __nv_bfloat16* __restrict__ out) {
    extern __shared__ uint8_t smem_raw[];
    const uint32_t sraw = smem_u32(smem_raw);
    const uint32_t sb = (sraw + 1023) & ~1023u;
    uint8_t* sp = smem_raw + (sb - sraw);
    const uint32_t obar = sb + K3_OFF_MISC;
    const uint32_t wbar = obar + 64;
    unsigned long long* s_key = (unsigned long long*)(sp + K3_OFF_MISC + 128);

    const int tid = threadIdx.x, warp = tid >> 5, lane = tid & 31;
    const int mt = blockIdx.x >> 2, nt = blockIdx.x & 3;
    if (tid == 0) TSTAMP0(2, 0);

    pdl_launch();
    if (tid == 0) {
        for (int i = 0; i < 16; i++) mbar_init(obar + 8 * i, 1);
        fence_barrier_init();
    }
    __syncthreads();

    if (warp == 8) {
        if (lane == 0) {
            for (int kb = 0; kb < 8; kb++) {
                mbar_expect_tx(wbar + 8 * kb, 16384);
                tma_load_3d(sb + K3_OFF_W + kb * 16384, &tm_wo, 0, kb * 64, nt * 2, wbar + 8 * kb);
            }
            pdl_wait();
            TSTAMP0(2, 1);
            for (int k2 = 0; k2 < 4; k2++) {
                mbar_expect_tx(obar + 8 * k2, 16384);
                tma_load_3d(sb + k2 * 16384, &tm_o, 0, mt * 64, k2 * 2, obar + 8 * k2);
            }
        }
        return;
    }
    const int wg = warp >> 2, wi = warp & 3, g = lane >> 2, t = lane & 3;
    const int r0 = mt * 64 + wi * 16 + g;
    const int cb = nt * 128 + wg * 64;
    uint32_t xr[16], wr[8];
#pragma unroll
    for (int j = 0; j < 8; j++) {
        xr[2 * j] = *(const uint32_t*)(x + (size_t)r0 * DM + cb + 8 * j + 2 * t);
        xr[2 * j + 1] = *(const uint32_t*)(x + (size_t)(r0 + 8) * DM + cb + 8 * j + 2 * t);
        wr[j] = *(const uint32_t*)(w_r + cb + 8 * j + 2 * t);
    }
    float wsum = 0.f;
    {
        const uint4 a = *(const uint4*)(w_r + lane * 16), b = *(const uint4*)(w_r + lane * 16 + 8);
        const uint32_t w[8] = {a.x, a.y, a.z, a.w, b.x, b.y, b.z, b.w};
#pragma unroll
        for (int i = 0; i < 8; i++) wsum += bf_lo(w[i]) + bf_hi(w[i]);
#pragma unroll
        for (int o = 16; o > 0; o >>= 1) wsum += __shfl_xor_sync(0xffffffffu, wsum, o);
    }
    float acc[32];
#pragma unroll
    for (int i = 0; i < 32; i++) acc[i] = 0.f;
    fence_regs(acc);
#pragma unroll 1
    for (int kb = 0; kb < 8; kb++) {
        mbar_wait(wbar + 8 * kb, 0);
        mbar_wait(obar + 8 * (kb >> 1), 0);
        const uint64_t da = make_desc(sb + kb * 8192, 16, 1024, 1);
        const uint64_t db = make_desc(sb + K3_OFF_W + kb * 16384 + wg * 8192, 1024, 1024, 1);
        wg_fence();
#pragma unroll
        for (int k = 0; k < 4; k++) wgmma_k3_n64(acc, da + k * 2, db + k * 128, (kb | k) != 0);
        wg_commit();
    }
    wg_wait<0>();
    fence_regs(acc);
    if (tid == 0) TSTAMP0(2, 2);
    float hv[32];
    float s0 = 0.f, s1 = 0.f, d0 = 0.f, d1 = 0.f;
#pragma unroll
    for (int j = 0; j < 8; j++) {
        hv[4 * j] = rbf(bf_lo(xr[2 * j]) + rbf(acc[4 * j]));
        hv[4 * j + 1] = rbf(bf_hi(xr[2 * j]) + rbf(acc[4 * j + 1]));
        hv[4 * j + 2] = rbf(bf_lo(xr[2 * j + 1]) + rbf(acc[4 * j + 2]));
        hv[4 * j + 3] = rbf(bf_hi(xr[2 * j + 1]) + rbf(acc[4 * j + 3]));
        const float wl = bf_lo(wr[j]), wh = bf_hi(wr[j]);
        s0 += hv[4 * j] + hv[4 * j + 1];
        s1 += hv[4 * j + 2] + hv[4 * j + 3];
        d0 = fmaf(hv[4 * j], wl, fmaf(hv[4 * j + 1], wh, d0));
        d1 = fmaf(hv[4 * j + 2], wl, fmaf(hv[4 * j + 3], wh, d1));
    }
#pragma unroll
    for (int o = 1; o < 4; o <<= 1) {
        s0 += __shfl_xor_sync(0xffffffffu, s0, o);
        s1 += __shfl_xor_sync(0xffffffffu, s1, o);
        d0 += __shfl_xor_sync(0xffffffffu, d0, o);
        d1 += __shfl_xor_sync(0xffffffffu, d1, o);
    }
    const float mu0 = s0 * (1.f / 64), mu1 = s1 * (1.f / 64);
    float q0 = 0.f, q1 = 0.f;
#pragma unroll
    for (int j = 0; j < 8; j++) {
        float a = hv[4 * j] - mu0, b = hv[4 * j + 1] - mu0, c = hv[4 * j + 2] - mu1, d = hv[4 * j + 3] - mu1;
        q0 = fmaf(a, a, fmaf(b, b, q0));
        q1 = fmaf(c, c, fmaf(d, d, q1));
    }
#pragma unroll
    for (int o = 1; o < 4; o <<= 1) {
        q0 += __shfl_xor_sync(0xffffffffu, q0, o);
        q1 += __shfl_xor_sync(0xffffffffu, q1, o);
    }
    float4* part = g_part + (size_t)mt * 512 + wi * 16 + g;
    if (t < 2) {
        float4* dst = part + (nt * 2 + wg) * 64 + t * 8;
        const float a = t ? mu1 : mu0, b = t ? q1 : q0, c = t ? d1 : d0;
        asm volatile("st.relaxed.gpu.global.v4.f32 [%0], {%1, %2, %3, %4};" ::"l"(dst), "f"(a), "f"(b), "f"(c), "f"(1.0f) : "memory");
    }
    named_sync(2, 256);
    const uint32_t stg_o = sb + warp * 4096;
    const uint32_t stg_h = stg_o + 2048;
    const int srow = (lane & 7) + ((lane >> 3) & 1) * 8;
    const int sj = lane >> 4;
#pragma unroll
    for (int j = 0; j < 8; j += 2) {
        const uint32_t off = srow * 128 + (((j + sj) ^ (srow & 7)) << 4);
        stmatrix_x4(stg_h + off, pack_bf16(hv[4 * j], hv[4 * j + 1]), pack_bf16(hv[4 * j + 2], hv[4 * j + 3]),
                    pack_bf16(hv[4 * j + 4], hv[4 * j + 5]), pack_bf16(hv[4 * j + 6], hv[4 * j + 7]));
    }
    __syncwarp();
#pragma unroll
    for (int i = 0; i < 4; i++) {
        const int row = i * 4 + (lane >> 3), ch = lane & 7;
        const uint4 vh = *(const uint4*)(sp + warp * 4096 + 2048 + row * 128 + ((ch ^ (row & 7)) << 4));
        *(uint4*)(g_h + (size_t)(mt * 64 + wi * 16 + row) * DM + cb + ch * 8) = vh;
    }
    float mean[2], den[2], rr[2];
    {
        float4 v[4];
        int spins = 0;
        while (true) {
#pragma unroll
            for (int i = 0; i < 4; i++) {
                const float4* p = part + (t + (i & 1) * 4) * 64 + (i >> 1) * 8;
                asm volatile("ld.relaxed.gpu.global.v4.f32 {%0, %1, %2, %3}, [%4];" : "=f"(v[i].x), "=f"(v[i].y), "=f"(v[i].z), "=f"(v[i].w) : "l"(p) : "memory");
            }
            const bool ok = (v[0].w != 0.f) && (v[1].w != 0.f) && (v[2].w != 0.f) && (v[3].w != 0.f);
            if (__all_sync(0xffffffffu, ok) || ++spins > (1 << 22)) break;
        }
#pragma unroll
        for (int u = 0; u < 2; u++) {
            float mu = v[2 * u].x + v[2 * u + 1].x, m2 = v[2 * u].y + v[2 * u + 1].y, hw = v[2 * u].z + v[2 * u + 1].z;
#pragma unroll
            for (int o = 1; o < 4; o <<= 1) {
                mu += __shfl_xor_sync(0xffffffffu, mu, o);
                m2 += __shfl_xor_sync(0xffffffffu, m2, o);
                hw += __shfl_xor_sync(0xffffffffu, hw, o);
            }
            mu *= 0.125f;
            const float da = v[2 * u].x - mu, db = v[2 * u + 1].x - mu;
            float dd = 64.f * (da * da + db * db);
#pragma unroll
            for (int o = 1; o < 4; o <<= 1) dd += __shfl_xor_sync(0xffffffffu, dd, o);
            m2 += dd;
            mean[u] = rbf(mu);
            den[u] = rbf(sqrtf(rbf(rbf(m2 * (1.f / DM)) + 1e-5f)));
            rr[u] = rbf((hw - mean[u] * wsum) / den[u]);
        }
    }
    if (tid == 0) TSTAMP0(2, 3);
    const float i0 = 1.f / den[0], i1 = 1.f / den[1];
#pragma unroll
    for (int j = 0; j < 8; j += 2) {
        uint32_t ro[4];
#pragma unroll
        for (int u = 0; u < 2; u++) {
            const int jj = j + u;
            const float a = hv[4 * jj], b = hv[4 * jj + 1], c = hv[4 * jj + 2], d = hv[4 * jj + 3];
            const float na = rbf(rbf(a - mean[0]) * i0), nb = rbf(rbf(b - mean[0]) * i0);
            const float nc = rbf(rbf(c - mean[1]) * i1), nd = rbf(rbf(d - mean[1]) * i1);
            ro[2 * u] = pack_bf16(a + na, b + nb);
            ro[2 * u + 1] = pack_bf16(c + nc, d + nd);
        }
        const uint32_t off = srow * 128 + (((j + sj) ^ (srow & 7)) << 4);
        stmatrix_x4(stg_o + off, ro[0], ro[1], ro[2], ro[3]);
    }
    __syncwarp();
#pragma unroll
    for (int i = 0; i < 4; i++) {
        const int row = i * 4 + (lane >> 3), ch = lane & 7;
        const uint4 vo = *(const uint4*)(sp + warp * 4096 + row * 128 + ((ch ^ (row & 7)) << 4));
        *(uint4*)(out + (size_t)(mt * 64 + wi * 16 + row) * DM + cb + ch * 8) = vo;
    }
    if (tid == 0) TSTAMP0(2, 4);
    if (nt == 0 && wg == 0) {
        if (t == 0) {
            g_stat[r0] = make_float2(mean[0], den[0]);
            g_stat[r0 + 8] = make_float2(mean[1], den[1]);
            s_key[wi * 16 + g] = make_key(rr[0], r0);
            s_key[wi * 16 + g + 8] = make_key(rr[1], r0 + 8);
        }
        named_sync(1, 128);
        if (warp == 0) {
            unsigned long long a = s_key[lane], b = s_key[lane + 32];
            if (b > a) { const unsigned long long c = a; a = b; b = c; }
            warp_top2(a, b);
            if (lane == 0) { g_cand[mt * 2] = a; g_cand[mt * 2 + 1] = b; }
        }
    }
}

__global__ void __launch_bounds__(256)
k4_moe(const __nv_bfloat16* __restrict__ w_gate, const __nv_bfloat16* __restrict__ w_up,
       const __nv_bfloat16* __restrict__ w_down, __nv_bfloat16* __restrict__ out) {
    __shared__ float s_gu[2][32];
    const int tid = threadIdx.x, warp = tid >> 5, lane = tid & 31;
    const int f0 = blockIdx.x * 16;
    if (tid == 0) TSTAMP0(3, 0);

    uint2 wgu[16];
    uint32_t wd[16];
    {
        const __nv_bfloat16* base = (warp < 4 ? w_gate : w_up) + (size_t)(16 * lane) * FF + f0 + (warp & 3) * 4;
#pragma unroll
        for (int k = 0; k < 16; k++) wgu[k] = __ldg((const uint2*)(base + (size_t)k * FF));
#pragma unroll
        for (int f = 0; f < 16; f++) wd[f] = __ldg((const uint32_t*)(w_down + (size_t)(f0 + f) * DM + 2 * tid));
    }
    pdl_wait();
    if (tid == 0) TSTAMP0(3, 1);

    unsigned long long ka = g_cand[2 * lane], kb = g_cand[2 * lane + 1];
    warp_top2(ka, kb);
    const int idx[2] = {key_index(ka), key_index(kb)};
    float acc[8];
    float hx[2][2], xo[2][2];
#pragma unroll
    for (int i = 0; i < 8; i++) acc[i] = 0.f;
#pragma unroll
    for (int u = 0; u < 2; u++) {
        const uint4* hp = (const uint4*)(g_h + (size_t)idx[u] * DM + 16 * lane);
        const uint4 ha = hp[0], hb = hp[1];
        const uint32_t ho = *(const uint32_t*)(g_h + (size_t)idx[u] * DM + 2 * tid);
        const float2 st = g_stat[idx[u]];
        const float inv = 1.f / st.y;
        const uint32_t hw[8] = {ha.x, ha.y, ha.z, ha.w, hb.x, hb.y, hb.z, hb.w};
#pragma unroll
        for (int k = 0; k < 8; k++) {
            const float x0 = rbf(rbf(bf_lo(hw[k]) - st.x) * inv), x1 = rbf(rbf(bf_hi(hw[k]) - st.x) * inv);
            const uint2 wa = wgu[2 * k], wb = wgu[2 * k + 1];
            acc[u * 4 + 0] = fmaf(x0, bf_lo(wa.x), fmaf(x1, bf_lo(wb.x), acc[u * 4 + 0]));
            acc[u * 4 + 1] = fmaf(x0, bf_hi(wa.x), fmaf(x1, bf_hi(wb.x), acc[u * 4 + 1]));
            acc[u * 4 + 2] = fmaf(x0, bf_lo(wa.y), fmaf(x1, bf_lo(wb.y), acc[u * 4 + 2]));
            acc[u * 4 + 3] = fmaf(x0, bf_hi(wa.y), fmaf(x1, bf_hi(wb.y), acc[u * 4 + 3]));
        }
        hx[u][0] = bf_lo(ho); hx[u][1] = bf_hi(ho);
        xo[u][0] = rbf(rbf(hx[u][0] - st.x) * inv); xo[u][1] = rbf(rbf(hx[u][1] - st.x) * inv);
    }
#define K4_STEP(O, N)                                                          \
    {                                                                          \
        const bool up = (lane & (O)) != 0;                                     \
        _Pragma("unroll") for (int i = 0; i < (N); i++) {                      \
            const float send = up ? acc[i] : acc[i + (N)];                     \
            const float keep = up ? acc[i + (N)] : acc[i];                     \
            acc[i] = keep + __shfl_xor_sync(0xffffffffu, send, (O));           \
        }                                                                      \
    }
    K4_STEP(16, 4) K4_STEP(8, 2) K4_STEP(4, 1)
    acc[0] += __shfl_xor_sync(0xffffffffu, acc[0], 2);
    acc[0] += __shfl_xor_sync(0xffffffffu, acc[0], 1);
    if ((lane & 3) == 0) {
        const int v = ((lane & 16) ? 4 : 0) + ((lane & 8) ? 2 : 0) + ((lane & 4) ? 1 : 0);
        s_gu[v >> 2][warp * 4 + (v & 3)] = acc[0];
    }
    __syncthreads();
    float y[2][2] = {{0.f, 0.f}, {0.f, 0.f}};
    {
        const int u = lane >> 4, c = lane & 15;
        const float gb = rbf(s_gu[u][c]);
        const float sg = rbf(gb / (1.f + __expf(-gb)));
        const float a = rbf(sg * rbf(s_gu[u][16 + c]));
#pragma unroll
        for (int f = 0; f < 16; f++) {
            const float a0 = __shfl_sync(0xffffffffu, a, f), a1 = __shfl_sync(0xffffffffu, a, 16 + f);
            const float w0 = bf_lo(wd[f]), w1 = bf_hi(wd[f]);
            y[0][0] = fmaf(a0, w0, y[0][0]); y[0][1] = fmaf(a0, w1, y[0][1]);
            y[1][0] = fmaf(a1, w0, y[1][0]); y[1][1] = fmaf(a1, w1, y[1][1]);
        }
    }
#pragma unroll
    for (int u = 0; u < 2; u++)
        asm volatile("red.global.add.v2.f32 [%0], {%1, %2};" ::"l"(g_y + u * DM + 2 * tid), "f"(y[u][0]), "f"(y[u][1]) : "memory");
    if (tid == 0) TSTAMP0(3, 2);
    __syncthreads();
    if (tid == 0) asm volatile("red.release.gpu.global.add.u32 [%0], 1;" ::"l"(&g_cnt) : "memory");
    if (tid == 0) TSTAMP0(3, 3);
    if (blockIdx.x == gridDim.x - 1) {
        if (tid == 0) {
            unsigned int c; int spins = 0;
            do { asm volatile("ld.acquire.gpu.global.u32 %0, [%1];" : "=r"(c) : "l"(&g_cnt) : "memory"); } while (c < gridDim.x && ++spins < (1 << 22));
        }
        __syncthreads();
        const float rv[2] = {key_value(ka), key_value(kb)};
#pragma unroll
        for (int u = 0; u < 2; u++) {
            const float2 yy = __ldcg((const float2*)(g_y + u * DM + 2 * tid));
            const float sig = rbf(1.f / (1.f + __expf(-rv[u])));
            const float o0 = hx[u][0] + rbf(xo[u][0] + rbf(rbf(yy.x) * sig));
            const float o1 = hx[u][1] + rbf(xo[u][1] + rbf(rbf(yy.y) * sig));
            *(uint32_t*)(out + (size_t)idx[u] * DM + 2 * tid) = pack_bf16(o0, o1);
        }
        if (tid == 0) g_epoch = g_epoch + 1u;
        if (tid == 0) TSTAMP0(3, 4);
    }
}

typedef CUresult (*PFN_encodeTiled)(CUtensorMap*, CUtensorMapDataType, cuuint32_t, void*, const cuuint64_t*, const cuuint64_t*,
                                    const cuuint32_t*, const cuuint32_t*, CUtensorMapInterleave, CUtensorMapSwizzle,
                                    CUtensorMapL2promotion, CUtensorMapFloatOOBfill);

void make_map(PFN_encodeTiled enc, CUtensorMap* m, const void* ptr, uint64_t cols, uint64_t rows, uint32_t bcols, uint32_t brows) {
    cuuint64_t dims[2] = {cols, rows};
    cuuint64_t strides[1] = {cols * 2};
    cuuint32_t box[2] = {bcols, brows};
    cuuint32_t es[2] = {1, 1};
    enc(m, CU_TENSOR_MAP_DATA_TYPE_BFLOAT16, 2, const_cast<void*>(ptr), dims, strides, box, es, CU_TENSOR_MAP_INTERLEAVE_NONE,
        CU_TENSOR_MAP_SWIZZLE_128B, CU_TENSOR_MAP_L2_PROMOTION_L2_256B, CU_TENSOR_MAP_FLOAT_OOB_FILL_NONE);
}

void make_map3(PFN_encodeTiled enc, CUtensorMap* m, const void* ptr, uint64_t d0, uint64_t rows, uint64_t d2, uint64_t row_stride_bytes,
               uint64_t d2_stride_bytes, uint32_t b0, uint32_t b1, uint32_t b2) {
    cuuint64_t dims[3] = {d0, rows, d2};
    cuuint64_t strides[2] = {row_stride_bytes, d2_stride_bytes};
    cuuint32_t box[3] = {b0, b1, b2};
    cuuint32_t es[3] = {1, 1, 1};
    enc(m, CU_TENSOR_MAP_DATA_TYPE_BFLOAT16, 3, const_cast<void*>(ptr), dims, strides, box, es, CU_TENSOR_MAP_INTERLEAVE_NONE,
        CU_TENSOR_MAP_SWIZZLE_128B, CU_TENSOR_MAP_L2_PROMOTION_L2_256B, CU_TENSOR_MAP_FLOAT_OOB_FILL_NONE);
}

template <typename... KArgs, typename... Args>
void launch(void (*kern)(KArgs...), int grid, int block, int smem, bool pdl, Args... args) {
    cudaLaunchConfig_t cfg = {};
    cfg.gridDim = dim3(grid);
    cfg.blockDim = dim3(block);
    cfg.dynamicSmemBytes = smem;
    cfg.stream = cudaStreamPerThread;
    cudaLaunchAttribute at[1];
    at[0].id = cudaLaunchAttributeProgrammaticStreamSerialization;
    at[0].val.programmaticStreamSerializationAllowed = 1;
    cfg.attrs = at;
    cfg.numAttrs = pdl ? 1 : 0;
    cudaLaunchKernelEx(&cfg, kern, KArgs(args)...);
}

}

extern "C" void kernel_launch(void* const* d_in, const int* in_sizes, int n_in, void* d_out, int out_size) {
    const __nv_bfloat16* x = (const __nv_bfloat16*)d_in[0];
    const __nv_bfloat16* wqkv = (const __nv_bfloat16*)d_in[1];
    const __nv_bfloat16* wo = (const __nv_bfloat16*)d_in[2];
    const __nv_bfloat16* w_r = (const __nv_bfloat16*)d_in[4];
    const __nv_bfloat16* w_gate = (const __nv_bfloat16*)d_in[5];
    const __nv_bfloat16* w_up = (const __nv_bfloat16*)d_in[6];
    const __nv_bfloat16* w_down = (const __nv_bfloat16*)d_in[7];
    __nv_bfloat16* out = (__nv_bfloat16*)d_out;

    static PFN_encodeTiled enc = nullptr;
    static void* g_o_ptr = nullptr;
    if (!enc) {
        cudaDriverEntryPointQueryResult qres;
        void* fn = nullptr;
        cudaGetDriverEntryPoint("cuTensorMapEncodeTiled", &fn, cudaEnableDefault, &qres);
        enc = (PFN_encodeTiled)fn;
        cudaGetSymbolAddress(&g_o_ptr, g_o);
        cudaFuncSetAttribute(k1_qkv, cudaFuncAttributeMaxDynamicSharedMemorySize, K1_SMEM);
        cudaFuncSetAttribute(k2_attn, cudaFuncAttributeMaxDynamicSharedMemorySize, K2_SMEM);
        cudaFuncSetAttribute(k3_proj, cudaFuncAttributeMaxDynamicSharedMemorySize, K3_SMEM);
    }
    CUtensorMap tm_x, tm_w, tm_o, tm_wo;
    make_map(enc, &tm_x, x, DM, SEQ, 64, 128);
    make_map3(enc, &tm_w, wqkv, DM, DM, 3, 3 * DM * 2, DM * 2, 64, 64, 3);
    make_map3(enc, &tm_o, g_o_ptr, 64, SEQ, 8, DM * 2, 128, 64, 64, 2);
    make_map3(enc, &tm_wo, wo, 64, DM, 8, DM * 2, 128, 64, 64, 2);

    const bool pdl = true;
    launch(k1_qkv, 128, 544, K1_SMEM, false, tm_x, tm_w, x);
    launch(k2_attn, 128, 512, K2_SMEM, pdl, (const uint8_t*)wo, (const uint8_t*)w_gate, (const uint8_t*)w_up, (const uint8_t*)w_down);
    launch(k3_proj, 128, 288, K3_SMEM, pdl, tm_o, tm_wo, x, w_r, out);
    launch(k4_moe, 112, 256, 0, pdl, w_gate, w_up, w_down, out);
}
```

```cpp
#include <cuda_runtime.h>
#include <cuda_bf16.h>
#include <cuda.h>
#include <stdint.h>

namespace {

constexpr int SEQ = 2048, DM = 512, NH = 32, FF = 1792;

__device__ __align__(1024) uint8_t g_q[NH * 2 * SEQ * 16];
__device__ __align__(1024) uint8_t g_kv[NH * 8 * 16384];
__device__ float g_norm[16 * NH * 3];
__device__ __align__(1024) __nv_bfloat16 g_o[SEQ * DM];
__device__ __align__(1024) __nv_bfloat16 g_h[SEQ * DM];
__device__ __align__(16) uint4 g_cand[64];
__device__ unsigned int g_oflag[32];
__device__ unsigned int g_hflag[32];
__device__ __align__(16) float g_y[2 * DM];
__device__ unsigned int g_cnt;
__device__ unsigned int g_epoch;
__device__ __align__(16) float4 g_ln1[SEQ];
__device__ __align__(16) float4 g_part[32 * 8 * 64];

#define TSTAMP(K, I)
#define TSTAMP0(K, I)
__device__ __forceinline__ uint32_t smem_u32(const void* p) { return (uint32_t)__cvta_generic_to_shared(p); }
__device__ __forceinline__ void wg_fence() { asm volatile("wgmma.fence.sync.aligned;" ::: "memory"); }
__device__ __forceinline__ void wg_commit() { asm volatile("wgmma.commit_group.sync.aligned;" ::: "memory"); }
template <int N> __device__ __forceinline__ void wg_wait() { asm volatile("wgmma.wait_group.sync.aligned %0;" ::"n"(N) : "memory"); }
template <int N> __device__ __forceinline__ void fence_regs(float (&r)[N]) {
#pragma unroll
    for (int i = 0; i < N; i++) asm volatile("" : "+f"(r[i])::"memory");
}
__device__ __forceinline__ uint64_t make_desc(uint32_t addr, uint32_t lbo, uint32_t sbo, uint32_t swz) {
    uint64_t d = 0;
    d |= (uint64_t)((addr & 0x3FFFF) >> 4);
    d |= (uint64_t)((lbo & 0x3FFFF) >> 4) << 16;
    d |= (uint64_t)((sbo & 0x3FFFF) >> 4) << 32;
    d |= (uint64_t)swz << 62;
    return d;
}
__device__ __forceinline__ void mbar_init(uint32_t bar, uint32_t cnt) {
    asm volatile("mbarrier.init.shared::cta.b64 [%0], %1;" ::"r"(bar), "r"(cnt) : "memory");
}
__device__ __forceinline__ void mbar_expect_tx(uint32_t bar, uint32_t bytes) {
    asm volatile("mbarrier.arrive.expect_tx.shared::cta.b64 _, [%0], %1;" ::"r"(bar), "r"(bytes) : "memory");
}
__device__ __forceinline__ void mbar_arrive(uint32_t bar) {
    asm volatile("mbarrier.arrive.shared::cta.b64 _, [%0];" ::"r"(bar) : "memory");
}
__device__ __forceinline__ void mbar_wait(uint32_t bar, uint32_t parity) {
    asm volatile(
        "{\n.reg .pred p;\nWAIT_%=:\n"
        "mbarrier.try_wait.parity.shared::cta.b64 p, [%0], %1;\n"
        "@p bra DONE_%=;\nbra WAIT_%=;\nDONE_%=:\n}\n" ::"r"(bar), "r"(parity) : "memory");
}
__device__ __forceinline__ void bulk_g2s(uint32_t dst, const void* src, uint32_t bytes, uint32_t bar) {
    asm volatile("cp.async.bulk.shared::cluster.global.mbarrier::complete_tx::bytes [%0], [%1], %2, [%3];" ::"r"(dst),
                 "l"(src), "r"(bytes), "r"(bar) : "memory");
}
__device__ __forceinline__ void bulk_s2g(void* dst, uint32_t src, uint32_t bytes) {
    asm volatile("cp.async.bulk.global.shared::cta.bulk_group [%0], [%1], %2;" ::"l"(dst), "r"(src), "r"(bytes) : "memory");
}
__device__ __forceinline__ void tma_load_2d(uint32_t dst, const CUtensorMap* tm, int c0, int c1, uint32_t bar) {
    asm volatile("cp.async.bulk.tensor.2d.shared::cluster.global.mbarrier::complete_tx::bytes [%0], [%1, {%3, %4}], [%2];" ::"r"(dst),
                 "l"(tm), "r"(bar), "r"(c0), "r"(c1) : "memory");
}
__device__ __forceinline__ void tma_load_3d(uint32_t dst, const CUtensorMap* tm, int c0, int c1, int c2, uint32_t bar) {
    asm volatile("cp.async.bulk.tensor.3d.shared::cluster.global.mbarrier::complete_tx::bytes [%0], [%1, {%3, %4, %5}], [%2];" ::"r"(dst),
                 "l"(tm), "r"(bar), "r"(c0), "r"(c1), "r"(c2) : "memory");
}
__device__ __forceinline__ void tma_load_2d_mc(uint32_t dst, const CUtensorMap* tm, int c0, int c1, uint32_t bar, uint16_t mask) {
    asm volatile("cp.async.bulk.tensor.2d.shared::cluster.global.mbarrier::complete_tx::bytes.multicast::cluster [%0], [%1, {%3, %4}], [%2], %5;" ::"r"(dst),
                 "l"(tm), "r"(bar), "r"(c0), "r"(c1), "h"(mask) : "memory");
}
__device__ __forceinline__ void mbar_arrive_cluster(uint32_t bar, uint32_t cta) {
    asm volatile("{\n.reg .b32 ra;\nmapa.shared::cluster.u32 ra, %0, %1;\nmbarrier.arrive.release.cluster.shared::cluster.b64 _, [ra];\n}" ::"r"(bar), "r"(cta) : "memory");
}
__device__ __forceinline__ void cluster_sync() {
    asm volatile("barrier.cluster.arrive.release.aligned;\nbarrier.cluster.wait.acquire.aligned;" ::: "memory");
}
__device__ __forceinline__ void prefetch_l2(const void* p, uint32_t bytes) {
    asm volatile("cp.async.bulk.prefetch.L2.global [%0], %1;" ::"l"(p), "r"(bytes) : "memory");
}
__device__ __forceinline__ void fence_proxy_async() { asm volatile("fence.proxy.async.shared::cta;" ::: "memory"); }
__device__ __forceinline__ void fence_barrier_init() { asm volatile("fence.mbarrier_init.release.cluster;" ::: "memory"); }
__device__ __forceinline__ void pdl_launch() { asm volatile("griddepcontrol.launch_dependents;" ::: "memory"); }
__device__ __forceinline__ void pdl_wait() { asm volatile("griddepcontrol.wait;" ::: "memory"); }
__device__ __forceinline__ void named_sync(int id, int n) { asm volatile("bar.sync %0, %1;" ::"r"(id), "r"(n) : "memory"); }
__device__ __forceinline__ void named_arrive(int id, int n) { asm volatile("bar.arrive %0, %1;" ::"r"(id), "r"(n) : "memory"); }

__device__ __forceinline__ float ex2f(float x) { float y; asm("ex2.approx.ftz.f32 %0, %1;" : "=f"(y) : "f"(x)); return y; }
__device__ __forceinline__ uint32_t pack_bf16(float lo, float hi) {
    uint32_t r; asm("cvt.rn.bf16x2.f32 %0, %1, %2;" : "=r"(r) : "f"(hi), "f"(lo)); return r;
}
__device__ __forceinline__ float bf_lo(uint32_t v) { return __uint_as_float(v << 16); }
__device__ __forceinline__ float bf_hi(uint32_t v) { return __uint_as_float(v & 0xFFFF0000u); }
__device__ __forceinline__ float rbf(float x) { return __bfloat162float(__float2bfloat16_rn(x)); }
__device__ __forceinline__ uint32_t fma_bf16x2(uint32_t a, uint32_t b, uint32_t c) {
    uint32_t r; asm("fma.rn.bf16x2 %0, %1, %2, %3;" : "=r"(r) : "r"(a), "r"(b), "r"(c)); return r;
}
__device__ __forceinline__ void stmatrix_x4(uint32_t addr, uint32_t r0, uint32_t r1, uint32_t r2, uint32_t r3) {
    asm volatile("stmatrix.sync.aligned.m8n8.x4.shared.b16 [%0], {%1, %2, %3, %4};" ::"r"(addr), "r"(r0), "r"(r1), "r"(r2), "r"(r3) : "memory");
}
__device__ __forceinline__ void stmatrix_x4_trans(uint32_t addr, uint32_t r0, uint32_t r1, uint32_t r2, uint32_t r3) {
    asm volatile("stmatrix.sync.aligned.m8n8.x4.trans.shared.b16 [%0], {%1, %2, %3, %4};" ::"r"(addr), "r"(r0), "r"(r1), "r"(r2), "r"(r3) : "memory");
}

__device__ __forceinline__ void wgmma_k1_n136(float (&d)[68], uint64_t desca, uint64_t descb, int scale_d) {
  asm volatile("{\n.reg .pred p;\nsetp.ne.b32 p, %70, 0;\n"
    "wgmma.mma_async.sync.aligned.m64n136k16.f32.bf16.bf16 "
    "{%0, %1, %2, %3, %4, %5, %6, %7, %8, %9, %10, %11, %12, %13, %14, %15, %16, %17, %18, %19, %20, %21, %22, %23, %24, %25, %26, %27, %28, %29, %30, %31, %32, %33, %34, %35, %36, %37, %38, %39, %40, %41, %42, %43, %44, %45, %46, %47, %48, %49, %50, %51, %52, %53, %54, %55, %56, %57, %58, %59, %60, %61, %62, %63, %64, %65, %66, %67}, "
    "%68, %69, p, 1, 1, 1, 0;\n}\n"
    : "+f"(d[0]), "+f"(d[1]), "+f"(d[2]), "+f"(d[3]), "+f"(d[4]), "+f"(d[5]), "+f"(d[6]), "+f"(d[7]), "+f"(d[8]), "+f"(d[9]), "+f"(d[10]), "+f"(d[11]), "+f"(d[12]), "+f"(d[13]), "+f"(d[14]), "+f"(d[15]), "+f"(d[16]), "+f"(d[17]), "+f"(d[18]), "+f"(d[19]), "+f"(d[20]), "+f"(d[21]), "+f"(d[22]), "+f"(d[23]), "+f"(d[24]), "+f"(d[25]), "+f"(d[26]), "+f"(d[27]), "+f"(d[28]), "+f"(d[29]), "+f"(d[30]), "+f"(d[31]), "+f"(d[32]), "+f"(d[33]), "+f"(d[34]), "+f"(d[35]), "+f"(d[36]), "+f"(d[37]), "+f"(d[38]), "+f"(d[39]), "+f"(d[40]), "+f"(d[41]), "+f"(d[42]), "+f"(d[43]), "+f"(d[44]), "+f"(d[45]), "+f"(d[46]), "+f"(d[47]), "+f"(d[48]), "+f"(d[49]), "+f"(d[50]), "+f"(d[51]), "+f"(d[52]), "+f"(d[53]), "+f"(d[54]), "+f"(d[55]), "+f"(d[56]), "+f"(d[57]), "+f"(d[58]), "+f"(d[59]), "+f"(d[60]), "+f"(d[61]), "+f"(d[62]), "+f"(d[63]), "+f"(d[64]), "+f"(d[65]), "+f"(d[66]), "+f"(d[67])
    : "l"(desca), "l"(descb), "r"(scale_d));
}
__device__ __forceinline__ void wgmma_qk_n64(float (&d)[32], uint32_t a0, uint32_t a1, uint32_t a2, uint32_t a3, uint64_t descb) {
  asm volatile("{\n.reg .pred p;\nsetp.ne.b32 p, 0, 0;\n"
    "wgmma.mma_async.sync.aligned.m64n64k16.f32.bf16.bf16 "
    "{%0, %1, %2, %3, %4, %5, %6, %7, %8, %9, %10, %11, %12, %13, %14, %15, %16, %17, %18, %19, %20, %21, %22, %23, %24, %25, %26, %27, %28, %29, %30, %31}, "
    "{%32, %33, %34, %35}, %36, p, 1, 1, 0;\n}\n"
    : "=f"(d[0]), "=f"(d[1]), "=f"(d[2]), "=f"(d[3]), "=f"(d[4]), "=f"(d[5]), "=f"(d[6]), "=f"(d[7]), "=f"(d[8]), "=f"(d[9]), "=f"(d[10]), "=f"(d[11]), "=f"(d[12]), "=f"(d[13]), "=f"(d[14]), "=f"(d[15]), "=f"(d[16]), "=f"(d[17]), "=f"(d[18]), "=f"(d[19]), "=f"(d[20]), "=f"(d[21]), "=f"(d[22]), "=f"(d[23]), "=f"(d[24]), "=f"(d[25]), "=f"(d[26]), "=f"(d[27]), "=f"(d[28]), "=f"(d[29]), "=f"(d[30]), "=f"(d[31])
    : "r"(a0), "r"(a1), "r"(a2), "r"(a3), "l"(descb));
}
__device__ __forceinline__ void wgmma_pv_n24(float (&d)[12], uint32_t a0, uint32_t a1, uint32_t a2, uint32_t a3, uint64_t descb) {
  asm volatile("{\n.reg .pred p;\nsetp.eq.b32 p, 0, 0;\n"
    "wgmma.mma_async.sync.aligned.m64n24k16.f32.bf16.bf16 "
    "{%0, %1, %2, %3, %4, %5, %6, %7, %8, %9, %10, %11}, "
    "{%12, %13, %14, %15}, %16, p, 1, 1, 1;\n}\n"
    : "+f"(d[0]), "+f"(d[1]), "+f"(d[2]), "+f"(d[3]), "+f"(d[4]), "+f"(d[5]), "+f"(d[6]), "+f"(d[7]), "+f"(d[8]), "+f"(d[9]), "+f"(d[10]), "+f"(d[11])
    : "r"(a0), "r"(a1), "r"(a2), "r"(a3), "l"(descb));
}
__device__ __forceinline__ void wgmma_k3_n64(float (&d)[32], uint64_t desca, uint64_t descb, int scale_d) {
  asm volatile("{\n.reg .pred p;\nsetp.ne.b32 p, %34, 0;\n"
    "wgmma.mma_async.sync.aligned.m64n64k16.f32.bf16.bf16 "
    "{%0, %1, %2, %3, %4, %5, %6, %7, %8, %9, %10, %11, %12, %13, %14, %15, %16, %17, %18, %19, %20, %21, %22, %23, %24, %25, %26, %27, %28, %29, %30, %31}, "
    "%32, %33, p, 1, 1, 0, 1;\n}\n"
    : "+f"(d[0]), "+f"(d[1]), "+f"(d[2]), "+f"(d[3]), "+f"(d[4]), "+f"(d[5]), "+f"(d[6]), "+f"(d[7]), "+f"(d[8]), "+f"(d[9]), "+f"(d[10]), "+f"(d[11]), "+f"(d[12]), "+f"(d[13]), "+f"(d[14]), "+f"(d[15]), "+f"(d[16]), "+f"(d[17]), "+f"(d[18]), "+f"(d[19]), "+f"(d[20]), "+f"(d[21]), "+f"(d[22]), "+f"(d[23]), "+f"(d[24]), "+f"(d[25]), "+f"(d[26]), "+f"(d[27]), "+f"(d[28]), "+f"(d[29]), "+f"(d[30]), "+f"(d[31])
    : "l"(desca), "l"(descb), "r"(scale_d));
}

constexpr int K1_XS = 17408;
constexpr int K1_WS = 24576;
constexpr int K1_ST = K1_XS + K1_WS;
constexpr int K1_NST = 5;
constexpr int K1_OFF_MISC = K1_NST * K1_ST;
constexpr int K1_SMEM = K1_OFF_MISC + 2048 + 1024;
constexpr float QSCALE = 0.25f * 1.4426950408889634f;

__global__ void __launch_bounds__(544, 1)
k1_qkv(const __grid_constant__ CUtensorMap tm_x, const __grid_constant__ CUtensorMap tm_w, const __nv_bfloat16* __restrict__ x) {
    extern __shared__ uint8_t smem_raw[];
    const uint32_t sraw = smem_u32(smem_raw);
    const uint32_t sb = (sraw + 1023) & ~1023u;
    uint8_t* sp = smem_raw + (sb - sraw);
    const uint32_t full = sb + K1_OFF_MISC;
    const uint32_t empty = full + 64;
    float* s_m = (float*)(sp + K1_OFF_MISC + 256);
    float* s_r = s_m + 128;

    const int tid = threadIdx.x, warp = tid >> 5, lane = tid & 31;
    const int mt = blockIdx.x >> 3, nt = blockIdx.x & 7;
    if (tid == 0) TSTAMP0(0, 0);
    pdl_launch();
    if (tid == 0) {
        for (int i = 0; i < K1_NST; i++) { mbar_init(full + 8 * i, 1); mbar_init(empty + 8 * i, 3); }
        fence_barrier_init();
    }
    if (tid < K1_NST * 64) {
        *(uint4*)(sp + (tid >> 6) * K1_ST + 16384 + (tid & 63) * 16) =
            make_uint4(0x3F803F80u, 0x3F803F80u, 0x3F803F80u, 0x3F803F80u);
    }
    fence_proxy_async();
    __syncthreads();

    if (warp == 16) {
        if (lane == 0) {
            for (int kb = 0; kb < 8; kb++) {
                const int s = kb % K1_NST;
                if (kb >= K1_NST) mbar_wait(empty + 8 * s, 0);
                mbar_expect_tx(full + 8 * s, 16384 + K1_WS);
                tma_load_2d(sb + s * K1_ST, &tm_x, kb * 64, mt * 128, full + 8 * s);
                tma_load_3d(sb + s * K1_ST + K1_XS, &tm_w, nt * 64, kb * 64, 0, full + 8 * s);
            }
        } else if (lane == 1) {
            if (blockIdx.x == 0) g_cnt = 0;
        }
        if (blockIdx.x == 0) for (int i = lane; i < 2 * DM; i += 32) g_y[i] = 0.f;
        for (int i = lane; i < 128; i += 32) g_part[blockIdx.x * 128 + i] = make_float4(0.f, 0.f, 0.f, 0.f);
        if (blockIdx.x == 1) { g_cand[lane] = make_uint4(0, 0, 0, 0); g_cand[lane + 32] = make_uint4(0, 0, 0, 0); g_oflag[lane] = 0; g_hflag[lane] = 0; }
    } else if (warp >= 12) {
        const int r = tid - 384;
        const unsigned int tag = *(volatile unsigned int*)&g_epoch + 1u;
        {
            const int row = mt * 128 + nt * 16 + (r >> 3);
            const uint4* xp = (const uint4*)(x + (size_t)row * DM) + (r & 7);
            uint4 v[8];
#pragma unroll
            for (int i = 0; i < 8; i++) v[i] = __ldg(xp + i * 8);
            float s1 = 0.f;
#pragma unroll
            for (int i = 0; i < 8; i++)
                s1 += ((bf_lo(v[i].x) + bf_hi(v[i].x)) + (bf_lo(v[i].y) + bf_hi(v[i].y))) + ((bf_lo(v[i].z) + bf_hi(v[i].z)) + (bf_lo(v[i].w) + bf_hi(v[i].w)));
#pragma unroll
            for (int o = 1; o < 8; o <<= 1) s1 += __shfl_xor_sync(0xffffffffu, s1, o);
            const float mean = s1 * (1.f / DM);
            float q0 = 0.f, q1 = 0.f;
#pragma unroll
            for (int i = 0; i < 8; i++) {
                const uint32_t w[4] = {v[i].x, v[i].y, v[i].z, v[i].w};
#pragma unroll
                for (int j = 0; j < 4; j++) {
                    const float a = bf_lo(w[j]) - mean, b = bf_hi(w[j]) - mean;
                    q0 = fmaf(a, a, q0); q1 = fmaf(b, b, q1);
                }
            }
            float q = q0 + q1;
#pragma unroll
            for (int o = 1; o < 8; o <<= 1) q += __shfl_xor_sync(0xffffffffu, q, o);
            const float den = rbf(sqrtf(rbf(rbf(q * (1.f / DM)) + 1e-5f)));
            if ((r & 7) == 0)
                asm volatile("st.relaxed.gpu.global.v4.f32 [%0], {%1, %2, %3, %4};" ::"l"(g_ln1 + row), "f"(rbf(mean)), "f"(1.f / den),
                             "f"(__uint_as_float(tag)), "f"(0.f) : "memory");
        }
        if (r == 0) TSTAMP0(0, 6);
        {
            float4 v;
            int spins = 0;
            do {
                asm volatile("ld.relaxed.gpu.global.v4.f32 {%0, %1, %2, %3}, [%4];" : "=f"(v.x), "=f"(v.y), "=f"(v.z), "=f"(v.w) : "l"(g_ln1 + mt * 128 + r) : "memory");
            } while (__float_as_uint(v.z) != tag && ++spins < (1 << 22));
            s_m[r] = v.x;
            s_r[r] = v.y;
        }
        if (r == 0) TSTAMP0(0, 7);
        named_arrive(1, 512);
    } else {
        const int part = warp >> 2, hw = warp & 3;
        float acc[68];
#pragma unroll
        for (int i = 0; i < 68; i++) acc[i] = 0.f;
        fence_regs(acc);
#pragma unroll 1
        for (int kb = 0; kb < 8; kb++) {
            const int s = kb % K1_NST;
            mbar_wait(full + 8 * s, (kb / K1_NST) & 1);
            const uint64_t da = make_desc(sb + s * K1_ST + K1_XS + part * 8192, 1024, 1024, 1);
            const uint64_t db = make_desc(sb + s * K1_ST, 16, 1024, 1);
            wg_fence();
#pragma unroll
            for (int k = 0; k < 4; k++) wgmma_k1_n136(acc, da + k * 128, db + k * 2, (kb | k) != 0);
            wg_commit();
            if (kb > 0 && kb <= 8 - K1_NST) {
                wg_wait<1>();
                if ((tid & 127) == 0) mbar_arrive(empty + 8 * (kb - 1));
            }
        }
        wg_wait<0>();
        fence_regs(acc);
        if (tid == 0) TSTAMP0(0, 1);
        named_sync(1, 512);
        if (tid == 0) TSTAMP0(0, 2);

        const int t = lane & 3;
        const float cs0 = acc[64], cs1 = acc[66];
        const float sc = (part == 0) ? QSCALE : 1.f;
        const uint32_t stg = sb + (hw >> 1) * K1_ST + K1_XS + part * 8192 + (hw & 1) * 4096;
        const uint32_t st_addr = stg + ((lane >> 3) & 1) * 2048 + ((lane >> 4) * 8 + (lane & 7)) * 16;
#pragma unroll
        for (int j = 0; j < 16; j += 2) {
            uint32_t rr[4];
#pragma unroll
            for (int u = 0; u < 2; u++) {
                const int jj = j + u;
                const float2 m2 = *(const float2*)(s_m + 8 * jj + 2 * t);
                const float2 r2 = *(const float2*)(s_r + 8 * jj + 2 * t);
                const float ra = r2.x * sc, rb = r2.y * sc;
                rr[2 * u] = pack_bf16((acc[4 * jj] - m2.x * cs0) * ra, (acc[4 * jj + 1] - m2.y * cs0) * rb);
                rr[2 * u + 1] = pack_bf16((acc[4 * jj + 2] - m2.x * cs1) * ra, (acc[4 * jj + 3] - m2.y * cs1) * rb);
            }
            stmatrix_x4_trans(st_addr + j * 128, rr[0], rr[1], rr[2], rr[3]);
        }
        __syncwarp();
        if (tid == 0) TSTAMP0(0, 4);
        float nmax = 0.f;
#pragma unroll
        for (int i = 0; i < 4; i++) {
            const int tok = lane + 32 * i;
            const uint4 a = *(const uint4*)(sp + (stg - sb) + tok * 16);
            const uint4 b = *(const uint4*)(sp + (stg - sb) + 2048 + tok * 16);
            const uint32_t w[8] = {a.x, a.y, a.z, a.w, b.x, b.y, b.z, b.w};
            float n2 = 0.f;
#pragma unroll
            for (int q = 0; q < 8; q++) {
                const float lo = bf_lo(w[q]), hi = bf_hi(w[q]);
                n2 = fmaf(lo, lo, n2); n2 = fmaf(hi, hi, n2);
            }
            nmax = (n2 > nmax || n2 != n2) ? n2 : nmax;
        }
#pragma unroll
        for (int o = 16; o > 0; o >>= 1) {
            const float v = __shfl_xor_sync(0xffffffffu, nmax, o);
            nmax = (v > nmax || v != v) ? v : nmax;
        }
        if (tid == 0) TSTAMP0(0, 5);
        fence_proxy_async();
        __syncwarp();
        if (lane == 0) {
            const int head = nt * 4 + hw;
            g_norm[(mt * NH + head) * 3 + part] = nmax;
            uint8_t* dst;
            uint32_t hstride;
            if (part == 0) { dst = g_q + (size_t)head * 65536 + mt * 2048; hstride = 32768; }
            else { dst = g_kv + (size_t)head * 131072 + (mt >> 1) * 16384 + (part - 1) * 8192 + (mt & 1) * 2048; hstride = 4096; }
            bulk_s2g(dst, stg, 2048);
            bulk_s2g(dst + hstride, stg + 2048, 2048);
            asm volatile("cp.async.bulk.commit_group;" ::: "memory");
            asm volatile("cp.async.bulk.wait_group.read 0;" ::: "memory");
            if (tid == 0) TSTAMP0(0, 3);
        }
    }
}

constexpr int KF_CH_G = 16384, KF_CH_S = 20480, KF_NCH = 8;
constexpr int KF_OFF_WO = KF_NCH * KF_CH_S;
constexpr int KF_OFF_MISC = KF_OFF_WO + 65536;
constexpr int KF_SMEM = KF_OFF_MISC + 1280 + 1024;

__device__ __forceinline__ uint32_t exp2_pair_poly(float s0, float s1) {
    const float KB = 65536.0f + 127.0f;
    const float t0 = s0 + KB, t1 = s1 + KB;
    const uint32_t w = __byte_perm(__float_as_uint(t0), __float_as_uint(t1), 0x5410);
    uint32_t z;
    asm("lop3.b32 %0, %1, %2, %3, 0xEA;" : "=r"(z) : "r"(w), "r"(0x007F007Fu), "r"(0x3F803F80u));
    uint32_t p = fma_bf16x2(0x3eab3eabu, z, 0xbc73bc73u);
    p = fma_bf16x2(p, z, 0x3f2f3f2fu);
    return p + w - z;
}
constexpr uint32_t KF_EMASK = 0x5757u;
template <int LO, int HI>
__device__ __forceinline__ void softmax_part(const float (&s)[32], uint32_t (&p)[16]) {
#pragma unroll
    for (int i = LO; i < HI; i++) {
        if ((KF_EMASK >> i) & 1) p[i] = exp2_pair_poly(s[2 * i], s[2 * i + 1]);
        else p[i] = pack_bf16(ex2f(s[2 * i]), ex2f(s[2 * i + 1]));
    }
}
#define KF_PV(P, OFF)                                                                              \
    _Pragma("unroll") for (int kk = 0; kk < 4; kk++)                                               \
        wgmma_pv_n24(o, P[4 * kk], P[4 * kk + 1], P[4 * kk + 2], P[4 * kk + 3], dv + ((OFF) + kk * 16));

__device__ __forceinline__ unsigned long long cand_key(const uint4& c) {
    return ((unsigned long long)c.x << 32) | (uint32_t)(0x7FFFFFFF - (int)c.y);
}
__device__ __forceinline__ uint32_t order_bits(float v) {
    const uint32_t u = __float_as_uint(v);
    return (u & 0x80000000u) ? ~u : (u | 0x80000000u);
}
__device__ __forceinline__ float order_value(uint32_t u) {
    return __uint_as_float((u & 0x80000000u) ? (u & 0x7FFFFFFFu) : ~u);
}
__device__ __forceinline__ void warp_top2(unsigned long long& a, unsigned long long& b) {
#pragma unroll
    for (int o = 16; o > 0; o >>= 1) {
        const unsigned long long c = __shfl_xor_sync(0xffffffffu, a, o);
        const unsigned long long d = __shfl_xor_sync(0xffffffffu, b, o);
        const unsigned long long hi = a > c ? a : c, lo = a > c ? c : a;
        const unsigned long long m = b > d ? b : d;
        a = hi;
        b = lo > m ? lo : m;
    }
}
__device__ __forceinline__ unsigned int ld_acquire(const unsigned int* p) {
    unsigned int v; asm volatile("ld.acquire.gpu.global.u32 %0, [%1];" : "=r"(v) : "l"(p) : "memory"); return v;
}
__device__ __forceinline__ void red_release_add(unsigned int* p) {
    asm volatile("red.release.gpu.global.add.u32 [%0], 1;" ::"l"(p) : "memory");
}

__global__ void __launch_bounds__(512, 1)
kf_main(const __grid_constant__ CUtensorMap tm_o, const __grid_constant__ CUtensorMap tm_wo,
        const __nv_bfloat16* __restrict__ x, const __nv_bfloat16* __restrict__ wo, const __nv_bfloat16* __restrict__ w_r,
        const __nv_bfloat16* __restrict__ w_gate, const __nv_bfloat16* __restrict__ w_up, const __nv_bfloat16* __restrict__ w_down,
        __nv_bfloat16* __restrict__ out) {
    extern __shared__ uint8_t smem_raw[];
    const uint32_t sraw = smem_u32(smem_raw);
    const uint32_t sb = (sraw + 1023) & ~1023u;
    uint8_t* sp = smem_raw + (sb - sraw);
    const uint32_t kvbar = sb + KF_OFF_MISC;
    const uint32_t wbar = kvbar + 64;
    const uint32_t obar = wbar + 64;
    unsigned int* s_cnt = (unsigned int*)(sp + KF_OFF_MISC + 192);
    unsigned long long* s_key = (unsigned long long*)(sp + KF_OFF_MISC + 256);
    float* s_gu = (float*)(sp + KF_OFF_MISC + 768);
    const int tid = threadIdx.x;
    const int head = blockIdx.x >> 2, quarter = blockIdx.x & 3;
    const int mt = blockIdx.x >> 2, nt = blockIdx.x & 3;
    if (tid == 0) TSTAMP0(1, 0);
    if (tid == 0) {
        for (int c = 0; c < 20; c++) mbar_init(kvbar + 8 * c, 1);
        for (int c = 0; c < 4; c++) s_cnt[c] = 0;
        fence_barrier_init();
        for (int kb = 0; kb < 4; kb++) {
            mbar_expect_tx(wbar + 8 * kb, 16384);
            tma_load_3d(sb + KF_OFF_WO + kb * 16384, &tm_wo, 0, kb * 64, nt * 2, wbar + 8 * kb);
        }
    }
    if (tid == 32) {
        prefetch_l2((const uint8_t*)wo + blockIdx.x * 4096, 4096);
        prefetch_l2((const uint8_t*)w_gate + blockIdx.x * 14336, 14336);
        prefetch_l2((const uint8_t*)w_up + blockIdx.x * 14336, 14336);
        prefetch_l2((const uint8_t*)w_down + blockIdx.x * 14336, 14336);
    }
    for (int i = tid; i < KF_NCH * 256; i += 512)
        *(uint4*)(sp + (i >> 8) * KF_CH_S + 16384 + (i & 255) * 16) =
            make_uint4(0x3F803F80u, 0x3F803F80u, 0x3F803F80u, 0x3F803F80u);
    fence_proxy_async();
    __syncthreads();
    pdl_wait();
    if (tid == 0) TSTAMP0(1, 1);
    if (tid == 0) {
        const uint8_t* src = g_kv + (size_t)head * (KF_NCH * KF_CH_G);
        for (int c = 0; c < KF_NCH; c++) {
            mbar_expect_tx(kvbar + 8 * c, KF_CH_G);
            bulk_g2s(sb + c * KF_CH_S, src + c * KF_CH_G, KF_CH_G, kvbar + 8 * c);
        }
    }
    const int wg = tid >> 7, warp = (tid >> 5) & 3, lane = tid & 31, g = lane >> 2, t = lane & 3;

    bool fast;
    {
        const int m16 = lane & 15;
        float kn = g_norm[(m16 * NH + head) * 3 + 1];
        float vn = g_norm[(m16 * NH + head) * 3 + 2];
        float qn = g_norm[((quarter * 4 + (lane & 3)) * NH + head) * 3 + 0];
        bool bad = !(kn < 1e30f) || !(vn < 1e30f) || !(qn < 1e30f);
#pragma unroll
        for (int o = 8; o > 0; o >>= 1) {
            kn = fmaxf(kn, __shfl_xor_sync(0xffffffffu, kn, o));
            qn = fmaxf(qn, __shfl_xor_sync(0xffffffffu, qn, o));
        }
        bad = __any_sync(0xffffffffu, bad);
        fast = !bad && (qn * kn <= 3500.f);
    }
    const uint64_t dk0 = make_desc(sb, 4096, 128, 0);
    const uint64_t dv0 = make_desc(sb + 8192, 128, 4096, 0);

#pragma unroll 1
    for (int pass = 0; pass < 2; pass++) {
        const int row0 = quarter * 512 + pass * 256 + wg * 64 + warp * 16 + g;
        uint32_t qa[4];
        {
            const uint8_t* qb = g_q + (size_t)head * 65536 + row0 * 16 + t * 4;
            qa[0] = *(const uint32_t*)(qb);
            qa[1] = *(const uint32_t*)(qb + 128);
            qa[2] = *(const uint32_t*)(qb + 32768);
            qa[3] = *(const uint32_t*)(qb + 32768 + 128);
        }
        float o[12];
#pragma unroll
        for (int i = 0; i < 12; i++) o[i] = 0.f;
        fence_regs(o);
#define KF_RELEASE_CHUNK(c)                                                                          \
        if (pass == 1 && (c) >= 1 && (c) <= 4) {                                                     \
            named_sync(4 + wg, 128);            \
            if ((tid & 127) == 0 && atomicAdd(&s_cnt[(c) - 1], 1u) == 3u) {                          \
                mbar_expect_tx(wbar + 8 * (3 + (c)), 16384);                                         \
                tma_load_3d(sb + ((c) - 1) * KF_CH_S, &tm_wo, 0, (3 + (c)) * 64, nt * 2, wbar + 8 * (3 + (c))); \
            }                                                                                        \
        }
        if (fast) {
#pragma unroll 1
            for (int c = 0; c < KF_NCH; c++) {
                const uint64_t dk = dk0 + (uint64_t)(c * (KF_CH_S >> 4));
                const uint64_t dv = dv0 + (uint64_t)(c * (KF_CH_S >> 4));
                float s0[32], s1[32], s2[32], s3[32];
                uint32_t p0[16], p1[16], p2[16], p3[16];
                mbar_wait(kvbar + 8 * c, 0);
                wg_wait<1>();
                wg_fence();
                wgmma_qk_n64(s0, qa[0], qa[1], qa[2], qa[3], dk);
                wg_commit();
                wg_wait<1>();
                KF_RELEASE_CHUNK(c);
                wg_fence();
                wgmma_qk_n64(s1, qa[0], qa[1], qa[2], qa[3], dk + 64);
                wg_commit();
                wg_wait<1>();
                fence_regs(s0);
                softmax_part<0, 16>(s0, p0);
                wg_fence();
                KF_PV(p0, 0);
                wg_commit();
                wg_wait<1>();
                fence_regs(s1);
                softmax_part<0, 8>(s1, p1);
                wg_wait<0>();
                wg_fence();
                wgmma_qk_n64(s2, qa[0], qa[1], qa[2], qa[3], dk + 128);
                wg_commit();
                softmax_part<8, 16>(s1, p1);
                wg_fence();
                KF_PV(p1, 64);
                wg_commit();
                wg_wait<1>();
                fence_regs(s2);
                softmax_part<0, 8>(s2, p2);
                wg_wait<0>();
                wg_fence();
                wgmma_qk_n64(s3, qa[0], qa[1], qa[2], qa[3], dk + 192);
                wg_commit();
                softmax_part<8, 16>(s2, p2);
                wg_fence();
                KF_PV(p2, 128);
                wg_commit();
                wg_wait<1>();
                fence_regs(s3);
                softmax_part<0, 16>(s3, p3);
                wg_fence();
                KF_PV(p3, 192);
                wg_commit();
            }
            wg_wait<0>();
            fence_regs(o);
        } else {
            float m0 = -INFINITY, m1 = -INFINITY;
#pragma unroll 1
            for (int b = 0; b < 32; b++) {
                const int c = b >> 2;
                const uint64_t dk = dk0 + (uint64_t)(c * (KF_CH_S >> 4) + (b & 3) * 64);
                const uint64_t dv = dv0 + (uint64_t)(c * (KF_CH_S >> 4) + (b & 3) * 64);
                float s[32];
                uint32_t p[16];
                mbar_wait(kvbar + 8 * c, 0);
                wg_fence();
                wgmma_qk_n64(s, qa[0], qa[1], qa[2], qa[3], dk);
                wg_commit();
                if ((b & 3) == 0) { KF_RELEASE_CHUNK(c); }
                wg_wait<0>();
                fence_regs(s);
                float x0 = s[0], x1 = s[2];
#pragma unroll
                for (int j = 0; j < 8; j++) {
                    x0 = fmaxf(x0, fmaxf(s[4 * j], s[4 * j + 1]));
                    x1 = fmaxf(x1, fmaxf(s[4 * j + 2], s[4 * j + 3]));
                }
                x0 = fmaxf(x0, __shfl_xor_sync(0xffffffffu, x0, 1));
                x0 = fmaxf(x0, __shfl_xor_sync(0xffffffffu, x0, 2));
                x1 = fmaxf(x1, __shfl_xor_sync(0xffffffffu, x1, 1));
                x1 = fmaxf(x1, __shfl_xor_sync(0xffffffffu, x1, 2));
                const float n0 = fmaxf(m0, x0), n1 = fmaxf(m1, x1);
                const float c0 = ex2f(m0 - n0), c1 = ex2f(m1 - n1);
                m0 = n0; m1 = n1;
#pragma unroll
                for (int j = 0; j < 3; j++) {
                    o[4 * j] *= c0; o[4 * j + 1] *= c0; o[4 * j + 2] *= c1; o[4 * j + 3] *= c1;
                }
#pragma unroll
                for (int j = 0; j < 8; j++) {
                    p[2 * j] = pack_bf16(ex2f(s[4 * j] - n0), ex2f(s[4 * j + 1] - n0));
                    p[2 * j + 1] = pack_bf16(ex2f(s[4 * j + 2] - n1), ex2f(s[4 * j + 3] - n1));
                }
                fence_regs(o);
                wg_fence();
                KF_PV(p, 0);
                wg_commit();
                wg_wait<0>();
                fence_regs(o);
            }
        }
        const float inv0 = 1.f / o[8], inv1 = 1.f / o[10];
        uint32_t* out0 = (uint32_t*)(g_o + (size_t)row0 * DM + head * 16);
        uint32_t* out1 = (uint32_t*)(g_o + (size_t)(row0 + 8) * DM + head * 16);
        out0[t] = pack_bf16(o[0] * inv0, o[1] * inv0);
        out0[4 + t] = pack_bf16(o[4] * inv0, o[5] * inv0);
        out1[t] = pack_bf16(o[2] * inv1, o[3] * inv1);
        out1[4 + t] = pack_bf16(o[6] * inv1, o[7] * inv1);
        named_sync(4 + wg, 128);
        if ((tid & 127) == 0) red_release_add(&g_oflag[quarter * 8 + pass * 4 + wg]);
        if (tid == 0) TSTAMP0(1, 2 + pass);
    }

    if (wg < 2) {
        const int wi = warp;
        const int r0 = mt * 64 + wi * 16 + g;
        const int cb = nt * 128 + wg * 64;
        uint32_t xr[16], wr[8];
#pragma unroll
        for (int j = 0; j < 8; j++) {
            xr[2 * j] = __ldg((const uint32_t*)(x + (size_t)r0 * DM + cb + 8 * j + 2 * t));
            xr[2 * j + 1] = __ldg((const uint32_t*)(x + (size_t)(r0 + 8) * DM + cb + 8 * j + 2 * t));
            wr[j] = __ldg((const uint32_t*)(w_r + cb + 8 * j + 2 * t));
        }
        if (tid == 0) {
            int spins = 0;
            while (ld_acquire(&g_oflag[mt]) < 32u && ++spins < (1 << 22)) {}
        }
        named_sync(1, 512);
        if (tid == 0) {
            asm volatile("fence.proxy.async;" ::: "memory");
            TSTAMP0(2, 1);
            for (int k2 = 0; k2 < 4; k2++) {
                mbar_expect_tx(obar + 8 * k2, 16384);
                tma_load_3d(sb + (4 + k2) * KF_CH_S, &tm_o, 0, mt * 64, k2 * 2, obar + 8 * k2);
            }
        }
        float wsum = 0.f;
        {
            const uint4 a = __ldg((const uint4*)(w_r + lane * 16)), b = __ldg((const uint4*)(w_r + lane * 16 + 8));
            const uint32_t w[8] = {a.x, a.y, a.z, a.w, b.x, b.y, b.z, b.w};
#pragma unroll
            for (int i = 0; i < 8; i++) wsum += bf_lo(w[i]) + bf_hi(w[i]);
#pragma unroll
            for (int o = 16; o > 0; o >>= 1) wsum += __shfl_xor_sync(0xffffffffu, wsum, o);
        }
        float acc[32];
#pragma unroll
        for (int i = 0; i < 32; i++) acc[i] = 0.f;
        fence_regs(acc);
#pragma unroll 1
        for (int kb = 0; kb < 8; kb++) {
            mbar_wait(wbar + 8 * kb, 0);
            mbar_wait(obar + 8 * (kb >> 1), 0);
            const uint32_t wa = (kb < 4) ? (KF_OFF_WO + kb * 16384) : ((kb - 4) * KF_CH_S);
            const uint64_t da = make_desc(sb + (4 + (kb >> 1)) * KF_CH_S + (kb & 1) * 8192, 16, 1024, 1);
            const uint64_t db = make_desc(sb + wa + wg * 8192, 1024, 1024, 1);
            wg_fence();
#pragma unroll
            for (int k = 0; k < 4; k++) wgmma_k3_n64(acc, da + k * 2, db + k * 128, (kb | k) != 0);
            wg_commit();
        }
        wg_wait<0>();
        fence_regs(acc);
        if (tid == 0) TSTAMP0(2, 2);
        float hv[32];
        float s0 = 0.f, s1 = 0.f, d0 = 0.f, d1 = 0.f;
#pragma unroll
        for (int j = 0; j < 8; j++) {
            hv[4 * j] = rbf(bf_lo(xr[2 * j]) + rbf(acc[4 * j]));
            hv[4 * j + 1] = rbf(bf_hi(xr[2 * j]) + rbf(acc[4 * j + 1]));
            hv[4 * j + 2] = rbf(bf_lo(xr[2 * j + 1]) + rbf(acc[4 * j + 2]));
            hv[4 * j + 3] = rbf(bf_hi(xr[2 * j + 1]) + rbf(acc[4 * j + 3]));
            const float wl = bf_lo(wr[j]), wh = bf_hi(wr[j]);
            s0 += hv[4 * j] + hv[4 * j + 1];
            s1 += hv[4 * j + 2] + hv[4 * j + 3];
            d0 = fmaf(hv[4 * j], wl, fmaf(hv[4 * j + 1], wh, d0));
            d1 = fmaf(hv[4 * j + 2], wl, fmaf(hv[4 * j + 3], wh, d1));
        }
#pragma unroll
        for (int o = 1; o < 4; o <<= 1) {
            s0 += __shfl_xor_sync(0xffffffffu, s0, o);
            s1 += __shfl_xor_sync(0xffffffffu, s1, o);
            d0 += __shfl_xor_sync(0xffffffffu, d0, o);
            d1 += __shfl_xor_sync(0xffffffffu, d1, o);
        }
        const float mu0 = s0 * (1.f / 64), mu1 = s1 * (1.f / 64);
        float q0 = 0.f, q1 = 0.f;
#pragma unroll
        for (int j = 0; j < 8; j++) {
            float a = hv[4 * j] - mu0, b = hv[4 * j + 1] - mu0, c = hv[4 * j + 2] - mu1, d = hv[4 * j + 3] - mu1;
            q0 = fmaf(a, a, fmaf(b, b, q0));
            q1 = fmaf(c, c, fmaf(d, d, q1));
        }
#pragma unroll
        for (int o = 1; o < 4; o <<= 1) {
            q0 += __shfl_xor_sync(0xffffffffu, q0, o);
            q1 += __shfl_xor_sync(0xffffffffu, q1, o);
        }
        float4* part = g_part + (size_t)mt * 512 + wi * 16 + g;
        if (t < 2) {
            float4* dst = part + (nt * 2 + wg) * 64 + t * 8;
            const float a = t ? mu1 : mu0, b = t ? q1 : q0, c = t ? d1 : d0;
            asm volatile("st.relaxed.gpu.global.v4.f32 [%0], {%1, %2, %3, %4};" ::"l"(dst), "f"(a), "f"(b), "f"(c), "f"(1.0f) : "memory");
        }
        const uint32_t stg_off = KF_OFF_WO + (wi >> 1) * 16384 + wg * 8192 + (wi & 1) * 4096;
        const uint32_t stg_o = sb + stg_off, stg_h = stg_o + 2048;
        const int srow = (lane & 7) + ((lane >> 3) & 1) * 8;
        const int sj = lane >> 4;
        named_sync(4 + wg, 128);
#pragma unroll
        for (int j = 0; j < 8; j += 2) {
            const uint32_t off = srow * 128 + (((j + sj) ^ (srow & 7)) << 4);
            stmatrix_x4(stg_h + off, pack_bf16(hv[4 * j], hv[4 * j + 1]), pack_bf16(hv[4 * j + 2], hv[4 * j + 3]),
                        pack_bf16(hv[4 * j + 4], hv[4 * j + 5]), pack_bf16(hv[4 * j + 6], hv[4 * j + 7]));
        }
        __syncwarp();
#pragma unroll
        for (int i = 0; i < 4; i++) {
            const int row = i * 4 + (lane >> 3), ch = lane & 7;
            const uint4 vh = *(const uint4*)(sp + stg_off + 2048 + row * 128 + ((ch ^ (row & 7)) << 4));
            *(uint4*)(g_h + (size_t)(mt * 64 + wi * 16 + row) * DM + cb + ch * 8) = vh;
        }
        named_sync(4 + wg, 128);
        if ((tid & 127) == 0) red_release_add(&g_hflag[mt]);
        float mean[2], den[2], rr[2];
        {
            float4 v[4];
            int spins = 0;
            while (true) {
#pragma unroll
                for (int i = 0; i < 4; i++) {
                    const float4* p = part + (t + (i & 1) * 4) * 64 + (i >> 1) * 8;
                    asm volatile("ld.relaxed.gpu.global.v4.f32 {%0, %1, %2, %3}, [%4];" : "=f"(v[i].x), "=f"(v[i].y), "=f"(v[i].z), "=f"(v[i].w) : "l"(p) : "memory");
                }
                const bool ok = (v[0].w != 0.f) && (v[1].w != 0.f) && (v[2].w != 0.f) && (v[3].w != 0.f);
                if (__all_sync(0xffffffffu, ok) || ++spins > (1 << 22)) break;
            }
#pragma unroll
            for (int u = 0; u < 2; u++) {
                float mu = v[2 * u].x + v[2 * u + 1].x, m2 = v[2 * u].y + v[2 * u + 1].y, hw = v[2 * u].z + v[2 * u + 1].z;
#pragma unroll
                for (int o = 1; o < 4; o <<= 1) {
                    mu += __shfl_xor_sync(0xffffffffu, mu, o);
                    m2 += __shfl_xor_sync(0xffffffffu, m2, o);
                    hw += __shfl_xor_sync(0xffffffffu, hw, o);
                }
                mu *= 0.125f;
                const float da = v[2 * u].x - mu, db = v[2 * u + 1].x - mu;
                float dd = 64.f * (da * da + db * db);
#pragma unroll
                for (int o = 1; o < 4; o <<= 1) dd += __shfl_xor_sync(0xffffffffu, dd, o);
                m2 += dd;
                mean[u] = rbf(mu);
                den[u] = rbf(sqrtf(rbf(rbf(m2 * (1.f / DM)) + 1e-5f)));
                rr[u] = rbf((hw - mean[u] * wsum) / den[u]);
            }
        }
        if (tid == 0) TSTAMP0(2, 3);
        if (nt == 0 && wg == 0) {
            float2* s_st = (float2*)(sp + KF_OFF_WO + 49152);
            if (t == 0) {
                s_key[wi * 16 + g] = ((unsigned long long)order_bits(rr[0]) << 32) | (uint32_t)(0x7FFFFFFF - (r0 + 1));
                s_key[wi * 16 + g + 8] = ((unsigned long long)order_bits(rr[1]) << 32) | (uint32_t)(0x7FFFFFFF - (r0 + 9));
                s_st[wi * 16 + g] = make_float2(mean[0], den[0]);
                s_st[wi * 16 + g + 8] = make_float2(mean[1], den[1]);
            }
            named_sync(4, 128);
            if (warp == 0) {
                unsigned long long a = s_key[lane], b = s_key[lane + 32];
                if (b > a) { const unsigned long long c = a; a = b; b = c; }
                warp_top2(a, b);
                if (lane < 2) {
                    const unsigned long long k = lane ? b : a;
                    const int tok1 = 0x7FFFFFFF - (int)(uint32_t)k;
                    const float2 st = s_st[(tok1 - 1) & 63];
                    asm volatile("st.relaxed.gpu.global.v4.u32 [%0], {%1, %2, %3, %4};" ::"l"(g_cand + mt * 2 + lane), "r"((uint32_t)(k >> 32)),
                                 "r"((uint32_t)tok1), "r"(__float_as_uint(st.x)), "r"(__float_as_uint(st.y)) : "memory");
                }
            }
        }
        const float i0 = 1.f / den[0], i1 = 1.f / den[1];
#pragma unroll
        for (int j = 0; j < 8; j += 2) {
            uint32_t ro[4];
#pragma unroll
            for (int u = 0; u < 2; u++) {
                const int jj = j + u;
                const float a = hv[4 * jj], b = hv[4 * jj + 1], c = hv[4 * jj + 2], d = hv[4 * jj + 3];
                const float na = rbf(rbf(a - mean[0]) * i0), nb = rbf(rbf(b - mean[0]) * i0);
                const float nc = rbf(rbf(c - mean[1]) * i1), nd = rbf(rbf(d - mean[1]) * i1);
                ro[2 * u] = pack_bf16(a + na, b + nb);
                ro[2 * u + 1] = pack_bf16(c + nc, d + nd);
            }
            const uint32_t off = srow * 128 + (((j + sj) ^ (srow & 7)) << 4);
            stmatrix_x4(stg_o + off, ro[0], ro[1], ro[2], ro[3]);
        }
        __syncwarp();
#pragma unroll
        for (int i = 0; i < 4; i++) {
            const int row = i * 4 + (lane >> 3), ch = lane & 7;
            const uint4 vo = *(const uint4*)(sp + stg_off + row * 128 + ((ch ^ (row & 7)) << 4));
            *(uint4*)(out + (size_t)(mt * 64 + wi * 16 + row) * DM + cb + ch * 8) = vo;
        }
        named_sync(4 + wg, 128);
        if ((tid & 127) == 0) red_release_add(&g_cnt);
        if (tid == 0) TSTAMP0(2, 4);
    } else {
        named_arrive(1, 512);
        const bool worker = blockIdx.x < FF / 16;
        const bool finisher = blockIdx.x == gridDim.x - 1;
        if (!worker && !finisher) return;
        const int mtid = tid - 256, mwarp = mtid >> 5;
        const int f0 = blockIdx.x * 16;
        uint2 wgu[16];
        uint32_t wd[16];
        if (worker) {
            const __nv_bfloat16* base = (mwarp < 4 ? w_gate : w_up) + (size_t)(16 * lane) * FF + f0 + (mwarp & 3) * 4;
#pragma unroll
            for (int k = 0; k < 16; k++) wgu[k] = __ldg((const uint2*)(base + (size_t)k * FF));
#pragma unroll
            for (int f = 0; f < 16; f++) wd[f] = __ldg((const uint32_t*)(w_down + (size_t)(f0 + f) * DM + 2 * mtid));
        }
        if (mtid == 0) TSTAMP0(3, 0);
        uint4 ca, cb4;
        {
            int spins = 0;
            while (true) {
                asm volatile("ld.relaxed.gpu.global.v4.u32 {%0, %1, %2, %3}, [%4];" : "=r"(ca.x), "=r"(ca.y), "=r"(ca.z), "=r"(ca.w) : "l"(g_cand + 2 * lane) : "memory");
                asm volatile("ld.relaxed.gpu.global.v4.u32 {%0, %1, %2, %3}, [%4];" : "=r"(cb4.x), "=r"(cb4.y), "=r"(cb4.z), "=r"(cb4.w) : "l"(g_cand + 2 * lane + 1) : "memory");
                const unsigned int hf = ld_acquire(&g_hflag[lane]);
                const bool ok = ca.y != 0 && cb4.y != 0 && hf >= 8u;
                if (__all_sync(0xffffffffu, ok) || ++spins > (1 << 22)) break;
            }
            __syncwarp();
        }
        if (mtid == 0) TSTAMP0(3, 1);
        unsigned long long ka = cand_key(ca), kb = cand_key(cb4);
        const unsigned long long mya = ka, myb = kb;
        warp_top2(ka, kb);
        int idx[2];
        float mean[2], den[2], rv[2];
#pragma unroll
        for (int u = 0; u < 2; u++) {
            const unsigned long long k = u ? kb : ka;
            const unsigned int own = __ballot_sync(0xffffffffu, mya == k || myb == k);
            const int src = __ffs(own) - 1;
            const bool first = (mya == k);
            mean[u] = __uint_as_float(__shfl_sync(0xffffffffu, first ? ca.z : cb4.z, src));
            den[u] = __uint_as_float(__shfl_sync(0xffffffffu, first ? ca.w : cb4.w, src));
            idx[u] = (0x7FFFFFFF - (int)(uint32_t)k) - 1;
            rv[u] = order_value((uint32_t)(k >> 32));
        }
        float hx[2][2], xo[2][2];
        if (worker) {
            float acc[8];
#pragma unroll
            for (int i = 0; i < 8; i++) acc[i] = 0.f;
            uint4 ha[2], hb[2];
#pragma unroll
            for (int u = 0; u < 2; u++) {
                const uint4* hp = (const uint4*)(g_h + (size_t)idx[u] * DM + 16 * lane);
                ha[u] = __ldcg(hp); hb[u] = __ldcg(hp + 1);
            }
#pragma unroll
            for (int u = 0; u < 2; u++) {
                const float inv = 1.f / den[u];
                const uint32_t hw[8] = {ha[u].x, ha[u].y, ha[u].z, ha[u].w, hb[u].x, hb[u].y, hb[u].z, hb[u].w};
#pragma unroll
                for (int k = 0; k < 8; k++) {
                    const float x0 = rbf(rbf(bf_lo(hw[k]) - mean[u]) * inv), x1 = rbf(rbf(bf_hi(hw[k]) - mean[u]) * inv);
                    const uint2 wa = wgu[2 * k], wb = wgu[2 * k + 1];
                    acc[u * 4 + 0] = fmaf(x0, bf_lo(wa.x), fmaf(x1, bf_lo(wb.x), acc[u * 4 + 0]));
                    acc[u * 4 + 1] = fmaf(x0, bf_hi(wa.x), fmaf(x1, bf_hi(wb.x), acc[u * 4 + 1]));
                    acc[u * 4 + 2] = fmaf(x0, bf_lo(wa.y), fmaf(x1, bf_lo(wb.y), acc[u * 4 + 2]));
                    acc[u * 4 + 3] = fmaf(x0, bf_hi(wa.y), fmaf(x1, bf_hi(wb.y), acc[u * 4 + 3]));
                }
            }
#define KF_STEP(O, N)                                                          \
            {                                                                  \
                const bool up = (lane & (O)) != 0;                             \
                _Pragma("unroll") for (int i = 0; i < (N); i++) {              \
                    const float send = up ? acc[i] : acc[i + (N)];             \
                    const float keep = up ? acc[i + (N)] : acc[i];             \
                    acc[i] = keep + __shfl_xor_sync(0xffffffffu, send, (O));   \
                }                                                              \
            }
            KF_STEP(16, 4) KF_STEP(8, 2) KF_STEP(4, 1)
            acc[0] += __shfl_xor_sync(0xffffffffu, acc[0], 2);
            acc[0] += __shfl_xor_sync(0xffffffffu, acc[0], 1);
            if ((lane & 3) == 0) {
                const int v = ((lane & 16) ? 4 : 0) + ((lane & 8) ? 2 : 0) + ((lane & 4) ? 1 : 0);
                s_gu[(v >> 2) * 32 + mwarp * 4 + (v & 3)] = acc[0];
            }
            named_sync(2, 256);
            float y[2][2] = {{0.f, 0.f}, {0.f, 0.f}};
            {
                const int u = lane >> 4, c = lane & 15;
                const float gb = rbf(s_gu[u * 32 + c]);
                const float sg = rbf(gb / (1.f + __expf(-gb)));
                const float a = rbf(sg * rbf(s_gu[u * 32 + 16 + c]));
#pragma unroll
                for (int f = 0; f < 16; f++) {
                    const float a0 = __shfl_sync(0xffffffffu, a, f), a1 = __shfl_sync(0xffffffffu, a, 16 + f);
                    const float w0 = bf_lo(wd[f]), w1 = bf_hi(wd[f]);
                    y[0][0] = fmaf(a0, w0, y[0][0]); y[0][1] = fmaf(a0, w1, y[0][1]);
                    y[1][0] = fmaf(a1, w0, y[1][0]); y[1][1] = fmaf(a1, w1, y[1][1]);
                }
            }
#pragma unroll
            for (int u = 0; u < 2; u++)
                asm volatile("red.global.add.v2.f32 [%0], {%1, %2};" ::"l"(g_y + u * DM + 2 * mtid), "f"(y[u][0]), "f"(y[u][1]) : "memory");
            if (mtid == 0) TSTAMP0(3, 2);
            named_sync(2, 256);
            if (mtid == 0) red_release_add(&g_cnt);
            if (mtid == 0) TSTAMP0(3, 3);
        } else {
#pragma unroll
            for (int u = 0; u < 2; u++) {
                const uint32_t ho = __ldcg((const uint32_t*)(g_h + (size_t)idx[u] * DM + 2 * mtid));
                const float inv = 1.f / den[u];
                hx[u][0] = bf_lo(ho); hx[u][1] = bf_hi(ho);
                xo[u][0] = rbf(rbf(hx[u][0] - mean[u]) * inv); xo[u][1] = rbf(rbf(hx[u][1] - mean[u]) * inv);
            }
            if (mtid == 0) {
                int spins = 0;
                while (ld_acquire(&g_cnt) < (unsigned)(FF / 16 + 256) && ++spins < (1 << 22)) {}
            }
            named_sync(2, 256);
#pragma unroll
            for (int u = 0; u < 2; u++) {
                const float2 yy = __ldcg((const float2*)(g_y + u * DM + 2 * mtid));
                const float sig = rbf(1.f / (1.f + __expf(-rv[u])));
                const float o0 = hx[u][0] + rbf(xo[u][0] + rbf(rbf(yy.x) * sig));
                const float o1 = hx[u][1] + rbf(xo[u][1] + rbf(rbf(yy.y) * sig));
                *(uint32_t*)(out + (size_t)idx[u] * DM + 2 * mtid) = pack_bf16(o0, o1);
            }
            if (mtid == 0) g_epoch = g_epoch + 1u;
            if (mtid == 0) TSTAMP0(3, 4);
        }
    }
}

typedef CUresult (*PFN_encodeTiled)(CUtensorMap*, CUtensorMapDataType, cuuint32_t, void*, const cuuint64_t*, const cuuint64_t*,
                                    const cuuint32_t*, const cuuint32_t*, CUtensorMapInterleave, CUtensorMapSwizzle,
                                    CUtensorMapL2promotion, CUtensorMapFloatOOBfill);

void make_map(PFN_encodeTiled enc, CUtensorMap* m, const void* ptr, uint64_t cols, uint64_t rows, uint32_t bcols, uint32_t brows) {
    cuuint64_t dims[2] = {cols, rows};
    cuuint64_t strides[1] = {cols * 2};
    cuuint32_t box[2] = {bcols, brows};
    cuuint32_t es[2] = {1, 1};
    enc(m, CU_TENSOR_MAP_DATA_TYPE_BFLOAT16, 2, const_cast<void*>(ptr), dims, strides, box, es, CU_TENSOR_MAP_INTERLEAVE_NONE,
        CU_TENSOR_MAP_SWIZZLE_128B, CU_TENSOR_MAP_L2_PROMOTION_L2_256B, CU_TENSOR_MAP_FLOAT_OOB_FILL_NONE);
}

void make_map3(PFN_encodeTiled enc, CUtensorMap* m, const void* ptr, uint64_t d0, uint64_t rows, uint64_t d2, uint64_t row_stride_bytes,
               uint64_t d2_stride_bytes, uint32_t b0, uint32_t b1, uint32_t b2) {
    cuuint64_t dims[3] = {d0, rows, d2};
    cuuint64_t strides[2] = {row_stride_bytes, d2_stride_bytes};
    cuuint32_t box[3] = {b0, b1, b2};
    cuuint32_t es[3] = {1, 1, 1};
    enc(m, CU_TENSOR_MAP_DATA_TYPE_BFLOAT16, 3, const_cast<void*>(ptr), dims, strides, box, es, CU_TENSOR_MAP_INTERLEAVE_NONE,
        CU_TENSOR_MAP_SWIZZLE_128B, CU_TENSOR_MAP_L2_PROMOTION_L2_256B, CU_TENSOR_MAP_FLOAT_OOB_FILL_NONE);
}

template <typename... KArgs, typename... Args>
void launch(void (*kern)(KArgs...), int grid, int block, int smem, bool pdl, Args... args) {
    cudaLaunchConfig_t cfg = {};
    cfg.gridDim = dim3(grid);
    cfg.blockDim = dim3(block);
    cfg.dynamicSmemBytes = smem;
    cfg.stream = cudaStreamPerThread;
    cudaLaunchAttribute at[1];
    at[0].id = cudaLaunchAttributeProgrammaticStreamSerialization;
    at[0].val.programmaticStreamSerializationAllowed = 1;
    cfg.attrs = at;
    cfg.numAttrs = pdl ? 1 : 0;
    cudaLaunchKernelEx(&cfg, kern, KArgs(args)...);
}

}

extern "C" void kernel_launch(void* const* d_in, const int* in_sizes, int n_in, void* d_out, int out_size) {
    const __nv_bfloat16* x = (const __nv_bfloat16*)d_in[0];
    const __nv_bfloat16* wqkv = (const __nv_bfloat16*)d_in[1];
    const __nv_bfloat16* wo = (const __nv_bfloat16*)d_in[2];
    const __nv_bfloat16* w_r = (const __nv_bfloat16*)d_in[4];
    const __nv_bfloat16* w_gate = (const __nv_bfloat16*)d_in[5];
    const __nv_bfloat16* w_up = (const __nv_bfloat16*)d_in[6];
    const __nv_bfloat16* w_down = (const __nv_bfloat16*)d_in[7];
    __nv_bfloat16* out = (__nv_bfloat16*)d_out;

    static PFN_encodeTiled enc = nullptr;
    static void* g_o_ptr = nullptr;
    if (!enc) {
        cudaDriverEntryPointQueryResult qres;
        void* fn = nullptr;
        cudaGetDriverEntryPoint("cuTensorMapEncodeTiled", &fn, cudaEnableDefault, &qres);
        enc = (PFN_encodeTiled)fn;
        cudaGetSymbolAddress(&g_o_ptr, g_o);
        cudaFuncSetAttribute(k1_qkv, cudaFuncAttributeMaxDynamicSharedMemorySize, K1_SMEM);
        cudaFuncSetAttribute(kf_main, cudaFuncAttributeMaxDynamicSharedMemorySize, KF_SMEM);
    }
    CUtensorMap tm_x, tm_w, tm_o, tm_wo;
    make_map(enc, &tm_x, x, DM, SEQ, 64, 128);
    make_map3(enc, &tm_w, wqkv, DM, DM, 3, 3 * DM * 2, DM * 2, 64, 64, 3);
    make_map3(enc, &tm_o, g_o_ptr, 64, SEQ, 8, DM * 2, 128, 64, 64, 2);
    make_map3(enc, &tm_wo, wo, 64, DM, 8, DM * 2, 128, 64, 64, 2);

    const bool pdl = true;
    launch(k1_qkv, 128, 544, K1_SMEM, false, tm_x, tm_w, x);
    launch(kf_main, 128, 512, KF_SMEM, pdl, tm_o, tm_wo, x, wo, w_r, w_gate, w_up, w_down, out);
}
```

```cpp
#include <cuda_runtime.h>
#include <cuda_bf16.h>
#include <cuda.h>
#include <stdint.h>

namespace {

constexpr int SEQ = 2048, DM = 512, NH = 32, FF = 1792;

__device__ __align__(1024) uint8_t g_q[NH * 2 * SEQ * 16];
__device__ __align__(1024) uint8_t g_kv[NH * 8 * 16384];
__device__ float g_norm[16 * NH * 3];
__device__ __align__(1024) __nv_bfloat16 g_o[SEQ * DM];
__device__ __align__(1024) __nv_bfloat16 g_h[SEQ * DM];
__device__ __align__(16) uint4 g_cand[64];
__device__ unsigned int g_oflag[32 * 32];
__device__ unsigned int g_hflag[32];
__device__ __align__(16) float g_y[2 * DM];
__device__ unsigned int g_cnt;
__device__ unsigned int g_epoch;
__device__ __align__(16) float4 g_ln1[SEQ];
__device__ __align__(16) float4 g_part[32 * 8 * 64];

#define TSTAMP(K, I)
#define TSTAMP0(K, I)
__device__ __forceinline__ uint32_t smem_u32(const void* p) { return (uint32_t)__cvta_generic_to_shared(p); }
__device__ __forceinline__ void wg_fence() { asm volatile("wgmma.fence.sync.aligned;" ::: "memory"); }
__device__ __forceinline__ void wg_commit() { asm volatile("wgmma.commit_group.sync.aligned;" ::: "memory"); }
template <int N> __device__ __forceinline__ void wg_wait() { asm volatile("wgmma.wait_group.sync.aligned %0;" ::"n"(N) : "memory"); }
template <int N> __device__ __forceinline__ void fence_regs(float (&r)[N]) {
#pragma unroll
    for (int i = 0; i < N; i++) asm volatile("" : "+f"(r[i])::"memory");
}
__device__ __forceinline__ uint64_t make_desc(uint32_t addr, uint32_t lbo, uint32_t sbo, uint32_t swz) {
    uint64_t d = 0;
    d |= (uint64_t)((addr & 0x3FFFF) >> 4);
    d |= (uint64_t)((lbo & 0x3FFFF) >> 4) << 16;
    d |= (uint64_t)((sbo & 0x3FFFF) >> 4) << 32;
    d |= (uint64_t)swz << 62;
    return d;
}
__device__ __forceinline__ void mbar_init(uint32_t bar, uint32_t cnt) {
    asm volatile("mbarrier.init.shared::cta.b64 [%0], %1;" ::"r"(bar), "r"(cnt) : "memory");
}
__device__ __forceinline__ void mbar_expect_tx(uint32_t bar, uint32_t bytes) {
    asm volatile("mbarrier.arrive.expect_tx.shared::cta.b64 _, [%0], %1;" ::"r"(bar), "r"(bytes) : "memory");
}
__device__ __forceinline__ void mbar_arrive(uint32_t bar) {
    asm volatile("mbarrier.arrive.shared::cta.b64 _, [%0];" ::"r"(bar) : "memory");
}
__device__ __forceinline__ void mbar_wait(uint32_t bar, uint32_t parity) {
    asm volatile(
        "{\n.reg .pred p;\nWAIT_%=:\n"
        "mbarrier.try_wait.parity.shared::cta.b64 p, [%0], %1;\n"
        "@p bra DONE_%=;\nbra WAIT_%=;\nDONE_%=:\n}\n" ::"r"(bar), "r"(parity) : "memory");
}
__device__ __forceinline__ void bulk_g2s(uint32_t dst, const void* src, uint32_t bytes, uint32_t bar) {
    asm volatile("cp.async.bulk.shared::cluster.global.mbarrier::complete_tx::bytes [%0], [%1], %2, [%3];" ::"r"(dst),
                 "l"(src), "r"(bytes), "r"(bar) : "memory");
}
__device__ __forceinline__ void bulk_s2g(void* dst, uint32_t src, uint32_t bytes) {
    asm volatile("cp.async.bulk.global.shared::cta.bulk_group [%0], [%1], %2;" ::"l"(dst), "r"(src), "r"(bytes) : "memory");
}
__device__ __forceinline__ void tma_load_2d(uint32_t dst, const CUtensorMap* tm, int c0, int c1, uint32_t bar) {
    asm volatile("cp.async.bulk.tensor.2d.shared::cluster.global.mbarrier::complete_tx::bytes [%0], [%1, {%3, %4}], [%2];" ::"r"(dst),
                 "l"(tm), "r"(bar), "r"(c0), "r"(c1) : "memory");
}
__device__ __forceinline__ void tma_load_3d(uint32_t dst, const CUtensorMap* tm, int c0, int c1, int c2, uint32_t bar) {
    asm volatile("cp.async.bulk.tensor.3d.shared::cluster.global.mbarrier::complete_tx::bytes [%0], [%1, {%3, %4, %5}], [%2];" ::"r"(dst),
                 "l"(tm), "r"(bar), "r"(c0), "r"(c1), "r"(c2) : "memory");
}
__device__ __forceinline__ void tma_load_2d_mc(uint32_t dst, const CUtensorMap* tm, int c0, int c1, uint32_t bar, uint16_t mask) {
    asm volatile("cp.async.bulk.tensor.2d.shared::cluster.global.mbarrier::complete_tx::bytes.multicast::cluster [%0], [%1, {%3, %4}], [%2], %5;" ::"r"(dst),
                 "l"(tm), "r"(bar), "r"(c0), "r"(c1), "h"(mask) : "memory");
}
__device__ __forceinline__ void mbar_arrive_cluster(uint32_t bar, uint32_t cta) {
    asm volatile("{\n.reg .b32 ra;\nmapa.shared::cluster.u32 ra, %0, %1;\nmbarrier.arrive.release.cluster.shared::cluster.b64 _, [ra];\n}" ::"r"(bar), "r"(cta) : "memory");
}
__device__ __forceinline__ void cluster_sync() {
    asm volatile("barrier.cluster.arrive.release.aligned;\nbarrier.cluster.wait.acquire.aligned;" ::: "memory");
}
__device__ __forceinline__ void prefetch_l2(const void* p, uint32_t bytes) {
    asm volatile("cp.async.bulk.prefetch.L2.global [%0], %1;" ::"l"(p), "r"(bytes) : "memory");
}
__device__ __forceinline__ void fence_proxy_async() { asm volatile("fence.proxy.async.shared::cta;" ::: "memory"); }
__device__ __forceinline__ void fence_barrier_init() { asm volatile("fence.mbarrier_init.release.cluster;" ::: "memory"); }
__device__ __forceinline__ void pdl_launch() { asm volatile("griddepcontrol.launch_dependents;" ::: "memory"); }
__device__ __forceinline__ void pdl_wait() { asm volatile("griddepcontrol.wait;" ::: "memory"); }
__device__ __forceinline__ void named_sync(int id, int n) { asm volatile("bar.sync %0, %1;" ::"r"(id), "r"(n) : "memory"); }
__device__ __forceinline__ void named_arrive(int id, int n) { asm volatile("bar.arrive %0, %1;" ::"r"(id), "r"(n) : "memory"); }

__device__ __forceinline__ float ex2f(float x) { float y; asm("ex2.approx.ftz.f32 %0, %1;" : "=f"(y) : "f"(x)); return y; }
__device__ __forceinline__ uint32_t pack_bf16(float lo, float hi) {
    uint32_t r; asm("cvt.rn.bf16x2.f32 %0, %1, %2;" : "=r"(r) : "f"(hi), "f"(lo)); return r;
}
__device__ __forceinline__ float bf_lo(uint32_t v) { return __uint_as_float(v << 16); }
__device__ __forceinline__ float bf_hi(uint32_t v) { return __uint_as_float(v & 0xFFFF0000u); }
__device__ __forceinline__ float rbf(float x) { return __bfloat162float(__float2bfloat16_rn(x)); }
__device__ __forceinline__ uint32_t fma_bf16x2(uint32_t a, uint32_t b, uint32_t c) {
    uint32_t r; asm("fma.rn.bf16x2 %0, %1, %2, %3;" : "=r"(r) : "r"(a), "r"(b), "r"(c)); return r;
}
__device__ __forceinline__ void stmatrix_x4(uint32_t addr, uint32_t r0, uint32_t r1, uint32_t r2, uint32_t r3) {
    asm volatile("stmatrix.sync.aligned.m8n8.x4.shared.b16 [%0], {%1, %2, %3, %4};" ::"r"(addr), "r"(r0), "r"(r1), "r"(r2), "r"(r3) : "memory");
}
__device__ __forceinline__ void stmatrix_x4_trans(uint32_t addr, uint32_t r0, uint32_t r1, uint32_t r2, uint32_t r3) {
    asm volatile("stmatrix.sync.aligned.m8n8.x4.trans.shared.b16 [%0], {%1, %2, %3, %4};" ::"r"(addr), "r"(r0), "r"(r1), "r"(r2), "r"(r3) : "memory");
}

__device__ __forceinline__ void wgmma_k1_n136(float (&d)[68], uint64_t desca, uint64_t descb, int scale_d) {
  asm volatile("{\n.reg .pred p;\nsetp.ne.b32 p, %70, 0;\n"
    "wgmma.mma_async.sync.aligned.m64n136k16.f32.bf16.bf16 "
    "{%0, %1, %2, %3, %4, %5, %6, %7, %8, %9, %10, %11, %12, %13, %14, %15, %16, %17, %18, %19, %20, %21, %22, %23, %24, %25, %26, %27, %28, %29, %30, %31, %32, %33, %34, %35, %36, %37, %38, %39, %40, %41, %42, %43, %44, %45, %46, %47, %48, %49, %50, %51, %52, %53, %54, %55, %56, %57, %58, %59, %60, %61, %62, %63, %64, %65, %66, %67}, "
    "%68, %69, p, 1, 1, 1, 0;\n}\n"
    : "+f"(d[0]), "+f"(d[1]), "+f"(d[2]), "+f"(d[3]), "+f"(d[4]), "+f"(d[5]), "+f"(d[6]), "+f"(d[7]), "+f"(d[8]), "+f"(d[9]), "+f"(d[10]), "+f"(d[11]), "+f"(d[12]), "+f"(d[13]), "+f"(d[14]), "+f"(d[15]), "+f"(d[16]), "+f"(d[17]), "+f"(d[18]), "+f"(d[19]), "+f"(d[20]), "+f"(d[21]), "+f"(d[22]), "+f"(d[23]), "+f"(d[24]), "+f"(d[25]), "+f"(d[26]), "+f"(d[27]), "+f"(d[28]), "+f"(d[29]), "+f"(d[30]), "+f"(d[31]), "+f"(d[32]), "+f"(d[33]), "+f"(d[34]), "+f"(d[35]), "+f"(d[36]), "+f"(d[37]), "+f"(d[38]), "+f"(d[39]), "+f"(d[40]), "+f"(d[41]), "+f"(d[42]), "+f"(d[43]), "+f"(d[44]), "+f"(d[45]), "+f"(d[46]), "+f"(d[47]), "+f"(d[48]), "+f"(d[49]), "+f"(d[50]), "+f"(d[51]), "+f"(d[52]), "+f"(d[53]), "+f"(d[54]), "+f"(d[55]), "+f"(d[56]), "+f"(d[57]), "+f"(d[58]), "+f"(d[59]), "+f"(d[60]), "+f"(d[61]), "+f"(d[62]), "+f"(d[63]), "+f"(d[64]), "+f"(d[65]), "+f"(d[66]), "+f"(d[67])
    : "l"(desca), "l"(descb), "r"(scale_d));
}
__device__ __forceinline__ void wgmma_qk_n64(float (&d)[32], uint32_t a0, uint32_t a1, uint32_t a2, uint32_t a3, uint64_t descb) {
  asm volatile("{\n.reg .pred p;\nsetp.ne.b32 p, 0, 0;\n"
    "wgmma.mma_async.sync.aligned.m64n64k16.f32.bf16.bf16 "
    "{%0, %1, %2, %3, %4, %5, %6, %7, %8, %9, %10, %11, %12, %13, %14, %15, %16, %17, %18, %19, %20, %21, %22, %23, %24, %25, %26, %27, %28, %29, %30, %31}, "
    "{%32, %33, %34, %35}, %36, p, 1, 1, 0;\n}\n"
    : "=f"(d[0]), "=f"(d[1]), "=f"(d[2]), "=f"(d[3]), "=f"(d[4]), "=f"(d[5]), "=f"(d[6]), "=f"(d[7]), "=f"(d[8]), "=f"(d[9]), "=f"(d[10]), "=f"(d[11]), "=f"(d[12]), "=f"(d[13]), "=f"(d[14]), "=f"(d[15]), "=f"(d[16]), "=f"(d[17]), "=f"(d[18]), "=f"(d[19]), "=f"(d[20]), "=f"(d[21]), "=f"(d[22]), "=f"(d[23]), "=f"(d[24]), "=f"(d[25]), "=f"(d[26]), "=f"(d[27]), "=f"(d[28]), "=f"(d[29]), "=f"(d[30]), "=f"(d[31])
    : "r"(a0), "r"(a1), "r"(a2), "r"(a3), "l"(descb));
}
__device__ __forceinline__ void wgmma_pv_n24(float (&d)[12], uint32_t a0, uint32_t a1, uint32_t a2, uint32_t a3, uint64_t descb) {
  asm volatile("{\n.reg .pred p;\nsetp.eq.b32 p, 0, 0;\n"
    "wgmma.mma_async.sync.aligned.m64n24k16.f32.bf16.bf16 "
    "{%0, %1, %2, %3, %4, %5, %6, %7, %8, %9, %10, %11}, "
    "{%12, %13, %14, %15}, %16, p, 1, 1, 1;\n}\n"
    : "+f"(d[0]), "+f"(d[1]), "+f"(d[2]), "+f"(d[3]), "+f"(d[4]), "+f"(d[5]), "+f"(d[6]), "+f"(d[7]), "+f"(d[8]), "+f"(d[9]), "+f"(d[10]), "+f"(d[11])
    : "r"(a0), "r"(a1), "r"(a2), "r"(a3), "l"(descb));
}
__device__ __forceinline__ void wgmma_k3_n64(float (&d)[32], uint64_t desca, uint64_t descb, int scale_d) {
  asm volatile("{\n.reg .pred p;\nsetp.ne.b32 p, %34, 0;\n"
    "wgmma.mma_async.sync.aligned.m64n64k16.f32.bf16.bf16 "
    "{%0, %1, %2, %3, %4, %5, %6, %7, %8, %9, %10, %11, %12, %13, %14, %15, %16, %17, %18, %19, %20, %21, %22, %23, %24, %25, %26, %27, %28, %29, %30, %31}, "
    "%32, %33, p, 1, 1, 0, 1;\n}\n"
    : "+f"(d[0]), "+f"(d[1]), "+f"(d[2]), "+f"(d[3]), "+f"(d[4]), "+f"(d[5]), "+f"(d[6]), "+f"(d[7]), "+f"(d[8]), "+f"(d[9]), "+f"(d[10]), "+f"(d[11]), "+f"(d[12]), "+f"(d[13]), "+f"(d[14]), "+f"(d[15]), "+f"(d[16]), "+f"(d[17]), "+f"(d[18]), "+f"(d[19]), "+f"(d[20]), "+f"(d[21]), "+f"(d[22]), "+f"(d[23]), "+f"(d[24]), "+f"(d[25]), "+f"(d[26]), "+f"(d[27]), "+f"(d[28]), "+f"(d[29]), "+f"(d[30]), "+f"(d[31])
    : "l"(desca), "l"(descb), "r"(scale_d));
}

constexpr int K1_XS = 17408;
constexpr int K1_WS = 24576;
constexpr int K1_ST = K1_XS + K1_WS;
constexpr int K1_NST = 5;
constexpr int K1_OFF_MISC = K1_NST * K1_ST;
constexpr int K1_SMEM = K1_OFF_MISC + 2048 + 1024;
constexpr float QSCALE = 0.25f * 1.4426950408889634f;

__global__ void __launch_bounds__(544, 1)
k1_qkv(const __grid_constant__ CUtensorMap tm_x, const __grid_constant__ CUtensorMap tm_w, const __nv_bfloat16* __restrict__ x) {
    extern __shared__ uint8_t smem_raw[];
    const uint32_t sraw = smem_u32(smem_raw);
    const uint32_t sb = (sraw + 1023) & ~1023u;
    uint8_t* sp = smem_raw + (sb - sraw);
    const uint32_t full = sb + K1_OFF_MISC;
    const uint32_t empty = full + 64;
    float* s_m = (float*)(sp + K1_OFF_MISC + 256);
    float* s_r = s_m + 128;

    const int tid = threadIdx.x, warp = tid >> 5, lane = tid & 31;
    const int mt = blockIdx.x >> 3, nt = blockIdx.x & 7;
    if (tid == 0) TSTAMP0(0, 0);
    pdl_launch();
    if (tid == 0) {
        for (int i = 0; i < K1_NST; i++) { mbar_init(full + 8 * i, 1); mbar_init(empty + 8 * i, 3); }
        fence_barrier_init();
    }
    if (tid < K1_NST * 64) {
        *(uint4*)(sp + (tid >> 6) * K1_ST + 16384 + (tid & 63) * 16) =
            make_uint4(0x3F803F80u, 0x3F803F80u, 0x3F803F80u, 0x3F803F80u);
    }
    fence_proxy_async();
    __syncthreads();

    if (warp == 16) {
        if (lane == 0) {
            for (int kb = 0; kb < 8; kb++) {
                const int s = kb % K1_NST;
                if (kb >= K1_NST) mbar_wait(empty + 8 * s, 0);
                mbar_expect_tx(full + 8 * s, 16384 + K1_WS);
                tma_load_2d(sb + s * K1_ST, &tm_x, kb * 64, mt * 128, full + 8 * s);
                tma_load_3d(sb + s * K1_ST + K1_XS, &tm_w, nt * 64, kb * 64, 0, full + 8 * s);
            }
        } else if (lane == 1) {
            if (blockIdx.x == 0) g_cnt = 0;
        }
        if (blockIdx.x == 0) for (int i = lane; i < 2 * DM; i += 32) g_y[i] = 0.f;
        for (int i = lane; i < 128; i += 32) g_part[blockIdx.x * 128 + i] = make_float4(0.f, 0.f, 0.f, 0.f);
        if (blockIdx.x == 1) { g_cand[lane] = make_uint4(0, 0, 0, 0); g_cand[lane + 32] = make_uint4(0, 0, 0, 0); g_oflag[lane * 32] = 0; g_hflag[lane] = 0; }
    } else if (warp >= 12) {
        const int r = tid - 384;
        const unsigned int tag = *(volatile unsigned int*)&g_epoch + 1u;
        {
            const int row = mt * 128 + nt * 16 + (r >> 3);
            const uint4* xp = (const uint4*)(x + (size_t)row * DM) + (r & 7);
            uint4 v[8];
#pragma unroll
            for (int i = 0; i < 8; i++) v[i] = __ldg(xp + i * 8);
            float s1 = 0.f;
#pragma unroll
            for (int i = 0; i < 8; i++)
                s1 += ((bf_lo(v[i].x) + bf_hi(v[i].x)) + (bf_lo(v[i].y) + bf_hi(v[i].y))) + ((bf_lo(v[i].z) + bf_hi(v[i].z)) + (bf_lo(v[i].w) + bf_hi(v[i].w)));
#pragma unroll
            for (int o = 1; o < 8; o <<= 1) s1 += __shfl_xor_sync(0xffffffffu, s1, o);
            const float mean = s1 * (1.f / DM);
            float q0 = 0.f, q1 = 0.f;
#pragma unroll
            for (int i = 0; i < 8; i++) {
                const uint32_t w[4] = {v[i].x, v[i].y, v[i].z, v[i].w};
#pragma unroll
                for (int j = 0; j < 4; j++) {
                    const float a = bf_lo(w[j]) - mean, b = bf_hi(w[j]) - mean;
                    q0 = fmaf(a, a, q0); q1 = fmaf(b, b, q1);
                }
            }
            float q = q0 + q1;
#pragma unroll
            for (int o = 1; o < 8; o <<= 1) q += __shfl_xor_sync(0xffffffffu, q, o);
            const float den = rbf(sqrtf(rbf(rbf(q * (1.f / DM)) + 1e-5f)));
            if ((r & 7) == 0)
                asm volatile("st.relaxed.gpu.global.v4.f32 [%0], {%1, %2, %3, %4};" ::"l"(g_ln1 + row), "f"(rbf(mean)), "f"(1.f / den),
                             "f"(__uint_as_float(tag)), "f"(0.f) : "memory");
        }
        if (r == 0) TSTAMP0(0, 6);
        {
            float4 v;
            int spins = 0;
            do {
                asm volatile("ld.relaxed.gpu.global.v4.f32 {%0, %1, %2, %3}, [%4];" : "=f"(v.x), "=f"(v.y), "=f"(v.z), "=f"(v.w) : "l"(g_ln1 + mt * 128 + r) : "memory");
            } while (__float_as_uint(v.z) != tag && ++spins < (1 << 22));
            s_m[r] = v.x;
            s_r[r] = v.y;
        }
        if (r == 0) TSTAMP0(0, 7);
        named_arrive(1, 512);
    } else {
        const int part = warp >> 2, hw = warp & 3;
        float acc[68];
#pragma unroll
        for (int i = 0; i < 68; i++) acc[i] = 0.f;
        fence_regs(acc);
#pragma unroll 1
        for (int kb = 0; kb < 8; kb++) {
            const int s = kb % K1_NST;
            mbar_wait(full + 8 * s, (kb / K1_NST) & 1);
            const uint64_t da = make_desc(sb + s * K1_ST + K1_XS + part * 8192, 1024, 1024, 1);
            const uint64_t db = make_desc(sb + s * K1_ST, 16, 1024, 1);
            wg_fence();
#pragma unroll
            for (int k = 0; k < 4; k++) wgmma_k1_n136(acc, da + k * 128, db + k * 2, (kb | k) != 0);
            wg_commit();
            if (kb > 0 && kb <= 8 - K1_NST) {
                wg_wait<1>();
                if ((tid & 127) == 0) mbar_arrive(empty + 8 * (kb - 1));
            }
        }
        wg_wait<0>();
        fence_regs(acc);
        if (tid == 0) TSTAMP0(0, 1);
        named_sync(1, 512);
        if (tid == 0) TSTAMP0(0, 2);

        const int t = lane & 3;
        const float cs0 = acc[64], cs1 = acc[66];
        const float sc = (part == 0) ? QSCALE : 1.f;
        const uint32_t stg = sb + (hw >> 1) * K1_ST + K1_XS + part * 8192 + (hw & 1) * 4096;
        const uint32_t st_addr = stg + ((lane >> 3) & 1) * 2048 + ((lane >> 4) * 8 + (lane & 7)) * 16;
#pragma unroll
        for (int j = 0; j < 16; j += 2) {
            uint32_t rr[4];
#pragma unroll
            for (int u = 0; u < 2; u++) {
                const int jj = j + u;
                const float2 m2 = *(const float2*)(s_m + 8 * jj + 2 * t);
                const float2 r2 = *(const float2*)(s_r + 8 * jj + 2 * t);
                const float ra = r2.x * sc, rb = r2.y * sc;
                rr[2 * u] = pack_bf16((acc[4 * jj] - m2.x * cs0) * ra, (acc[4 * jj + 1] - m2.y * cs0) * rb);
                rr[2 * u + 1] = pack_bf16((acc[4 * jj + 2] - m2.x * cs1) * ra, (acc[4 * jj + 3] - m2.y * cs1) * rb);
            }
            stmatrix_x4_trans(st_addr + j * 128, rr[0], rr[1], rr[2], rr[3]);
        }
        __syncwarp();
        if (tid == 0) TSTAMP0(0, 4);
        float nmax = 0.f;
#pragma unroll
        for (int i = 0; i < 4; i++) {
            const int tok = lane + 32 * i;
            const uint4 a = *(const uint4*)(sp + (stg - sb) + tok * 16);
            const uint4 b = *(const uint4*)(sp + (stg - sb) + 2048 + tok * 16);
            const uint32_t w[8] = {a.x, a.y, a.z, a.w, b.x, b.y, b.z, b.w};
            float n2 = 0.f;
#pragma unroll
            for (int q = 0; q < 8; q++) {
                const float lo = bf_lo(w[q]), hi = bf_hi(w[q]);
                n2 = fmaf(lo, lo, n2); n2 = fmaf(hi, hi, n2);
            }
            nmax = (n2 > nmax || n2 != n2) ? n2 : nmax;
        }
#pragma unroll
        for (int o = 16; o > 0; o >>= 1) {
            const float v = __shfl_xor_sync(0xffffffffu, nmax, o);
            nmax = (v > nmax || v != v) ? v : nmax;
        }
        if (tid == 0) TSTAMP0(0, 5);
        fence_proxy_async();
        __syncwarp();
        if (lane == 0) {
            const int head = nt * 4 + hw;
            g_norm[(mt * NH + head) * 3 + part] = nmax;
            uint8_t* dst;
            uint32_t hstride;
            if (part == 0) { dst = g_q + (size_t)head * 65536 + mt * 2048; hstride = 32768; }
            else { dst = g_kv + (size_t)head * 131072 + (mt >> 1) * 16384 + (part - 1) * 8192 + (mt & 1) * 2048; hstride = 4096; }
            bulk_s2g(dst, stg, 2048);
            bulk_s2g(dst + hstride, stg + 2048, 2048);
            asm volatile("cp.async.bulk.commit_group;" ::: "memory");
            asm volatile("cp.async.bulk.wait_group.read 0;" ::: "memory");
            if (tid == 0) TSTAMP0(0, 3);
        }
    }
}

constexpr int KF_CH_G = 16384, KF_CH_S = 20480, KF_NCH = 8;
constexpr int KF_OFF_WO = KF_NCH * KF_CH_S;
constexpr int KF_OFF_MISC = KF_OFF_WO + 65536;
constexpr int KF_SMEM = KF_OFF_MISC + 1280 + 1024;

__device__ __forceinline__ uint32_t exp2_pair_poly(float s0, float s1) {
    const float KB = 65536.0f + 127.0f;
    const float t0 = s0 + KB, t1 = s1 + KB;
    const uint32_t w = __byte_perm(__float_as_uint(t0), __float_as_uint(t1), 0x5410);
    uint32_t z;
    asm("lop3.b32 %0, %1, %2, %3, 0xEA;" : "=r"(z) : "r"(w), "r"(0x007F007Fu), "r"(0x3F803F80u));
    uint32_t p = fma_bf16x2(0x3eab3eabu, z, 0xbc73bc73u);
    p = fma_bf16x2(p, z, 0x3f2f3f2fu);
    return p + w - z;
}
constexpr uint32_t KF_EMASK = 0x5757u;
template <int LO, int HI>
__device__ __forceinline__ void softmax_part(const float (&s)[32], uint32_t (&p)[16]) {
#pragma unroll
    for (int i = LO; i < HI; i++) {
        if ((KF_EMASK >> i) & 1) p[i] = exp2_pair_poly(s[2 * i], s[2 * i + 1]);
        else p[i] = pack_bf16(ex2f(s[2 * i]), ex2f(s[2 * i + 1]));
    }
}
#define KF_PV(P, OFF)                                                                              \
    _Pragma("unroll") for (int kk = 0; kk < 4; kk++)                                               \
        wgmma_pv_n24(o, P[4 * kk], P[4 * kk + 1], P[4 * kk + 2], P[4 * kk + 3], dv + ((OFF) + kk * 16));

__device__ __forceinline__ unsigned long long cand_key(const uint4& c) {
    return ((unsigned long long)c.x << 32) | (uint32_t)(0x7FFFFFFF - (int)c.y);
}
__device__ __forceinline__ uint32_t order_bits(float v) {
    const uint32_t u = __float_as_uint(v);
    return (u & 0x80000000u) ? ~u : (u | 0x80000000u);
}
__device__ __forceinline__ float order_value(uint32_t u) {
    return __uint_as_float((u & 0x80000000u) ? (u & 0x7FFFFFFFu) : ~u);
}
__device__ __forceinline__ void warp_top2(unsigned long long& a, unsigned long long& b) {
#pragma unroll
    for (int o = 16; o > 0; o >>= 1) {
        const unsigned long long c = __shfl_xor_sync(0xffffffffu, a, o);
        const unsigned long long d = __shfl_xor_sync(0xffffffffu, b, o);
        const unsigned long long hi = a > c ? a : c, lo = a > c ? c : a;
        const unsigned long long m = b > d ? b : d;
        a = hi;
        b = lo > m ? lo : m;
    }
}
__device__ __forceinline__ unsigned int ld_acquire(const unsigned int* p) {
    unsigned int v; asm volatile("ld.acquire.gpu.global.u32 %0, [%1];" : "=r"(v) : "l"(p) : "memory"); return v;
}
__device__ __forceinline__ void red_release_add(unsigned int* p) {
    asm volatile("red.release.gpu.global.add.u32 [%0], 1;" ::"l"(p) : "memory");
}

__global__ void __launch_bounds__(512, 1)
kf_main(const __grid_constant__ CUtensorMap tm_o, const __grid_constant__ CUtensorMap tm_wo,
        const __nv_bfloat16* __restrict__ x, const __nv_bfloat16* __restrict__ wo, const __nv_bfloat16* __restrict__ w_r,
        const __nv_bfloat16* __restrict__ w_gate, const __nv_bfloat16* __restrict__ w_up, const __nv_bfloat16* __restrict__ w_down,
        __nv_bfloat16* __restrict__ out) {
    extern __shared__ uint8_t smem_raw[];
    const uint32_t sraw = smem_u32(smem_raw);
    const uint32_t sb = (sraw + 1023) & ~1023u;
    uint8_t* sp = smem_raw + (sb - sraw);
    const uint32_t kvbar = sb + KF_OFF_MISC;
    const uint32_t wbar = kvbar + 64;
    const uint32_t obar = wbar + 64;
    unsigned int* s_cnt = (unsigned int*)(sp + KF_OFF_MISC + 192);
    unsigned long long* s_key = (unsigned long long*)(sp + KF_OFF_MISC + 256);
    float* s_gu = (float*)(sp + KF_OFF_MISC + 768);
    uint4* s_sel = (uint4*)(sp + KF_OFF_MISC + 1024);
    const int tid = threadIdx.x;
    const int head = blockIdx.x >> 2, quarter = blockIdx.x & 3;
    const int mt = blockIdx.x >> 2, nt = blockIdx.x & 3;
    if (tid == 0) TSTAMP0(1, 0);
    if (tid == 0) {
        for (int c = 0; c < 20; c++) mbar_init(kvbar + 8 * c, 1);
        for (int c = 0; c < 4; c++) s_cnt[c] = 0;
        fence_barrier_init();
        for (int kb = 0; kb < 4; kb++) {
            mbar_expect_tx(wbar + 8 * kb, 16384);
            tma_load_3d(sb + KF_OFF_WO + kb * 16384, &tm_wo, 0, kb * 64, nt * 2, wbar + 8 * kb);
        }
    }
    if (tid == 32) {
        prefetch_l2((const uint8_t*)wo + blockIdx.x * 4096, 4096);
        prefetch_l2((const uint8_t*)w_gate + blockIdx.x * 14336, 14336);
        prefetch_l2((const uint8_t*)w_up + blockIdx.x * 14336, 14336);
        prefetch_l2((const uint8_t*)w_down + blockIdx.x * 14336, 14336);
    }
    for (int i = tid; i < KF_NCH * 256; i += 512)
        *(uint4*)(sp + (i >> 8) * KF_CH_S + 16384 + (i & 255) * 16) =
            make_uint4(0x3F803F80u, 0x3F803F80u, 0x3F803F80u, 0x3F803F80u);
    fence_proxy_async();
    __syncthreads();
    pdl_wait();
    if (tid == 0) TSTAMP0(1, 1);
    if (tid == 0) {
        const uint8_t* src = g_kv + (size_t)head * (KF_NCH * KF_CH_G);
        for (int c = 0; c < KF_NCH; c++) {
            mbar_expect_tx(kvbar + 8 * c, KF_CH_G);
            bulk_g2s(sb + c * KF_CH_S, src + c * KF_CH_G, KF_CH_G, kvbar + 8 * c);
        }
    }
    const int wg = tid >> 7, warp = (tid >> 5) & 3, lane = tid & 31, g = lane >> 2, t = lane & 3;

    bool fast;
    {
        const int m16 = lane & 15;
        float kn = g_norm[(m16 * NH + head) * 3 + 1];
        float vn = g_norm[(m16 * NH + head) * 3 + 2];
        float qn = g_norm[((quarter * 4 + (lane & 3)) * NH + head) * 3 + 0];
        bool bad = !(kn < 1e30f) || !(vn < 1e30f) || !(qn < 1e30f);
#pragma unroll
        for (int o = 8; o > 0; o >>= 1) {
            kn = fmaxf(kn, __shfl_xor_sync(0xffffffffu, kn, o));
            qn = fmaxf(qn, __shfl_xor_sync(0xffffffffu, qn, o));
        }
        bad = __any_sync(0xffffffffu, bad);
        fast = !bad && (qn * kn <= 3500.f);
    }
    const uint64_t dk0 = make_desc(sb, 4096, 128, 0);
    const uint64_t dv0 = make_desc(sb + 8192, 128, 4096, 0);

#pragma unroll 1
    for (int pass = 0; pass < 2; pass++) {
        const int row0 = quarter * 512 + pass * 256 + wg * 64 + warp * 16 + g;
        uint32_t qa[4];
        {
            const uint8_t* qb = g_q + (size_t)head * 65536 + row0 * 16 + t * 4;
            qa[0] = *(const uint32_t*)(qb);
            qa[1] = *(const uint32_t*)(qb + 128);
            qa[2] = *(const uint32_t*)(qb + 32768);
            qa[3] = *(const uint32_t*)(qb + 32768 + 128);
        }
        float o[12];
#pragma unroll
        for (int i = 0; i < 12; i++) o[i] = 0.f;
        fence_regs(o);
#define KF_RELEASE_CHUNK(c)                                                                          \
        if (pass == 1 && (c) >= 1 && (c) <= 4) {                                                     \
            named_sync(4 + wg, 128);            \
            if ((tid & 127) == 0 && atomicAdd(&s_cnt[(c) - 1], 1u) == 3u) {                          \
                mbar_expect_tx(wbar + 8 * (3 + (c)), 16384);                                         \
                tma_load_3d(sb + ((c) - 1) * KF_CH_S, &tm_wo, 0, (3 + (c)) * 64, nt * 2, wbar + 8 * (3 + (c))); \
            }                                                                                        \
        }
        if (fast) {
#pragma unroll 1
            for (int c = 0; c < KF_NCH; c++) {
                const uint64_t dk = dk0 + (uint64_t)(c * (KF_CH_S >> 4));
                const uint64_t dv = dv0 + (uint64_t)(c * (KF_CH_S >> 4));
                float s0[32], s1[32], s2[32], s3[32];
                uint32_t p0[16], p1[16], p2[16], p3[16];
                mbar_wait(kvbar + 8 * c, 0);
                wg_wait<1>();
                wg_fence();
                wgmma_qk_n64(s0, qa[0], qa[1], qa[2], qa[3], dk);
                wg_commit();
                wg_wait<1>();
                KF_RELEASE_CHUNK(c);
                wg_fence();
                wgmma_qk_n64(s1, qa[0], qa[1], qa[2], qa[3], dk + 64);
                wg_commit();
                wg_wait<1>();
                fence_regs(s0);
                softmax_part<0, 16>(s0, p0);
                wg_fence();
                KF_PV(p0, 0);
                wg_commit();
                wg_wait<1>();
                fence_regs(s1);
                softmax_part<0, 8>(s1, p1);
                wg_wait<0>();
                wg_fence();
                wgmma_qk_n64(s2, qa[0], qa[1], qa[2], qa[3], dk + 128);
                wg_commit();
                softmax_part<8, 16>(s1, p1);
                wg_fence();
                KF_PV(p1, 64);
                wg_commit();
                wg_wait<1>();
                fence_regs(s2);
                softmax_part<0, 8>(s2, p2);
                wg_wait<0>();
                wg_fence();
                wgmma_qk_n64(s3, qa[0], qa[1], qa[2], qa[3], dk + 192);
                wg_commit();
                softmax_part<8, 16>(s2, p2);
                wg_fence();
                KF_PV(p2, 128);
                wg_commit();
                wg_wait<1>();
                fence_regs(s3);
                softmax_part<0, 16>(s3, p3);
                wg_fence();
                KF_PV(p3, 192);
                wg_commit();
            }
            wg_wait<0>();
            fence_regs(o);
        } else {
            float m0 = -INFINITY, m1 = -INFINITY;
#pragma unroll 1
            for (int b = 0; b < 32; b++) {
                const int c = b >> 2;
                const uint64_t dk = dk0 + (uint64_t)(c * (KF_CH_S >> 4) + (b & 3) * 64);
                const uint64_t dv = dv0 + (uint64_t)(c * (KF_CH_S >> 4) + (b & 3) * 64);
                float s[32];
                uint32_t p[16];
                mbar_wait(kvbar + 8 * c, 0);
                wg_fence();
                wgmma_qk_n64(s, qa[0], qa[1], qa[2], qa[3], dk);
                wg_commit();
                if ((b & 3) == 0) { KF_RELEASE_CHUNK(c); }
                wg_wait<0>();
                fence_regs(s);
                float x0 = s[0], x1 = s[2];
#pragma unroll
                for (int j = 0; j < 8; j++) {
                    x0 = fmaxf(x0, fmaxf(s[4 * j], s[4 * j + 1]));
                    x1 = fmaxf(x1, fmaxf(s[4 * j + 2], s[4 * j + 3]));
                }
                x0 = fmaxf(x0, __shfl_xor_sync(0xffffffffu, x0, 1));
                x0 = fmaxf(x0, __shfl_xor_sync(0xffffffffu, x0, 2));
                x1 = fmaxf(x1, __shfl_xor_sync(0xffffffffu, x1, 1));
                x1 = fmaxf(x1, __shfl_xor_sync(0xffffffffu, x1, 2));
                const float n0 = fmaxf(m0, x0), n1 = fmaxf(m1, x1);
                const float c0 = ex2f(m0 - n0), c1 = ex2f(m1 - n1);
                m0 = n0; m1 = n1;
#pragma unroll
                for (int j = 0; j < 3; j++) {
                    o[4 * j] *= c0; o[4 * j + 1] *= c0; o[4 * j + 2] *= c1; o[4 * j + 3] *= c1;
                }
#pragma unroll
                for (int j = 0; j < 8; j++) {
                    p[2 * j] = pack_bf16(ex2f(s[4 * j] - n0), ex2f(s[4 * j + 1] - n0));
                    p[2 * j + 1] = pack_bf16(ex2f(s[4 * j + 2] - n1), ex2f(s[4 * j + 3] - n1));
                }
                fence_regs(o);
                wg_fence();
                KF_PV(p, 0);
                wg_commit();
                wg_wait<0>();
                fence_regs(o);
            }
        }
        const float inv0 = 1.f / o[8], inv1 = 1.f / o[10];
        uint32_t* out0 = (uint32_t*)(g_o + (size_t)row0 * DM + head * 16);
        uint32_t* out1 = (uint32_t*)(g_o + (size_t)(row0 + 8) * DM + head * 16);
        out0[t] = pack_bf16(o[0] * inv0, o[1] * inv0);
        out0[4 + t] = pack_bf16(o[4] * inv0, o[5] * inv0);
        out1[t] = pack_bf16(o[2] * inv1, o[3] * inv1);
        out1[4 + t] = pack_bf16(o[6] * inv1, o[7] * inv1);
        named_sync(4 + wg, 128);
        if ((tid & 127) == 0) red_release_add(&g_oflag[(quarter * 8 + pass * 4 + wg) * 32]);
        if (tid == 0) TSTAMP0(1, 2 + pass);
    }

    if (wg < 2) {
        const int wi = warp;
        const int r0 = mt * 64 + wi * 16 + g;
        const int cb = nt * 128 + wg * 64;
        uint32_t xr[16], wr[8];
#pragma unroll
        for (int j = 0; j < 8; j++) {
            xr[2 * j] = __ldg((const uint32_t*)(x + (size_t)r0 * DM + cb + 8 * j + 2 * t));
            xr[2 * j + 1] = __ldg((const uint32_t*)(x + (size_t)(r0 + 8) * DM + cb + 8 * j + 2 * t));
            wr[j] = __ldg((const uint32_t*)(w_r + cb + 8 * j + 2 * t));
        }
        if (tid == 0) {
            int spins = 0;
            while (ld_acquire(&g_oflag[mt * 32]) < 32u && ++spins < (1 << 20)) __nanosleep(64);
        }
        named_sync(1, 512);
        if (tid == 0) {
            asm volatile("fence.proxy.async;" ::: "memory");
            TSTAMP0(2, 1);
            for (int k2 = 0; k2 < 4; k2++) {
                mbar_expect_tx(obar + 8 * k2, 16384);
                tma_load_3d(sb + (4 + k2) * KF_CH_S, &tm_o, 0, mt * 64, k2 * 2, obar + 8 * k2);
            }
        }
        float wsum = 0.f;
        {
            const uint4 a = __ldg((const uint4*)(w_r + lane * 16)), b = __ldg((const uint4*)(w_r + lane * 16 + 8));
            const uint32_t w[8] = {a.x, a.y, a.z, a.w, b.x, b.y, b.z, b.w};
#pragma unroll
            for (int i = 0; i < 8; i++) wsum += bf_lo(w[i]) + bf_hi(w[i]);
#pragma unroll
            for (int o = 16; o > 0; o >>= 1) wsum += __shfl_xor_sync(0xffffffffu, wsum, o);
        }
        float acc[32];
#pragma unroll
        for (int i = 0; i < 32; i++) acc[i] = 0.f;
        fence_regs(acc);
#pragma unroll 1
        for (int kb = 0; kb < 8; kb++) {
            mbar_wait(wbar + 8 * kb, 0);
            mbar_wait(obar + 8 * (kb >> 1), 0);
            const uint32_t wa = (kb < 4) ? (KF_OFF_WO + kb * 16384) : ((kb - 4) * KF_CH_S);
            const uint64_t da = make_desc(sb + (4 + (kb >> 1)) * KF_CH_S + (kb & 1) * 8192, 16, 1024, 1);
            const uint64_t db = make_desc(sb + wa + wg * 8192, 1024, 1024, 1);
            wg_fence();
#pragma unroll
            for (int k = 0; k < 4; k++) wgmma_k3_n64(acc, da + k * 2, db + k * 128, (kb | k) != 0);
            wg_commit();
        }
        wg_wait<0>();
        fence_regs(acc);
        if (tid == 0) TSTAMP0(2, 2);
        float hv[32];
        float s0 = 0.f, s1 = 0.f, d0 = 0.f, d1 = 0.f;
#pragma unroll
        for (int j = 0; j < 8; j++) {
            hv[4 * j] = rbf(bf_lo(xr[2 * j]) + rbf(acc[4 * j]));
            hv[4 * j + 1] = rbf(bf_hi(xr[2 * j]) + rbf(acc[4 * j + 1]));
            hv[4 * j + 2] = rbf(bf_lo(xr[2 * j + 1]) + rbf(acc[4 * j + 2]));
            hv[4 * j + 3] = rbf(bf_hi(xr[2 * j + 1]) + rbf(acc[4 * j + 3]));
            const float wl = bf_lo(wr[j]), wh = bf_hi(wr[j]);
            s0 += hv[4 * j] + hv[4 * j + 1];
            s1 += hv[4 * j + 2] + hv[4 * j + 3];
            d0 = fmaf(hv[4 * j], wl, fmaf(hv[4 * j + 1], wh, d0));
            d1 = fmaf(hv[4 * j + 2], wl, fmaf(hv[4 * j + 3], wh, d1));
        }
#pragma unroll
        for (int o = 1; o < 4; o <<= 1) {
            s0 += __shfl_xor_sync(0xffffffffu, s0, o);
            s1 += __shfl_xor_sync(0xffffffffu, s1, o);
            d0 += __shfl_xor_sync(0xffffffffu, d0, o);
            d1 += __shfl_xor_sync(0xffffffffu, d1, o);
        }
        const float mu0 = s0 * (1.f / 64), mu1 = s1 * (1.f / 64);
        float q0 = 0.f, q1 = 0.f;
#pragma unroll
        for (int j = 0; j < 8; j++) {
            float a = hv[4 * j] - mu0, b = hv[4 * j + 1] - mu0, c = hv[4 * j + 2] - mu1, d = hv[4 * j + 3] - mu1;
            q0 = fmaf(a, a, fmaf(b, b, q0));
            q1 = fmaf(c, c, fmaf(d, d, q1));
        }
#pragma unroll
        for (int o = 1; o < 4; o <<= 1) {
            q0 += __shfl_xor_sync(0xffffffffu, q0, o);
            q1 += __shfl_xor_sync(0xffffffffu, q1, o);
        }
        float4* part = g_part + (size_t)mt * 512 + wi * 16 + g;
        if (t < 2) {
            float4* dst = part + (nt * 2 + wg) * 64 + t * 8;
            const float a = t ? mu1 : mu0, b = t ? q1 : q0, c = t ? d1 : d0;
            asm volatile("st.relaxed.gpu.global.v4.f32 [%0], {%1, %2, %3, %4};" ::"l"(dst), "f"(a), "f"(b), "f"(c), "f"(1.0f) : "memory");
        }
        const uint32_t stg_off = KF_OFF_WO + (wi >> 1) * 16384 + wg * 8192 + (wi & 1) * 4096;
        const uint32_t stg_o = sb + stg_off, stg_h = stg_o + 2048;
        const int srow = (lane & 7) + ((lane >> 3) & 1) * 8;
        const int sj = lane >> 4;
        named_sync(4 + wg, 128);
#pragma unroll
        for (int j = 0; j < 8; j += 2) {
            const uint32_t off = srow * 128 + (((j + sj) ^ (srow & 7)) << 4);
            stmatrix_x4(stg_h + off, pack_bf16(hv[4 * j], hv[4 * j + 1]), pack_bf16(hv[4 * j + 2], hv[4 * j + 3]),
                        pack_bf16(hv[4 * j + 4], hv[4 * j + 5]), pack_bf16(hv[4 * j + 6], hv[4 * j + 7]));
        }
        __syncwarp();
#pragma unroll
        for (int i = 0; i < 4; i++) {
            const int row = i * 4 + (lane >> 3), ch = lane & 7;
            const uint4 vh = *(const uint4*)(sp + stg_off + 2048 + row * 128 + ((ch ^ (row & 7)) << 4));
            *(uint4*)(g_h + (size_t)(mt * 64 + wi * 16 + row) * DM + cb + ch * 8) = vh;
        }
        named_sync(4 + wg, 128);
        if ((tid & 127) == 0) red_release_add(&g_hflag[mt]);
        float mean[2], den[2], rr[2];
        {
            float4 v[4];
            int spins = 0;
            while (true) {
#pragma unroll
                for (int i = 0; i < 4; i++) {
                    const float4* p = part + (t + (i & 1) * 4) * 64 + (i >> 1) * 8;
                    asm volatile("ld.relaxed.gpu.global.v4.f32 {%0, %1, %2, %3}, [%4];" : "=f"(v[i].x), "=f"(v[i].y), "=f"(v[i].z), "=f"(v[i].w) : "l"(p) : "memory");
                }
                const bool ok = (v[0].w != 0.f) && (v[1].w != 0.f) && (v[2].w != 0.f) && (v[3].w != 0.f);
                if (__all_sync(0xffffffffu, ok) || ++spins > (1 << 20)) break;
                __nanosleep(40);
            }
#pragma unroll
            for (int u = 0; u < 2; u++) {
                float mu = v[2 * u].x + v[2 * u + 1].x, m2 = v[2 * u].y + v[2 * u + 1].y, hw = v[2 * u].z + v[2 * u + 1].z;
#pragma unroll
                for (int o = 1; o < 4; o <<= 1) {
                    mu += __shfl_xor_sync(0xffffffffu, mu, o);
                    m2 += __shfl_xor_sync(0xffffffffu, m2, o);
                    hw += __shfl_xor_sync(0xffffffffu, hw, o);
                }
                mu *= 0.125f;
                const float da = v[2 * u].x - mu, db = v[2 * u + 1].x - mu;
                float dd = 64.f * (da * da + db * db);
#pragma unroll
                for (int o = 1; o < 4; o <<= 1) dd += __shfl_xor_sync(0xffffffffu, dd, o);
                m2 += dd;
                mean[u] = rbf(mu);
                den[u] = rbf(sqrtf(rbf(rbf(m2 * (1.f / DM)) + 1e-5f)));
                rr[u] = rbf((hw - mean[u] * wsum) / den[u]);
            }
        }
        if (tid == 0) TSTAMP0(2, 3);
        named_arrive(3, 512);
        if (nt == 0 && wg == 0) {
            float2* s_st = (float2*)(sp + KF_OFF_WO + 49152);
            if (t == 0) {
                s_key[wi * 16 + g] = ((unsigned long long)order_bits(rr[0]) << 32) | (uint32_t)(0x7FFFFFFF - (r0 + 1));
                s_key[wi * 16 + g + 8] = ((unsigned long long)order_bits(rr[1]) << 32) | (uint32_t)(0x7FFFFFFF - (r0 + 9));
                s_st[wi * 16 + g] = make_float2(mean[0], den[0]);
                s_st[wi * 16 + g + 8] = make_float2(mean[1], den[1]);
            }
            named_sync(4, 128);
            if (warp == 0) {
                unsigned long long a = s_key[lane], b = s_key[lane + 32];
                if (b > a) { const unsigned long long c = a; a = b; b = c; }
                warp_top2(a, b);
                if (lane < 2) {
                    const unsigned long long k = lane ? b : a;
                    const int tok1 = 0x7FFFFFFF - (int)(uint32_t)k;
                    const float2 st = s_st[(tok1 - 1) & 63];
                    asm volatile("st.relaxed.gpu.global.v4.u32 [%0], {%1, %2, %3, %4};" ::"l"(g_cand + mt * 2 + lane), "r"((uint32_t)(k >> 32)),
                                 "r"((uint32_t)tok1), "r"(__float_as_uint(st.x)), "r"(__float_as_uint(st.y)) : "memory");
                }
            }
        }
        const float i0 = 1.f / den[0], i1 = 1.f / den[1];
#pragma unroll
        for (int j = 0; j < 8; j += 2) {
            uint32_t ro[4];
#pragma unroll
            for (int u = 0; u < 2; u++) {
                const int jj = j + u;
                const float a = hv[4 * jj], b = hv[4 * jj + 1], c = hv[4 * jj + 2], d = hv[4 * jj + 3];
                const float na = rbf(rbf(a - mean[0]) * i0), nb = rbf(rbf(b - mean[0]) * i0);
                const float nc = rbf(rbf(c - mean[1]) * i1), nd = rbf(rbf(d - mean[1]) * i1);
                ro[2 * u] = pack_bf16(a + na, b + nb);
                ro[2 * u + 1] = pack_bf16(c + nc, d + nd);
            }
            const uint32_t off = srow * 128 + (((j + sj) ^ (srow & 7)) << 4);
            stmatrix_x4(stg_o + off, ro[0], ro[1], ro[2], ro[3]);
        }
        __syncwarp();
#pragma unroll
        for (int i = 0; i < 4; i++) {
            const int row = i * 4 + (lane >> 3), ch = lane & 7;
            const uint4 vo = *(const uint4*)(sp + stg_off + row * 128 + ((ch ^ (row & 7)) << 4));
            *(uint4*)(out + (size_t)(mt * 64 + wi * 16 + row) * DM + cb + ch * 8) = vo;
        }
        named_sync(4 + wg, 128);
        if ((tid & 127) == 0) red_release_add(&g_cnt);
        if (tid == 0) TSTAMP0(2, 4);
    } else {
        named_arrive(1, 512);
        const bool worker = blockIdx.x < FF / 16;
        const bool finisher = blockIdx.x == gridDim.x - 1;
        if (!worker && !finisher) { named_arrive(3, 512); return; }
        const int mtid = tid - 256, mwarp = mtid >> 5;
        const int f0 = blockIdx.x * 16;
        uint2 wgu[16];
        uint32_t wd[16];
        if (worker) {
            const __nv_bfloat16* base = (mwarp < 4 ? w_gate : w_up) + (size_t)(16 * lane) * FF + f0 + (mwarp & 3) * 4;
#pragma unroll
            for (int k = 0; k < 16; k++) wgu[k] = __ldg((const uint2*)(base + (size_t)k * FF));
#pragma unroll
            for (int f = 0; f < 16; f++) wd[f] = __ldg((const uint32_t*)(w_down + (size_t)(f0 + f) * DM + 2 * mtid));
        }
        if (mtid == 0) TSTAMP0(3, 0);
        named_sync(3, 512);
        if (mwarp == 0) {
            uint4 ca, cb4;
            int spins = 0;
            while (true) {
                asm volatile("ld.relaxed.gpu.global.v4.u32 {%0, %1, %2, %3}, [%4];" : "=r"(ca.x), "=r"(ca.y), "=r"(ca.z), "=r"(ca.w) : "l"(g_cand + 2 * lane) : "memory");
                asm volatile("ld.relaxed.gpu.global.v4.u32 {%0, %1, %2, %3}, [%4];" : "=r"(cb4.x), "=r"(cb4.y), "=r"(cb4.z), "=r"(cb4.w) : "l"(g_cand + 2 * lane + 1) : "memory");
                const unsigned int hf = ld_acquire(&g_hflag[lane]);
                const bool ok = ca.y != 0 && cb4.y != 0 && hf >= 8u;
                if (__all_sync(0xffffffffu, ok) || ++spins > (1 << 20)) break;
                __nanosleep(40);
            }
            unsigned long long ka = cand_key(ca), kb = cand_key(cb4);
            const unsigned long long mya = ka, myb = kb;
            warp_top2(ka, kb);
            if (mya == ka) s_sel[0] = ca;
            if (myb == ka) s_sel[0] = cb4;
            if (mya == kb) s_sel[1] = ca;
            if (myb == kb) s_sel[1] = cb4;
        }
        named_sync(2, 256);
        if (mtid == 0) TSTAMP0(3, 1);
        int idx[2];
        float mean[2], den[2], rv[2];
#pragma unroll
        for (int u = 0; u < 2; u++) {
            const uint4 c = s_sel[u];
            idx[u] = (int)c.y - 1;
            rv[u] = order_value(c.x);
            mean[u] = __uint_as_float(c.z);
            den[u] = __uint_as_float(c.w);
        }
        float hx[2][2], xo[2][2];
        if (worker) {
            float acc[8];
#pragma unroll
            for (int i = 0; i < 8; i++) acc[i] = 0.f;
            uint4 ha[2], hb[2];
#pragma unroll
            for (int u = 0; u < 2; u++) {
                const uint4* hp = (const uint4*)(g_h + (size_t)idx[u] * DM + 16 * lane);
                ha[u] = __ldcg(hp); hb[u] = __ldcg(hp + 1);
            }
#pragma unroll
            for (int u = 0; u < 2; u++) {
                const float inv = 1.f / den[u];
                const uint32_t hw[8] = {ha[u].x, ha[u].y, ha[u].z, ha[u].w, hb[u].x, hb[u].y, hb[u].z, hb[u].w};
#pragma unroll
                for (int k = 0; k < 8; k++) {
                    const float x0 = rbf(rbf(bf_lo(hw[k]) - mean[u]) * inv), x1 = rbf(rbf(bf_hi(hw[k]) - mean[u]) * inv);
                    const uint2 wa = wgu[2 * k], wb = wgu[2 * k + 1];
                    acc[u * 4 + 0] = fmaf(x0, bf_lo(wa.x), fmaf(x1, bf_lo(wb.x), acc[u * 4 + 0]));
                    acc[u * 4 + 1] = fmaf(x0, bf_hi(wa.x), fmaf(x1, bf_hi(wb.x), acc[u * 4 + 1]));
                    acc[u * 4 + 2] = fmaf(x0, bf_lo(wa.y), fmaf(x1, bf_lo(wb.y), acc[u * 4 + 2]));
                    acc[u * 4 + 3] = fmaf(x0, bf_hi(wa.y), fmaf(x1, bf_hi(wb.y), acc[u * 4 + 3]));
                }
            }
#define KF_STEP(O, N)                                                          \
            {                                                                  \
                const bool up = (lane & (O)) != 0;                             \
                _Pragma("unroll") for (int i = 0; i < (N); i++) {              \
                    const float send = up ? acc[i] : acc[i + (N)];             \
                    const float keep = up ? acc[i + (N)] : acc[i];             \
                    acc[i] = keep + __shfl_xor_sync(0xffffffffu, send, (O));   \
                }                                                              \
            }
            KF_STEP(16, 4) KF_STEP(8, 2) KF_STEP(4, 1)
            acc[0] += __shfl_xor_sync(0xffffffffu, acc[0], 2);
            acc[0] += __shfl_xor_sync(0xffffffffu, acc[0], 1);
            if ((lane & 3) == 0) {
                const int v = ((lane & 16) ? 4 : 0) + ((lane & 8) ? 2 : 0) + ((lane & 4) ? 1 : 0);
                s_gu[(v >> 2) * 32 + mwarp * 4 + (v & 3)] = acc[0];
            }
            named_sync(2, 256);
            float y[2][2] = {{0.f, 0.f}, {0.f, 0.f}};
            {
                const int u = lane >> 4, c = lane & 15;
                const float gb = rbf(s_gu[u * 32 + c]);
                const float sg = rbf(gb / (1.f + __expf(-gb)));
                const float a = rbf(sg * rbf(s_gu[u * 32 + 16 + c]));
#pragma unroll
                for (int f = 0; f < 16; f++) {
                    const float a0 = __shfl_sync(0xffffffffu, a, f), a1 = __shfl_sync(0xffffffffu, a, 16 + f);
                    const float w0 = bf_lo(wd[f]), w1 = bf_hi(wd[f]);
                    y[0][0] = fmaf(a0, w0, y[0][0]); y[0][1] = fmaf(a0, w1, y[0][1]);
                    y[1][0] = fmaf(a1, w0, y[1][0]); y[1][1] = fmaf(a1, w1, y[1][1]);
                }
            }
#pragma unroll
            for (int u = 0; u < 2; u++)
                asm volatile("red.global.add.v2.f32 [%0], {%1, %2};" ::"l"(g_y + u * DM + 2 * mtid), "f"(y[u][0]), "f"(y[u][1]) : "memory");
            if (mtid == 0) TSTAMP0(3, 2);
            named_sync(2, 256);
            if (mtid == 0) red_release_add(&g_cnt);
            if (mtid == 0) TSTAMP0(3, 3);
        } else {
#pragma unroll
            for (int u = 0; u < 2; u++) {
                const uint32_t ho = __ldcg((const uint32_t*)(g_h + (size_t)idx[u] * DM + 2 * mtid));
                const float inv = 1.f / den[u];
                hx[u][0] = bf_lo(ho); hx[u][1] = bf_hi(ho);
                xo[u][0] = rbf(rbf(hx[u][0] - mean[u]) * inv); xo[u][1] = rbf(rbf(hx[u][1] - mean[u]) * inv);
            }
            if (mtid == 0) {
                int spins = 0;
                while (ld_acquire(&g_cnt) < (unsigned)(FF / 16 + 256) && ++spins < (1 << 20)) __nanosleep(40);
            }
            named_sync(2, 256);
#pragma unroll
            for (int u = 0; u < 2; u++) {
                const float2 yy = __ldcg((const float2*)(g_y + u * DM + 2 * mtid));
                const float sig = rbf(1.f / (1.f + __expf(-rv[u])));
                const float o0 = hx[u][0] + rbf(xo[u][0] + rbf(rbf(yy.x) * sig));
                const float o1 = hx[u][1] + rbf(xo[u][1] + rbf(rbf(yy.y) * sig));
                *(uint32_t*)(out + (size_t)idx[u] * DM + 2 * mtid) = pack_bf16(o0, o1);
            }
            if (mtid == 0) g_epoch = g_epoch + 1u;
            if (mtid == 0) TSTAMP0(3, 4);
        }
    }
}

typedef CUresult (*PFN_encodeTiled)(CUtensorMap*, CUtensorMapDataType, cuuint32_t, void*, const cuuint64_t*, const cuuint64_t*,
                                    const cuuint32_t*, const cuuint32_t*, CUtensorMapInterleave, CUtensorMapSwizzle,
                                    CUtensorMapL2promotion, CUtensorMapFloatOOBfill);

void make_map(PFN_encodeTiled enc, CUtensorMap* m, const void* ptr, uint64_t cols, uint64_t rows, uint32_t bcols, uint32_t brows) {
    cuuint64_t dims[2] = {cols, rows};
    cuuint64_t strides[1] = {cols * 2};
    cuuint32_t box[2] = {bcols, brows};
    cuuint32_t es[2] = {1, 1};
    enc(m, CU_TENSOR_MAP_DATA_TYPE_BFLOAT16, 2, const_cast<void*>(ptr), dims, strides, box, es, CU_TENSOR_MAP_INTERLEAVE_NONE,
        CU_TENSOR_MAP_SWIZZLE_128B, CU_TENSOR_MAP_L2_PROMOTION_L2_256B, CU_TENSOR_MAP_FLOAT_OOB_FILL_NONE);
}

void make_map3(PFN_encodeTiled enc, CUtensorMap* m, const void* ptr, uint64_t d0, uint64_t rows, uint64_t d2, uint64_t row_stride_bytes,
               uint64_t d2_stride_bytes, uint32_t b0, uint32_t b1, uint32_t b2) {
    cuuint64_t dims[3] = {d0, rows, d2};
    cuuint64_t strides[2] = {row_stride_bytes, d2_stride_bytes};
    cuuint32_t box[3] = {b0, b1, b2};
    cuuint32_t es[3] = {1, 1, 1};
    enc(m, CU_TENSOR_MAP_DATA_TYPE_BFLOAT16, 3, const_cast<void*>(ptr), dims, strides, box, es, CU_TENSOR_MAP_INTERLEAVE_NONE,
        CU_TENSOR_MAP_SWIZZLE_128B, CU_TENSOR_MAP_L2_PROMOTION_L2_256B, CU_TENSOR_MAP_FLOAT_OOB_FILL_NONE);
}

template <typename... KArgs, typename... Args>
void launch(void (*kern)(KArgs...), int grid, int block, int smem, bool pdl, Args... args) {
    cudaLaunchConfig_t cfg = {};
    cfg.gridDim = dim3(grid);
    cfg.blockDim = dim3(block);
    cfg.dynamicSmemBytes = smem;
    cfg.stream = cudaStreamPerThread;
    cudaLaunchAttribute at[1];
    at[0].id = cudaLaunchAttributeProgrammaticStreamSerialization;
    at[0].val.programmaticStreamSerializationAllowed = 1;
    cfg.attrs = at;
    cfg.numAttrs = pdl ? 1 : 0;
    cudaLaunchKernelEx(&cfg, kern, KArgs(args)...);
}

}

extern "C" void kernel_launch(void* const* d_in, const int* in_sizes, int n_in, void* d_out, int out_size) {
    const __nv_bfloat16* x = (const __nv_bfloat16*)d_in[0];
    const __nv_bfloat16* wqkv = (const __nv_bfloat16*)d_in[1];
    const __nv_bfloat16* wo = (const __nv_bfloat16*)d_in[2];
    const __nv_bfloat16* w_r = (const __nv_bfloat16*)d_in[4];
    const __nv_bfloat16* w_gate = (const __nv_bfloat16*)d_in[5];
    const __nv_bfloat16* w_up = (const __nv_bfloat16*)d_in[6];
    const __nv_bfloat16* w_down = (const __nv_bfloat16*)d_in[7];
    __nv_bfloat16* out = (__nv_bfloat16*)d_out;

    static PFN_encodeTiled enc = nullptr;
    static void* g_o_ptr = nullptr;
    if (!enc) {
        cudaDriverEntryPointQueryResult qres;
        void* fn = nullptr;
        cudaGetDriverEntryPoint("cuTensorMapEncodeTiled", &fn, cudaEnableDefault, &qres);
        enc = (PFN_encodeTiled)fn;
        cudaGetSymbolAddress(&g_o_ptr, g_o);
        cudaFuncSetAttribute(k1_qkv, cudaFuncAttributeMaxDynamicSharedMemorySize, K1_SMEM);
        cudaFuncSetAttribute(kf_main, cudaFuncAttributeMaxDynamicSharedMemorySize, KF_SMEM);
    }
    CUtensorMap tm_x, tm_w, tm_o, tm_wo;
    make_map(enc, &tm_x, x, DM, SEQ, 64, 128);
    make_map3(enc, &tm_w, wqkv, DM, DM, 3, 3 * DM * 2, DM * 2, 64, 64, 3);
    make_map3(enc, &tm_o, g_o_ptr, 64, SEQ, 8, DM * 2, 128, 64, 64, 2);
    make_map3(enc, &tm_wo, wo, 64, DM, 8, DM * 2, 128, 64, 64, 2);

    const bool pdl = true;
    launch(k1_qkv, 128, 544, K1_SMEM, false, tm_x, tm_w, x);
    launch(kf_main, 128, 512, KF_SMEM, pdl, tm_o, tm_wo, x, wo, w_r, w_gate, w_up, w_down, out);
}
```

```cpp
#include <cuda_runtime.h>
#include <cuda_bf16.h>
#include <cuda.h>
#include <stdint.h>

namespace {

constexpr int SEQ = 2048, DM = 512, NH = 32, FF = 1792;

__device__ __align__(1024) uint8_t g_q[NH * 2 * SEQ * 16];
__device__ __align__(1024) uint8_t g_kv[NH * 8 * 16384];
__device__ float g_norm[16 * NH * 3];
__device__ __align__(1024) __nv_bfloat16 g_o[SEQ * DM];
__device__ __align__(1024) __nv_bfloat16 g_h[SEQ * DM];
__device__ __align__(16) uint4 g_cand[64];
__device__ unsigned int g_oflag[32 * 32];
__device__ unsigned int g_hflag[32];
__device__ __align__(16) float g_y[2 * DM];
__device__ unsigned int g_cnt;
__device__ unsigned int g_epoch;
__device__ __align__(16) float4 g_ln1[SEQ];
__device__ __align__(16) float4 g_part[32 * 8 * 64];

#define TSTAMP(K, I)
#define TSTAMP0(K, I)
__device__ __forceinline__ uint32_t smem_u32(const void* p) { return (uint32_t)__cvta_generic_to_shared(p); }
__device__ __forceinline__ void wg_fence() { asm volatile("wgmma.fence.sync.aligned;" ::: "memory"); }
__device__ __forceinline__ void wg_commit() { asm volatile("wgmma.commit_group.sync.aligned;" ::: "memory"); }
template <int N> __device__ __forceinline__ void wg_wait() { asm volatile("wgmma.wait_group.sync.aligned %0;" ::"n"(N) : "memory"); }
template <int N> __device__ __forceinline__ void fence_regs(float (&r)[N]) {
#pragma unroll
    for (int i = 0; i < N; i++) asm volatile("" : "+f"(r[i])::"memory");
}
__device__ __forceinline__ uint64_t make_desc(uint32_t addr, uint32_t lbo, uint32_t sbo, uint32_t swz) {
    uint64_t d = 0;
    d |= (uint64_t)((addr & 0x3FFFF) >> 4);
    d |= (uint64_t)((lbo & 0x3FFFF) >> 4) << 16;
    d |= (uint64_t)((sbo & 0x3FFFF) >> 4) << 32;
    d |= (uint64_t)swz << 62;
    return d;
}
__device__ __forceinline__ void mbar_init(uint32_t bar, uint32_t cnt) {
    asm volatile("mbarrier.init.shared::cta.b64 [%0], %1;" ::"r"(bar), "r"(cnt) : "memory");
}
__device__ __forceinline__ void mbar_expect_tx(uint32_t bar, uint32_t bytes) {
    asm volatile("mbarrier.arrive.expect_tx.shared::cta.b64 _, [%0], %1;" ::"r"(bar), "r"(bytes) : "memory");
}
__device__ __forceinline__ void mbar_arrive(uint32_t bar) {
    asm volatile("mbarrier.arrive.shared::cta.b64 _, [%0];" ::"r"(bar) : "memory");
}
__device__ __forceinline__ void mbar_wait(uint32_t bar, uint32_t parity) {
    asm volatile(
        "{\n.reg .pred p;\nWAIT_%=:\n"
        "mbarrier.try_wait.parity.shared::cta.b64 p, [%0], %1;\n"
        "@p bra DONE_%=;\nbra WAIT_%=;\nDONE_%=:\n}\n" ::"r"(bar), "r"(parity) : "memory");
}
__device__ __forceinline__ void bulk_g2s(uint32_t dst, const void* src, uint32_t bytes, uint32_t bar) {
    asm volatile("cp.async.bulk.shared::cluster.global.mbarrier::complete_tx::bytes [%0], [%1], %2, [%3];" ::"r"(dst),
                 "l"(src), "r"(bytes), "r"(bar) : "memory");
}
__device__ __forceinline__ void bulk_s2g(void* dst, uint32_t src, uint32_t bytes) {
    asm volatile("cp.async.bulk.global.shared::cta.bulk_group [%0], [%1], %2;" ::"l"(dst), "r"(src), "r"(bytes) : "memory");
}
__device__ __forceinline__ void tma_load_2d(uint32_t dst, const CUtensorMap* tm, int c0, int c1, uint32_t bar) {
    asm volatile("cp.async.bulk.tensor.2d.shared::cluster.global.mbarrier::complete_tx::bytes [%0], [%1, {%3, %4}], [%2];" ::"r"(dst),
                 "l"(tm), "r"(bar), "r"(c0), "r"(c1) : "memory");
}
__device__ __forceinline__ void tma_load_3d(uint32_t dst, const CUtensorMap* tm, int c0, int c1, int c2, uint32_t bar) {
    asm volatile("cp.async.bulk.tensor.3d.shared::cluster.global.mbarrier::complete_tx::bytes [%0], [%1, {%3, %4, %5}], [%2];" ::"r"(dst),
                 "l"(tm), "r"(bar), "r"(c0), "r"(c1), "r"(c2) : "memory");
}
__device__ __forceinline__ void tma_load_2d_mc(uint32_t dst, const CUtensorMap* tm, int c0, int c1, uint32_t bar, uint16_t mask) {
    asm volatile("cp.async.bulk.tensor.2d.shared::cluster.global.mbarrier::complete_tx::bytes.multicast::cluster [%0], [%1, {%3, %4}], [%2], %5;" ::"r"(dst),
                 "l"(tm), "r"(bar), "r"(c0), "r"(c1), "h"(mask) : "memory");
}
__device__ __forceinline__ void mbar_arrive_cluster(uint32_t bar, uint32_t cta) {
    asm volatile("{\n.reg .b32 ra;\nmapa.shared::cluster.u32 ra, %0, %1;\nmbarrier.arrive.release.cluster.shared::cluster.b64 _, [ra];\n}" ::"r"(bar), "r"(cta) : "memory");
}
__device__ __forceinline__ void cluster_sync() {
    asm volatile("barrier.cluster.arrive.release.aligned;\nbarrier.cluster.wait.acquire.aligned;" ::: "memory");
}
__device__ __forceinline__ void prefetch_l2(const void* p, uint32_t bytes) {
    asm volatile("cp.async.bulk.prefetch.L2.global [%0], %1;" ::"l"(p), "r"(bytes) : "memory");
}
__device__ __forceinline__ void fence_proxy_async() { asm volatile("fence.proxy.async.shared::cta;" ::: "memory"); }
__device__ __forceinline__ void fence_barrier_init() { asm volatile("fence.mbarrier_init.release.cluster;" ::: "memory"); }
__device__ __forceinline__ void pdl_launch() { asm volatile("griddepcontrol.launch_dependents;" ::: "memory"); }
__device__ __forceinline__ void pdl_wait() { asm volatile("griddepcontrol.wait;" ::: "memory"); }
__device__ __forceinline__ void named_sync(int id, int n) { asm volatile("bar.sync %0, %1;" ::"r"(id), "r"(n) : "memory"); }
__device__ __forceinline__ void named_arrive(int id, int n) { asm volatile("bar.arrive %0, %1;" ::"r"(id), "r"(n) : "memory"); }

__device__ __forceinline__ float ex2f(float x) { float y; asm("ex2.approx.ftz.f32 %0, %1;" : "=f"(y) : "f"(x)); return y; }
__device__ __forceinline__ uint32_t pack_bf16(float lo, float hi) {
    uint32_t r; asm("cvt.rn.bf16x2.f32 %0, %1, %2;" : "=r"(r) : "f"(hi), "f"(lo)); return r;
}
__device__ __forceinline__ float bf_lo(uint32_t v) { return __uint_as_float(v << 16); }
__device__ __forceinline__ float bf_hi(uint32_t v) { return __uint_as_float(v & 0xFFFF0000u); }
__device__ __forceinline__ float rbf(float x) { return __bfloat162float(__float2bfloat16_rn(x)); }
__device__ __forceinline__ uint32_t fma_bf16x2(uint32_t a, uint32_t b, uint32_t c) {
    uint32_t r; asm("fma.rn.bf16x2 %0, %1, %2, %3;" : "=r"(r) : "r"(a), "r"(b), "r"(c)); return r;
}
__device__ __forceinline__ void stmatrix_x4(uint32_t addr, uint32_t r0, uint32_t r1, uint32_t r2, uint32_t r3) {
    asm volatile("stmatrix.sync.aligned.m8n8.x4.shared.b16 [%0], {%1, %2, %3, %4};" ::"r"(addr), "r"(r0), "r"(r1), "r"(r2), "r"(r3) : "memory");
}
__device__ __forceinline__ void stmatrix_x4_trans(uint32_t addr, uint32_t r0, uint32_t r1, uint32_t r2, uint32_t r3) {
    asm volatile("stmatrix.sync.aligned.m8n8.x4.trans.shared.b16 [%0], {%1, %2, %3, %4};" ::"r"(addr), "r"(r0), "r"(r1), "r"(r2), "r"(r3) : "memory");
}

__device__ __forceinline__ void wgmma_k1_n136(float (&d)[68], uint64_t desca, uint64_t descb, int scale_d) {
  asm volatile("{\n.reg .pred p;\nsetp.ne.b32 p, %70, 0;\n"
    "wgmma.mma_async.sync.aligned.m64n136k16.f32.bf16.bf16 "
    "{%0, %1, %2, %3, %4, %5, %6, %7, %8, %9, %10, %11, %12, %13, %14, %15, %16, %17, %18, %19, %20, %21, %22, %23, %24, %25, %26, %27, %28, %29, %30, %31, %32, %33, %34, %35, %36, %37, %38, %39, %40, %41, %42, %43, %44, %45, %46, %47, %48, %49, %50, %51, %52, %53, %54, %55, %56, %57, %58, %59, %60, %61, %62, %63, %64, %65, %66, %67}, "
    "%68, %69, p, 1, 1, 1, 0;\n}\n"
    : "+f"(d[0]), "+f"(d[1]), "+f"(d[2]), "+f"(d[3]), "+f"(d[4]), "+f"(d[5]), "+f"(d[6]), "+f"(d[7]), "+f"(d[8]), "+f"(d[9]), "+f"(d[10]), "+f"(d[11]), "+f"(d[12]), "+f"(d[13]), "+f"(d[14]), "+f"(d[15]), "+f"(d[16]), "+f"(d[17]), "+f"(d[18]), "+f"(d[19]), "+f"(d[20]), "+f"(d[21]), "+f"(d[22]), "+f"(d[23]), "+f"(d[24]), "+f"(d[25]), "+f"(d[26]), "+f"(d[27]), "+f"(d[28]), "+f"(d[29]), "+f"(d[30]), "+f"(d[31]), "+f"(d[32]), "+f"(d[33]), "+f"(d[34]), "+f"(d[35]), "+f"(d[36]), "+f"(d[37]), "+f"(d[38]), "+f"(d[39]), "+f"(d[40]), "+f"(d[41]), "+f"(d[42]), "+f"(d[43]), "+f"(d[44]), "+f"(d[45]), "+f"(d[46]), "+f"(d[47]), "+f"(d[48]), "+f"(d[49]), "+f"(d[50]), "+f"(d[51]), "+f"(d[52]), "+f"(d[53]), "+f"(d[54]), "+f"(d[55]), "+f"(d[56]), "+f"(d[57]), "+f"(d[58]), "+f"(d[59]), "+f"(d[60]), "+f"(d[61]), "+f"(d[62]), "+f"(d[63]), "+f"(d[64]), "+f"(d[65]), "+f"(d[66]), "+f"(d[67])
    : "l"(desca), "l"(descb), "r"(scale_d));
}
__device__ __forceinline__ void wgmma_qk_n64(float (&d)[32], uint32_t a0, uint32_t a1, uint32_t a2, uint32_t a3, uint64_t descb) {
  asm volatile("{\n.reg .pred p;\nsetp.ne.b32 p, 0, 0;\n"
    "wgmma.mma_async.sync.aligned.m64n64k16.f32.bf16.bf16 "
    "{%0, %1, %2, %3, %4, %5, %6, %7, %8, %9, %10, %11, %12, %13, %14, %15, %16, %17, %18, %19, %20, %21, %22, %23, %24, %25, %26, %27, %28, %29, %30, %31}, "
    "{%32, %33, %34, %35}, %36, p, 1, 1, 0;\n}\n"
    : "=f"(d[0]), "=f"(d[1]), "=f"(d[2]), "=f"(d[3]), "=f"(d[4]), "=f"(d[5]), "=f"(d[6]), "=f"(d[7]), "=f"(d[8]), "=f"(d[9]), "=f"(d[10]), "=f"(d[11]), "=f"(d[12]), "=f"(d[13]), "=f"(d[14]), "=f"(d[15]), "=f"(d[16]), "=f"(d[17]), "=f"(d[18]), "=f"(d[19]), "=f"(d[20]), "=f"(d[21]), "=f"(d[22]), "=f"(d[23]), "=f"(d[24]), "=f"(d[25]), "=f"(d[26]), "=f"(d[27]), "=f"(d[28]), "=f"(d[29]), "=f"(d[30]), "=f"(d[31])
    : "r"(a0), "r"(a1), "r"(a2), "r"(a3), "l"(descb));
}
__device__ __forceinline__ void wgmma_pv_n24(float (&d)[12], uint32_t a0, uint32_t a1, uint32_t a2, uint32_t a3, uint64_t descb) {
  asm volatile("{\n.reg .pred p;\nsetp.eq.b32 p, 0, 0;\n"
    "wgmma.mma_async.sync.aligned.m64n24k16.f32.bf16.bf16 "
    "{%0, %1, %2, %3, %4, %5, %6, %7, %8, %9, %10, %11}, "
    "{%12, %13, %14, %15}, %16, p, 1, 1, 1;\n}\n"
    : "+f"(d[0]), "+f"(d[1]), "+f"(d[2]), "+f"(d[3]), "+f"(d[4]), "+f"(d[5]), "+f"(d[6]), "+f"(d[7]), "+f"(d[8]), "+f"(d[9]), "+f"(d[10]), "+f"(d[11])
    : "r"(a0), "r"(a1), "r"(a2), "r"(a3), "l"(descb));
}
__device__ __forceinline__ void wgmma_k3_n64(float (&d)[32], uint64_t desca, uint64_t descb, int scale_d) {
  asm volatile("{\n.reg .pred p;\nsetp.ne.b32 p, %34, 0;\n"
    "wgmma.mma_async.sync.aligned.m64n64k16.f32.bf16.bf16 "
    "{%0, %1, %2, %3, %4, %5, %6, %7, %8, %9, %10, %11, %12, %13, %14, %15, %16, %17, %18, %19, %20, %21, %22, %23, %24, %25, %26, %27, %28, %29, %30, %31}, "
    "%32, %33, p, 1, 1, 0, 1;\n}\n"
    : "+f"(d[0]), "+f"(d[1]), "+f"(d[2]), "+f"(d[3]), "+f"(d[4]), "+f"(d[5]), "+f"(d[6]), "+f"(d[7]), "+f"(d[8]), "+f"(d[9]), "+f"(d[10]), "+f"(d[11]), "+f"(d[12]), "+f"(d[13]), "+f"(d[14]), "+f"(d[15]), "+f"(d[16]), "+f"(d[17]), "+f"(d[18]), "+f"(d[19]), "+f"(d[20]), "+f"(d[21]), "+f"(d[22]), "+f"(d[23]), "+f"(d[24]), "+f"(d[25]), "+f"(d[26]), "+f"(d[27]), "+f"(d[28]), "+f"(d[29]), "+f"(d[30]), "+f"(d[31])
    : "l"(desca), "l"(descb), "r"(scale_d));
}

constexpr int K1_XS = 17408;
constexpr int K1_WS = 24576;
constexpr int K1_ST = K1_XS + K1_WS;
constexpr int K1_NST = 5;
constexpr int K1_OFF_MISC = K1_NST * K1_ST;
constexpr int K1_SMEM = K1_OFF_MISC + 2048 + 1024;
constexpr float QSCALE = 0.25f * 1.4426950408889634f;

__global__ void __launch_bounds__(544, 1)
k1_qkv(const __grid_constant__ CUtensorMap tm_x, const __grid_constant__ CUtensorMap tm_w, const __nv_bfloat16* __restrict__ x) {
    extern __shared__ uint8_t smem_raw[];
    const uint32_t sraw = smem_u32(smem_raw);
    const uint32_t sb = (sraw + 1023) & ~1023u;
    uint8_t* sp = smem_raw + (sb - sraw);
    const uint32_t full = sb + K1_OFF_MISC;
    const uint32_t empty = full + 64;
    float* s_m = (float*)(sp + K1_OFF_MISC + 256);
    float* s_r = s_m + 128;

    const int tid = threadIdx.x, warp = tid >> 5, lane = tid & 31;
    const int mt = blockIdx.x >> 3, nt = blockIdx.x & 7;
    if (tid == 0) TSTAMP0(0, 0);
    pdl_launch();
    if (tid == 0) {
        for (int i = 0; i < K1_NST; i++) { mbar_init(full + 8 * i, 1); mbar_init(empty + 8 * i, 3); }
        fence_barrier_init();
    }
    if (tid < K1_NST * 64) {
        *(uint4*)(sp + (tid >> 6) * K1_ST + 16384 + (tid & 63) * 16) =
            make_uint4(0x3F803F80u, 0x3F803F80u, 0x3F803F80u, 0x3F803F80u);
    }
    fence_proxy_async();
    __syncthreads();

    if (warp == 16) {
        if (lane == 0) {
            for (int kb = 0; kb < 8; kb++) {
                const int s = kb % K1_NST;
                if (kb >= K1_NST) mbar_wait(empty + 8 * s, 0);
                mbar_expect_tx(full + 8 * s, 16384 + K1_WS);
                tma_load_2d(sb + s * K1_ST, &tm_x, kb * 64, mt * 128, full + 8 * s);
                tma_load_3d(sb + s * K1_ST + K1_XS, &tm_w, nt * 64, kb * 64, 0, full + 8 * s);
            }
        } else if (lane == 1) {
            if (blockIdx.x == 0) g_cnt = 0;
        }
        if (blockIdx.x == 0) for (int i = lane; i < 2 * DM; i += 32) g_y[i] = 0.f;
        for (int i = lane; i < 128; i += 32) g_part[blockIdx.x * 128 + i] = make_float4(0.f, 0.f, 0.f, 0.f);
        if (blockIdx.x == 1) { g_cand[lane] = make_uint4(0, 0, 0, 0); g_cand[lane + 32] = make_uint4(0, 0, 0, 0); g_oflag[lane * 32] = 0; g_hflag[lane] = 0; }
    } else if (warp >= 12) {
        const int r = tid - 384;
        const unsigned int tag = *(volatile unsigned int*)&g_epoch + 1u;
        {
            const int row = mt * 128 + nt * 16 + (r >> 3);
            const uint4* xp = (const uint4*)(x + (size_t)row * DM) + (r & 7);
            uint4 v[8];
#pragma unroll
            for (int i = 0; i < 8; i++) v[i] = __ldg(xp + i * 8);
            float s1 = 0.f;
#pragma unroll
            for (int i = 0; i < 8; i++)
                s1 += ((bf_lo(v[i].x) + bf_hi(v[i].x)) + (bf_lo(v[i].y) + bf_hi(v[i].y))) + ((bf_lo(v[i].z) + bf_hi(v[i].z)) + (bf_lo(v[i].w) + bf_hi(v[i].w)));
#pragma unroll
            for (int o = 1; o < 8; o <<= 1) s1 += __shfl_xor_sync(0xffffffffu, s1, o);
            const float mean = s1 * (1.f / DM);
            float q0 = 0.f, q1 = 0.f;
#pragma unroll
            for (int i = 0; i < 8; i++) {
                const uint32_t w[4] = {v[i].x, v[i].y, v[i].z, v[i].w};
#pragma unroll
                for (int j = 0; j < 4; j++) {
                    const float a = bf_lo(w[j]) - mean, b = bf_hi(w[j]) - mean;
                    q0 = fmaf(a, a, q0); q1 = fmaf(b, b, q1);
                }
            }
            float q = q0 + q1;
#pragma unroll
            for (int o = 1; o < 8; o <<= 1) q += __shfl_xor_sync(0xffffffffu, q, o);
            const float den = rbf(sqrtf(rbf(rbf(q * (1.f / DM)) + 1e-5f)));
            if ((r & 7) == 0)
                asm volatile("st.relaxed.gpu.global.v4.f32 [%0], {%1, %2, %3, %4};" ::"l"(g_ln1 + row), "f"(rbf(mean)), "f"(1.f / den),
                             "f"(__uint_as_float(tag)), "f"(0.f) : "memory");
        }
        if (r == 0) TSTAMP0(0, 6);
        {
            float4 v;
            int spins = 0;
            do {
                asm volatile("ld.relaxed.gpu.global.v4.f32 {%0, %1, %2, %3}, [%4];" : "=f"(v.x), "=f"(v.y), "=f"(v.z), "=f"(v.w) : "l"(g_ln1 + mt * 128 + r) : "memory");
            } while (__float_as_uint(v.z) != tag && ++spins < (1 << 22));
            s_m[r] = v.x;
            s_r[r] = v.y;
        }
        if (r == 0) TSTAMP0(0, 7);
        named_arrive(1, 512);
    } else {
        const int part = warp >> 2, hw = warp & 3;
        float acc[68];
#pragma unroll
        for (int i = 0; i < 68; i++) acc[i] = 0.f;
        fence_regs(acc);
#pragma unroll 1
        for (int kb = 0; kb < 8; kb++) {
            const int s = kb % K1_NST;
            mbar_wait(full + 8 * s, (kb / K1_NST) & 1);
            const uint64_t da = make_desc(sb + s * K1_ST + K1_XS + part * 8192, 1024, 1024, 1);
            const uint64_t db = make_desc(sb + s * K1_ST, 16, 1024, 1);
            wg_fence();
#pragma unroll
            for (int k = 0; k < 4; k++) wgmma_k1_n136(acc, da + k * 128, db + k * 2, (kb | k) != 0);
            wg_commit();
            if (kb > 0 && kb <= 8 - K1_NST) {
                wg_wait<1>();
                if ((tid & 127) == 0) mbar_arrive(empty + 8 * (kb - 1));
            }
        }
        wg_wait<0>();
        fence_regs(acc);
        if (tid == 0) TSTAMP0(0, 1);
        named_sync(1, 512);
        if (tid == 0) TSTAMP0(0, 2);

        const int t = lane & 3;
        const float cs0 = acc[64], cs1 = acc[66];
        const float sc = (part == 0) ? QSCALE : 1.f;
        const uint32_t stg = sb + (hw >> 1) * K1_ST + K1_XS + part * 8192 + (hw & 1) * 4096;
        const uint32_t st_addr = stg + ((lane >> 3) & 1) * 2048 + ((lane >> 4) * 8 + (lane & 7)) * 16;
#pragma unroll
        for (int j = 0; j < 16; j += 2) {
            uint32_t rr[4];
#pragma unroll
            for (int u = 0; u < 2; u++) {
                const int jj = j + u;
                const float2 m2 = *(const float2*)(s_m + 8 * jj + 2 * t);
                const float2 r2 = *(const float2*)(s_r + 8 * jj + 2 * t);
                const float ra = r2.x * sc, rb = r2.y * sc;
                rr[2 * u] = pack_bf16((acc[4 * jj] - m2.x * cs0) * ra, (acc[4 * jj + 1] - m2.y * cs0) * rb);
                rr[2 * u + 1] = pack_bf16((acc[4 * jj + 2] - m2.x * cs1) * ra, (acc[4 * jj + 3] - m2.y * cs1) * rb);
            }
            stmatrix_x4_trans(st_addr + j * 128, rr[0], rr[1], rr[2], rr[3]);
        }
        __syncwarp();
        if (tid == 0) TSTAMP0(0, 4);
        float nmax = 0.f;
#pragma unroll
        for (int i = 0; i < 4; i++) {
            const int tok = lane + 32 * i;
            const uint4 a = *(const uint4*)(sp + (stg - sb) + tok * 16);
            const uint4 b = *(const uint4*)(sp + (stg - sb) + 2048 + tok * 16);
            const uint32_t w[8] = {a.x, a.y, a.z, a.w, b.x, b.y, b.z, b.w};
            float n2 = 0.f;
#pragma unroll
            for (int q = 0; q < 8; q++) {
                const float lo = bf_lo(w[q]), hi = bf_hi(w[q]);
                n2 = fmaf(lo, lo, n2); n2 = fmaf(hi, hi, n2);
            }
            nmax = (n2 > nmax || n2 != n2) ? n2 : nmax;
        }
#pragma unroll
        for (int o = 16; o > 0; o >>= 1) {
            const float v = __shfl_xor_sync(0xffffffffu, nmax, o);
            nmax = (v > nmax || v != v) ? v : nmax;
        }
        if (tid == 0) TSTAMP0(0, 5);
        fence_proxy_async();
        __syncwarp();
        if (lane == 0) {
            const int head = nt * 4 + hw;
            g_norm[(mt * NH + head) * 3 + part] = nmax;
            uint8_t* dst;
            uint32_t hstride;
            if (part == 0) { dst = g_q + (size_t)head * 65536 + mt * 2048; hstride = 32768; }
            else { dst = g_kv + (size_t)head * 131072 + (mt >> 1) * 16384 + (part - 1) * 8192 + (mt & 1) * 2048; hstride = 4096; }
            bulk_s2g(dst, stg, 2048);
            bulk_s2g(dst + hstride, stg + 2048, 2048);
            asm volatile("cp.async.bulk.commit_group;" ::: "memory");
            asm volatile("cp.async.bulk.wait_group.read 0;" ::: "memory");
            if (tid == 0) TSTAMP0(0, 3);
        }
    }
}

constexpr int KF_CH_G = 16384, KF_CH_S = 20480, KF_NCH = 8;
constexpr int KF_OFF_WO = KF_NCH * KF_CH_S;
constexpr int KF_OFF_MISC = KF_OFF_WO + 65536;
constexpr int KF_SMEM = KF_OFF_MISC + 1280 + 1024;

__device__ __forceinline__ uint32_t exp2_pair_poly(float s0, float s1) {
    const float KB = 65536.0f + 127.0f;
    const float t0 = s0 + KB, t1 = s1 + KB;
    const uint32_t w = __byte_perm(__float_as_uint(t0), __float_as_uint(t1), 0x5410);
    uint32_t z;
    asm("lop3.b32 %0, %1, %2, %3, 0xEA;" : "=r"(z) : "r"(w), "r"(0x007F007Fu), "r"(0x3F803F80u));
    uint32_t p = fma_bf16x2(0x3eab3eabu, z, 0xbc73bc73u);
    p = fma_bf16x2(p, z, 0x3f2f3f2fu);
    return p + w - z;
}
constexpr uint32_t KF_EMASK = 0x5757u;
template <int LO, int HI>
__device__ __forceinline__ void softmax_part(const float (&s)[32], uint32_t (&p)[16]) {
#pragma unroll
    for (int i = LO; i < HI; i++) {
        if ((KF_EMASK >> i) & 1) p[i] = exp2_pair_poly(s[2 * i], s[2 * i + 1]);
        else p[i] = pack_bf16(ex2f(s[2 * i]), ex2f(s[2 * i + 1]));
    }
}
#define KF_PV(P, OFF)                                                                              \
    _Pragma("unroll") for (int kk = 0; kk < 4; kk++)                                               \
        wgmma_pv_n24(o, P[4 * kk], P[4 * kk + 1], P[4 * kk + 2], P[4 * kk + 3], dv + ((OFF) + kk * 16));

__device__ __forceinline__ unsigned long long cand_key(const uint4& c) {
    return ((unsigned long long)c.x << 32) | (uint32_t)(0x7FFFFFFF - (int)c.y);
}
__device__ __forceinline__ uint32_t order_bits(float v) {
    const uint32_t u = __float_as_uint(v);
    return (u & 0x80000000u) ? ~u : (u | 0x80000000u);
}
__device__ __forceinline__ float order_value(uint32_t u) {
    return __uint_as_float((u & 0x80000000u) ? (u & 0x7FFFFFFFu) : ~u);
}
__device__ __forceinline__ void warp_top2(unsigned long long& a, unsigned long long& b) {
#pragma unroll
    for (int o = 16; o > 0; o >>= 1) {
        const unsigned long long c = __shfl_xor_sync(0xffffffffu, a, o);
        const unsigned long long d = __shfl_xor_sync(0xffffffffu, b, o);
        const unsigned long long hi = a > c ? a : c, lo = a > c ? c : a;
        const unsigned long long m = b > d ? b : d;
        a = hi;
        b = lo > m ? lo : m;
    }
}
__device__ __forceinline__ unsigned int ld_acquire(const unsigned int* p) {
    unsigned int v; asm volatile("ld.acquire.gpu.global.u32 %0, [%1];" : "=r"(v) : "l"(p) : "memory"); return v;
}
__device__ __forceinline__ void red_release_add(unsigned int* p) {
    asm volatile("red.release.gpu.global.add.u32 [%0], 1;" ::"l"(p) : "memory");
}

__global__ void __launch_bounds__(512, 1)
kf_main(const __grid_constant__ CUtensorMap tm_o, const __grid_constant__ CUtensorMap tm_wo,
        const __grid_constant__ CUtensorMap tm_g, const __grid_constant__ CUtensorMap tm_u,
        const __nv_bfloat16* __restrict__ x, const __nv_bfloat16* __restrict__ wo, const __nv_bfloat16* __restrict__ w_r,
        const __nv_bfloat16* __restrict__ w_gate, const __nv_bfloat16* __restrict__ w_up, const __nv_bfloat16* __restrict__ w_down,
        __nv_bfloat16* __restrict__ out) {
    extern __shared__ uint8_t smem_raw[];
    const uint32_t sraw = smem_u32(smem_raw);
    const uint32_t sb = (sraw + 1023) & ~1023u;
    uint8_t* sp = smem_raw + (sb - sraw);
    const uint32_t kvbar = sb + KF_OFF_MISC;
    const uint32_t wbar = kvbar + 64;
    const uint32_t obar = wbar + 64;
    const uint32_t gbar = obar + 32;
    unsigned int* s_cnt = (unsigned int*)(sp + KF_OFF_MISC + 192);
    unsigned long long* s_key = (unsigned long long*)(sp + KF_OFF_MISC + 256);
    float* s_gu = (float*)(sp + KF_OFF_MISC + 768);
    uint4* s_sel = (uint4*)(sp + KF_OFF_MISC + 1024);
    const int tid = threadIdx.x;
    const int head = blockIdx.x >> 2, quarter = blockIdx.x & 3;
    const int mt = blockIdx.x >> 2, nt = blockIdx.x & 3;
    if (tid == 0) TSTAMP0(1, 0);
    if (tid == 0) {
        for (int c = 0; c < 21; c++) mbar_init(kvbar + 8 * c, 1);
        for (int c = 0; c < 4; c++) s_cnt[c] = 0;
        fence_barrier_init();
        for (int kb = 0; kb < 4; kb++) {
            mbar_expect_tx(wbar + 8 * kb, 16384);
            tma_load_3d(sb + KF_OFF_WO + kb * 16384, &tm_wo, 0, kb * 64, nt * 2, wbar + 8 * kb);
        }
    }
    if (tid == 32) {
        prefetch_l2((const uint8_t*)wo + blockIdx.x * 4096, 4096);
        prefetch_l2((const uint8_t*)w_gate + blockIdx.x * 14336, 14336);
        prefetch_l2((const uint8_t*)w_up + blockIdx.x * 14336, 14336);
        prefetch_l2((const uint8_t*)w_down + blockIdx.x * 14336, 14336);
    }
    for (int i = tid; i < KF_NCH * 256; i += 512)
        *(uint4*)(sp + (i >> 8) * KF_CH_S + 16384 + (i & 255) * 16) =
            make_uint4(0x3F803F80u, 0x3F803F80u, 0x3F803F80u, 0x3F803F80u);
    fence_proxy_async();
    __syncthreads();
    pdl_wait();
    if (tid == 0) TSTAMP0(1, 1);
    if (tid == 0) {
        const uint8_t* src = g_kv + (size_t)head * (KF_NCH * KF_CH_G);
        for (int c = 0; c < KF_NCH; c++) {
            mbar_expect_tx(kvbar + 8 * c, KF_CH_G);
            bulk_g2s(sb + c * KF_CH_S, src + c * KF_CH_G, KF_CH_G, kvbar + 8 * c);
        }
    }
    const int wg = tid >> 7, warp = (tid >> 5) & 3, lane = tid & 31, g = lane >> 2, t = lane & 3;

    bool fast;
    {
        const int m16 = lane & 15;
        float kn = g_norm[(m16 * NH + head) * 3 + 1];
        float vn = g_norm[(m16 * NH + head) * 3 + 2];
        float qn = g_norm[((quarter * 4 + (lane & 3)) * NH + head) * 3 + 0];
        bool bad = !(kn < 1e30f) || !(vn < 1e30f) || !(qn < 1e30f);
#pragma unroll
        for (int o = 8; o > 0; o >>= 1) {
            kn = fmaxf(kn, __shfl_xor_sync(0xffffffffu, kn, o));
            qn = fmaxf(qn, __shfl_xor_sync(0xffffffffu, qn, o));
        }
        bad = __any_sync(0xffffffffu, bad);
        fast = !bad && (qn * kn <= 3500.f);
    }
    const uint64_t dk0 = make_desc(sb, 4096, 128, 0);
    const uint64_t dv0 = make_desc(sb + 8192, 128, 4096, 0);

#pragma unroll 1
    for (int pass = 0; pass < 2; pass++) {
        const int row0 = quarter * 512 + pass * 256 + wg * 64 + warp * 16 + g;
        uint32_t qa[4];
        {
            const uint8_t* qb = g_q + (size_t)head * 65536 + row0 * 16 + t * 4;
            qa[0] = *(const uint32_t*)(qb);
            qa[1] = *(const uint32_t*)(qb + 128);
            qa[2] = *(const uint32_t*)(qb + 32768);
            qa[3] = *(const uint32_t*)(qb + 32768 + 128);
        }
        float o[12];
#pragma unroll
        for (int i = 0; i < 12; i++) o[i] = 0.f;
        fence_regs(o);
#define KF_RELEASE_CHUNK(c)                                                                          \
        if (pass == 1 && (c) >= 1 && (c) <= 4) {                                                     \
            named_sync(4 + wg, 128);            \
            if ((tid & 127) == 0 && atomicAdd(&s_cnt[(c) - 1], 1u) == 3u) {                          \
                mbar_expect_tx(wbar + 8 * (3 + (c)), 16384);                                         \
                tma_load_3d(sb + ((c) - 1) * KF_CH_S, &tm_wo, 0, (3 + (c)) * 64, nt * 2, wbar + 8 * (3 + (c))); \
            }                                                                                        \
        }
        if (fast) {
#pragma unroll 1
            for (int c = 0; c < KF_NCH; c++) {
                const uint64_t dk = dk0 + (uint64_t)(c * (KF_CH_S >> 4));
                const uint64_t dv = dv0 + (uint64_t)(c * (KF_CH_S >> 4));
                float s0[32], s1[32], s2[32], s3[32];
                uint32_t p0[16], p1[16], p2[16], p3[16];
                mbar_wait(kvbar + 8 * c, 0);
                wg_wait<1>();
                wg_fence();
                wgmma_qk_n64(s0, qa[0], qa[1], qa[2], qa[3], dk);
                wg_commit();
                wg_wait<1>();
                KF_RELEASE_CHUNK(c);
                wg_fence();
                wgmma_qk_n64(s1, qa[0], qa[1], qa[2], qa[3], dk + 64);
                wg_commit();
                wg_wait<1>();
                fence_regs(s0);
                softmax_part<0, 16>(s0, p0);
                wg_fence();
                KF_PV(p0, 0);
                wg_commit();
                wg_wait<1>();
                fence_regs(s1);
                softmax_part<0, 8>(s1, p1);
                wg_wait<0>();
                wg_fence();
                wgmma_qk_n64(s2, qa[0], qa[1], qa[2], qa[3], dk + 128);
                wg_commit();
                softmax_part<8, 16>(s1, p1);
                wg_fence();
                KF_PV(p1, 64);
                wg_commit();
                wg_wait<1>();
                fence_regs(s2);
                softmax_part<0, 8>(s2, p2);
                wg_wait<0>();
                wg_fence();
                wgmma_qk_n64(s3, qa[0], qa[1], qa[2], qa[3], dk + 192);
                wg_commit();
                softmax_part<8, 16>(s2, p2);
                wg_fence();
                KF_PV(p2, 128);
                wg_commit();
                wg_wait<1>();
                fence_regs(s3);
                softmax_part<0, 16>(s3, p3);
                wg_fence();
                KF_PV(p3, 192);
                wg_commit();
            }
            wg_wait<0>();
            fence_regs(o);
        } else {
            float m0 = -INFINITY, m1 = -INFINITY;
#pragma unroll 1
            for (int b = 0; b < 32; b++) {
                const int c = b >> 2;
                const uint64_t dk = dk0 + (uint64_t)(c * (KF_CH_S >> 4) + (b & 3) * 64);
                const uint64_t dv = dv0 + (uint64_t)(c * (KF_CH_S >> 4) + (b & 3) * 64);
                float s[32];
                uint32_t p[16];
                mbar_wait(kvbar + 8 * c, 0);
                wg_fence();
                wgmma_qk_n64(s, qa[0], qa[1], qa[2], qa[3], dk);
                wg_commit();
                if ((b & 3) == 0) { KF_RELEASE_CHUNK(c); }
                wg_wait<0>();
                fence_regs(s);
                float x0 = s[0], x1 = s[2];
#pragma unroll
                for (int j = 0; j < 8; j++) {
                    x0 = fmaxf(x0, fmaxf(s[4 * j], s[4 * j + 1]));
                    x1 = fmaxf(x1, fmaxf(s[4 * j + 2], s[4 * j + 3]));
                }
                x0 = fmaxf(x0, __shfl_xor_sync(0xffffffffu, x0, 1));
                x0 = fmaxf(x0, __shfl_xor_sync(0xffffffffu, x0, 2));
                x1 = fmaxf(x1, __shfl_xor_sync(0xffffffffu, x1, 1));
                x1 = fmaxf(x1, __shfl_xor_sync(0xffffffffu, x1, 2));
                const float n0 = fmaxf(m0, x0), n1 = fmaxf(m1, x1);
                const float c0 = ex2f(m0 - n0), c1 = ex2f(m1 - n1);
                m0 = n0; m1 = n1;
#pragma unroll
                for (int j = 0; j < 3; j++) {
                    o[4 * j] *= c0; o[4 * j + 1] *= c0; o[4 * j + 2] *= c1; o[4 * j + 3] *= c1;
                }
#pragma unroll
                for (int j = 0; j < 8; j++) {
                    p[2 * j] = pack_bf16(ex2f(s[4 * j] - n0), ex2f(s[4 * j + 1] - n0));
                    p[2 * j + 1] = pack_bf16(ex2f(s[4 * j + 2] - n1), ex2f(s[4 * j + 3] - n1));
                }
                fence_regs(o);
                wg_fence();
                KF_PV(p, 0);
                wg_commit();
                wg_wait<0>();
                fence_regs(o);
            }
        }
        const float inv0 = 1.f / o[8], inv1 = 1.f / o[10];
        {
            uint32_t v0 = pack_bf16(o[0] * inv0, o[1] * inv0), v1 = pack_bf16(o[4] * inv0, o[5] * inv0);
            uint32_t v2 = pack_bf16(o[2] * inv1, o[3] * inv1), v3 = pack_bf16(o[6] * inv1, o[7] * inv1);
            const bool o1 = t & 1, o2 = t & 2;
            uint32_t s0 = o1 ? v0 : v1, s1 = o1 ? v2 : v3;
            s0 = __shfl_xor_sync(0xffffffffu, s0, 1); s1 = __shfl_xor_sync(0xffffffffu, s1, 1);
            uint32_t a0 = o1 ? s0 : v0, a1 = o1 ? v1 : s0, b0 = o1 ? s1 : v2, b1 = o1 ? v3 : s1;
            uint32_t x0 = o2 ? a0 : b0, x1 = o2 ? a1 : b1;
            x0 = __shfl_xor_sync(0xffffffffu, x0, 2); x1 = __shfl_xor_sync(0xffffffffu, x1, 2);
            uint4 r;
            r.x = o2 ? x0 : a0; r.y = o2 ? x1 : a1; r.z = o2 ? b0 : x0; r.w = o2 ? b1 : x1;
            *(uint4*)(g_o + (size_t)(row0 + (t >> 1) * 8) * DM + head * 16 + (t & 1) * 8) = r;
        }
        named_sync(4 + wg, 128);
        if ((tid & 127) == 0) red_release_add(&g_oflag[(quarter * 8 + pass * 4 + wg) * 32]);
        if (tid == 0) TSTAMP0(1, 2 + pass);
    }

    if (wg < 2) {
        const int wi = warp;
        const int r0 = mt * 64 + wi * 16 + g;
        const int cb = nt * 128 + wg * 64;
        uint32_t xr[16], wr[8];
#pragma unroll
        for (int j = 0; j < 8; j++) {
            xr[2 * j] = __ldg((const uint32_t*)(x + (size_t)r0 * DM + cb + 8 * j + 2 * t));
            xr[2 * j + 1] = __ldg((const uint32_t*)(x + (size_t)(r0 + 8) * DM + cb + 8 * j + 2 * t));
            wr[j] = __ldg((const uint32_t*)(w_r + cb + 8 * j + 2 * t));
        }
        if (tid == 0) {
            int spins = 0;
            while (ld_acquire(&g_oflag[mt * 32]) < 32u && ++spins < (1 << 20)) __nanosleep(64);
        }
        named_sync(1, 512);
        if (tid == 128 && blockIdx.x < FF / 16) {
            mbar_expect_tx(gbar, 32768);
            for (int i = 0; i < 4; i++) {
                tma_load_2d(sb + i * KF_CH_S + 16384, &tm_g, blockIdx.x * 16, i * 128, gbar);
                tma_load_2d(sb + (4 + i) * KF_CH_S + 16384, &tm_u, blockIdx.x * 16, i * 128, gbar);
            }
        }
        if (tid == 0) {
            asm volatile("fence.proxy.async;" ::: "memory");
            TSTAMP0(2, 1);
            for (int k2 = 0; k2 < 4; k2++) {
                mbar_expect_tx(obar + 8 * k2, 16384);
                tma_load_3d(sb + (4 + k2) * KF_CH_S, &tm_o, 0, mt * 64, k2 * 2, obar + 8 * k2);
            }
        }
        float wsum = 0.f;
        {
            const uint4 a = __ldg((const uint4*)(w_r + lane * 16)), b = __ldg((const uint4*)(w_r + lane * 16 + 8));
            const uint32_t w[8] = {a.x, a.y, a.z, a.w, b.x, b.y, b.z, b.w};
#pragma unroll
            for (int i = 0; i < 8; i++) wsum += bf_lo(w[i]) + bf_hi(w[i]);
#pragma unroll
            for (int o = 16; o > 0; o >>= 1) wsum += __shfl_xor_sync(0xffffffffu, wsum, o);
        }
        float acc[32];
#pragma unroll
        for (int i = 0; i < 32; i++) acc[i] = 0.f;
        fence_regs(acc);
#pragma unroll 1
        for (int kb = 0; kb < 8; kb++) {
            mbar_wait(wbar + 8 * kb, 0);
            mbar_wait(obar + 8 * (kb >> 1), 0);
            const uint32_t wa = (kb < 4) ? (KF_OFF_WO + kb * 16384) : ((kb - 4) * KF_CH_S);
            const uint64_t da = make_desc(sb + (4 + (kb >> 1)) * KF_CH_S + (kb & 1) * 8192, 16, 1024, 1);
            const uint64_t db = make_desc(sb + wa + wg * 8192, 1024, 1024, 1);
            wg_fence();
#pragma unroll
            for (int k = 0; k < 4; k++) wgmma_k3_n64(acc, da + k * 2, db + k * 128, (kb | k) != 0);
            wg_commit();
        }
        wg_wait<0>();
        fence_regs(acc);
        if (tid == 0) TSTAMP0(2, 2);
        float hv[32];
        float s0 = 0.f, s1 = 0.f, d0 = 0.f, d1 = 0.f;
#pragma unroll
        for (int j = 0; j < 8; j++) {
            hv[4 * j] = rbf(bf_lo(xr[2 * j]) + rbf(acc[4 * j]));
            hv[4 * j + 1] = rbf(bf_hi(xr[2 * j]) + rbf(acc[4 * j + 1]));
            hv[4 * j + 2] = rbf(bf_lo(xr[2 * j + 1]) + rbf(acc[4 * j + 2]));
            hv[4 * j + 3] = rbf(bf_hi(xr[2 * j + 1]) + rbf(acc[4 * j + 3]));
            const float wl = bf_lo(wr[j]), wh = bf_hi(wr[j]);
            s0 += hv[4 * j] + hv[4 * j + 1];
            s1 += hv[4 * j + 2] + hv[4 * j + 3];
            d0 = fmaf(hv[4 * j], wl, fmaf(hv[4 * j + 1], wh, d0));
            d1 = fmaf(hv[4 * j + 2], wl, fmaf(hv[4 * j + 3], wh, d1));
        }
#pragma unroll
        for (int o = 1; o < 4; o <<= 1) {
            s0 += __shfl_xor_sync(0xffffffffu, s0, o);
            s1 += __shfl_xor_sync(0xffffffffu, s1, o);
            d0 += __shfl_xor_sync(0xffffffffu, d0, o);
            d1 += __shfl_xor_sync(0xffffffffu, d1, o);
        }
        const float mu0 = s0 * (1.f / 64), mu1 = s1 * (1.f / 64);
        float q0 = 0.f, q1 = 0.f;
#pragma unroll
        for (int j = 0; j < 8; j++) {
            float a = hv[4 * j] - mu0, b = hv[4 * j + 1] - mu0, c = hv[4 * j + 2] - mu1, d = hv[4 * j + 3] - mu1;
            q0 = fmaf(a, a, fmaf(b, b, q0));
            q1 = fmaf(c, c, fmaf(d, d, q1));
        }
#pragma unroll
        for (int o = 1; o < 4; o <<= 1) {
            q0 += __shfl_xor_sync(0xffffffffu, q0, o);
            q1 += __shfl_xor_sync(0xffffffffu, q1, o);
        }
        float4* part = g_part + (size_t)mt * 512 + wi * 16 + g;
        if (t < 2) {
            float4* dst = part + (nt * 2 + wg) * 64 + t * 8;
            const float a = t ? mu1 : mu0, b = t ? q1 : q0, c = t ? d1 : d0;
            asm volatile("st.relaxed.gpu.global.v4.f32 [%0], {%1, %2, %3, %4};" ::"l"(dst), "f"(a), "f"(b), "f"(c), "f"(1.0f) : "memory");
        }
        const uint32_t stg_off = KF_OFF_WO + (wi >> 1) * 16384 + wg * 8192 + (wi & 1) * 4096;
        const uint32_t stg_o = sb + stg_off, stg_h = stg_o + 2048;
        const int srow = (lane & 7) + ((lane >> 3) & 1) * 8;
        const int sj = lane >> 4;
        named_sync(4 + wg, 128);
#pragma unroll
        for (int j = 0; j < 8; j += 2) {
            const uint32_t off = srow * 128 + (((j + sj) ^ (srow & 7)) << 4);
            stmatrix_x4(stg_h + off, pack_bf16(hv[4 * j], hv[4 * j + 1]), pack_bf16(hv[4 * j + 2], hv[4 * j + 3]),
                        pack_bf16(hv[4 * j + 4], hv[4 * j + 5]), pack_bf16(hv[4 * j + 6], hv[4 * j + 7]));
        }
        __syncwarp();
#pragma unroll
        for (int i = 0; i < 4; i++) {
            const int row = i * 4 + (lane >> 3), ch = lane & 7;
            const uint4 vh = *(const uint4*)(sp + stg_off + 2048 + row * 128 + ((ch ^ (row & 7)) << 4));
            *(uint4*)(g_h + (size_t)(mt * 64 + wi * 16 + row) * DM + cb + ch * 8) = vh;
        }
        named_sync(4 + wg, 128);
        if ((tid & 127) == 0) red_release_add(&g_hflag[mt]);
        float mean[2], den[2], rr[2];
        {
            float4 v[4];
            int spins = 0;
            while (true) {
#pragma unroll
                for (int i = 0; i < 4; i++) {
                    const float4* p = part + (t + (i & 1) * 4) * 64 + (i >> 1) * 8;
                    asm volatile("ld.relaxed.gpu.global.v4.f32 {%0, %1, %2, %3}, [%4];" : "=f"(v[i].x), "=f"(v[i].y), "=f"(v[i].z), "=f"(v[i].w) : "l"(p) : "memory");
                }
                const bool ok = (v[0].w != 0.f) && (v[1].w != 0.f) && (v[2].w != 0.f) && (v[3].w != 0.f);
                if (__all_sync(0xffffffffu, ok) || ++spins > (1 << 20)) break;
                __nanosleep(40);
            }
#pragma unroll
            for (int u = 0; u < 2; u++) {
                float mu = v[2 * u].x + v[2 * u + 1].x, m2 = v[2 * u].y + v[2 * u + 1].y, hw = v[2 * u].z + v[2 * u + 1].z;
#pragma unroll
                for (int o = 1; o < 4; o <<= 1) {
                    mu += __shfl_xor_sync(0xffffffffu, mu, o);
                    m2 += __shfl_xor_sync(0xffffffffu, m2, o);
                    hw += __shfl_xor_sync(0xffffffffu, hw, o);
                }
                mu *= 0.125f;
                const float da = v[2 * u].x - mu, db = v[2 * u + 1].x - mu;
                float dd = 64.f * (da * da + db * db);
#pragma unroll
                for (int o = 1; o < 4; o <<= 1) dd += __shfl_xor_sync(0xffffffffu, dd, o);
                m2 += dd;
                mean[u] = rbf(mu);
                den[u] = rbf(sqrtf(rbf(rbf(m2 * (1.f / DM)) + 1e-5f)));
                rr[u] = rbf((hw - mean[u] * wsum) / den[u]);
            }
        }
        if (tid == 0) TSTAMP0(2, 3);
        named_arrive(3, 512);
        if (nt == 0 && wg == 0) {
            float2* s_st = (float2*)(sp + KF_OFF_WO + 49152);
            if (t == 0) {
                s_key[wi * 16 + g] = ((unsigned long long)order_bits(rr[0]) << 32) | (uint32_t)(0x7FFFFFFF - (r0 + 1));
                s_key[wi * 16 + g + 8] = ((unsigned long long)order_bits(rr[1]) << 32) | (uint32_t)(0x7FFFFFFF - (r0 + 9));
                s_st[wi * 16 + g] = make_float2(mean[0], den[0]);
                s_st[wi * 16 + g + 8] = make_float2(mean[1], den[1]);
            }
            named_sync(4, 128);
            if (warp == 0) {
                unsigned long long a = s_key[lane], b = s_key[lane + 32];
                if (b > a) { const unsigned long long c = a; a = b; b = c; }
                warp_top2(a, b);
                if (lane < 2) {
                    const unsigned long long k = lane ? b : a;
                    const int tok1 = 0x7FFFFFFF - (int)(uint32_t)k;
                    const float2 st = s_st[(tok1 - 1) & 63];
                    asm volatile("st.relaxed.gpu.global.v4.u32 [%0], {%1, %2, %3, %4};" ::"l"(g_cand + mt * 2 + lane), "r"((uint32_t)(k >> 32)),
                                 "r"((uint32_t)tok1), "r"(__float_as_uint(st.x)), "r"(__float_as_uint(st.y)) : "memory");
                }
            }
        }
        const float i0 = 1.f / den[0], i1 = 1.f / den[1];
#pragma unroll
        for (int j = 0; j < 8; j += 2) {
            uint32_t ro[4];
#pragma unroll
            for (int u = 0; u < 2; u++) {
                const int jj = j + u;
                const float a = hv[4 * jj], b = hv[4 * jj + 1], c = hv[4 * jj + 2], d = hv[4 * jj + 3];
                const float na = rbf(rbf(a - mean[0]) * i0), nb = rbf(rbf(b - mean[0]) * i0);
                const float nc = rbf(rbf(c - mean[1]) * i1), nd = rbf(rbf(d - mean[1]) * i1);
                ro[2 * u] = pack_bf16(a + na, b + nb);
                ro[2 * u + 1] = pack_bf16(c + nc, d + nd);
            }
            const uint32_t off = srow * 128 + (((j + sj) ^ (srow & 7)) << 4);
            stmatrix_x4(stg_o + off, ro[0], ro[1], ro[2], ro[3]);
        }
        __syncwarp();
#pragma unroll
        for (int i = 0; i < 4; i++) {
            const int row = i * 4 + (lane >> 3), ch = lane & 7;
            const uint4 vo = *(const uint4*)(sp + stg_off + row * 128 + ((ch ^ (row & 7)) << 4));
            *(uint4*)(out + (size_t)(mt * 64 + wi * 16 + row) * DM + cb + ch * 8) = vo;
        }
        named_sync(4 + wg, 128);
        if ((tid & 127) == 0) red_release_add(&g_cnt);
        if (tid == 0) TSTAMP0(2, 4);
    } else {
        named_arrive(1, 512);
        const bool worker = blockIdx.x < FF / 16;
        const bool finisher = blockIdx.x == gridDim.x - 1;
        if (!worker && !finisher) { named_arrive(3, 512); return; }
        const int mtid = tid - 256, mwarp = mtid >> 5;
        const int f0 = blockIdx.x * 16;
        float* s_x = (float*)(sp + KF_OFF_WO + 49152 + 8192);
        uint32_t wd[16];
        if (worker) {
#pragma unroll
            for (int f = 0; f < 16; f++) wd[f] = __ldg((const uint32_t*)(w_down + (size_t)(f0 + f) * DM + 2 * mtid));
        }
        if (mtid == 0) TSTAMP0(3, 0);
        named_sync(3, 512);
        if (mwarp == 0) {
            uint4 ca, cb4;
            int spins = 0;
            while (true) {
                asm volatile("ld.relaxed.gpu.global.v4.u32 {%0, %1, %2, %3}, [%4];" : "=r"(ca.x), "=r"(ca.y), "=r"(ca.z), "=r"(ca.w) : "l"(g_cand + 2 * lane) : "memory");
                asm volatile("ld.relaxed.gpu.global.v4.u32 {%0, %1, %2, %3}, [%4];" : "=r"(cb4.x), "=r"(cb4.y), "=r"(cb4.z), "=r"(cb4.w) : "l"(g_cand + 2 * lane + 1) : "memory");
                const unsigned int hf = ld_acquire(&g_hflag[lane]);
                const bool ok = ca.y != 0 && cb4.y != 0 && hf >= 8u;
                if (__all_sync(0xffffffffu, ok) || ++spins > (1 << 20)) break;
                __nanosleep(40);
            }
            unsigned long long ka = cand_key(ca), kb = cand_key(cb4);
            const unsigned long long mya = ka, myb = kb;
            warp_top2(ka, kb);
            if (mya == ka) s_sel[0] = ca;
            if (myb == ka) s_sel[0] = cb4;
            if (mya == kb) s_sel[1] = ca;
            if (myb == kb) s_sel[1] = cb4;
        }
        named_sync(2, 256);
        if (mtid == 0) TSTAMP0(3, 1);
        int idx[2];
        float rv[2], hx[2][2], xo[2][2];
#pragma unroll
        for (int u = 0; u < 2; u++) {
            const uint4 c = s_sel[u];
            idx[u] = (int)c.y - 1;
            rv[u] = order_value(c.x);
            const float mean = __uint_as_float(c.z), inv = 1.f / __uint_as_float(c.w);
            const uint32_t ho = __ldcg((const uint32_t*)(g_h + (size_t)idx[u] * DM + 2 * mtid));
            hx[u][0] = bf_lo(ho); hx[u][1] = bf_hi(ho);
            xo[u][0] = rbf(rbf(hx[u][0] - mean) * inv); xo[u][1] = rbf(rbf(hx[u][1] - mean) * inv);
        }
        if (worker) {
            *(float2*)(s_x + 2 * mtid) = make_float2(xo[0][0], xo[0][1]);
            *(float2*)(s_x + 512 + 2 * mtid) = make_float2(xo[1][0], xo[1][1]);
            mbar_wait(gbar, 0);
            named_sync(2, 256);
            float acc[8];
#pragma unroll
            for (int i = 0; i < 8; i++) acc[i] = 0.f;
            const uint8_t* wbase = sp + (mwarp >> 2) * (4 * KF_CH_S) + 16384 + lane * 32 + (mwarp & 3) * 8;
#pragma unroll
            for (int k = 0; k < 16; k++) {
                const uint2 w = *(const uint2*)(wbase + (k >> 2) * KF_CH_S + (k & 3) * 1024);
                const float x0 = s_x[lane + 32 * k], x1 = s_x[512 + lane + 32 * k];
                const float w0 = bf_lo(w.x), w1 = bf_hi(w.x), w2 = bf_lo(w.y), w3 = bf_hi(w.y);
                acc[0] = fmaf(x0, w0, acc[0]); acc[1] = fmaf(x0, w1, acc[1]); acc[2] = fmaf(x0, w2, acc[2]); acc[3] = fmaf(x0, w3, acc[3]);
                acc[4] = fmaf(x1, w0, acc[4]); acc[5] = fmaf(x1, w1, acc[5]); acc[6] = fmaf(x1, w2, acc[6]); acc[7] = fmaf(x1, w3, acc[7]);
            }
#define KF_STEP(O, N)                                                          \
            {                                                                  \
                const bool up = (lane & (O)) != 0;                             \
                _Pragma("unroll") for (int i = 0; i < (N); i++) {              \
                    const float send = up ? acc[i] : acc[i + (N)];             \
                    const float keep = up ? acc[i + (N)] : acc[i];             \
                    acc[i] = keep + __shfl_xor_sync(0xffffffffu, send, (O));   \
                }                                                              \
            }
            KF_STEP(16, 4) KF_STEP(8, 2) KF_STEP(4, 1)
            acc[0] += __shfl_xor_sync(0xffffffffu, acc[0], 2);
            acc[0] += __shfl_xor_sync(0xffffffffu, acc[0], 1);
            if ((lane & 3) == 0) {
                const int v = ((lane & 16) ? 4 : 0) + ((lane & 8) ? 2 : 0) + ((lane & 4) ? 1 : 0);
                s_gu[(v >> 2) * 32 + mwarp * 4 + (v & 3)] = acc[0];
            }
            named_sync(2, 256);
            float y[2][2] = {{0.f, 0.f}, {0.f, 0.f}};
            {
                const int u = lane >> 4, c = lane & 15;
                const float gb = rbf(s_gu[u * 32 + c]);
                const float sg = rbf(gb / (1.f + __expf(-gb)));
                const float a = rbf(sg * rbf(s_gu[u * 32 + 16 + c]));
#pragma unroll
                for (int f = 0; f < 16; f++) {
                    const float a0 = __shfl_sync(0xffffffffu, a, f), a1 = __shfl_sync(0xffffffffu, a, 16 + f);
                    const float w0 = bf_lo(wd[f]), w1 = bf_hi(wd[f]);
                    y[0][0] = fmaf(a0, w0, y[0][0]); y[0][1] = fmaf(a0, w1, y[0][1]);
                    y[1][0] = fmaf(a1, w0, y[1][0]); y[1][1] = fmaf(a1, w1, y[1][1]);
                }
            }
#pragma unroll
            for (int u = 0; u < 2; u++)
                asm volatile("red.global.add.v2.f32 [%0], {%1, %2};" ::"l"(g_y + u * DM + 2 * mtid), "f"(y[u][0]), "f"(y[u][1]) : "memory");
            if (mtid == 0) TSTAMP0(3, 2);
            named_sync(2, 256);
            if (mtid == 0) red_release_add(&g_cnt);
            if (mtid == 0) TSTAMP0(3, 3);
        } else {
            if (mtid == 0) {
                int spins = 0;
                while (ld_acquire(&g_cnt) < (unsigned)(FF / 16 + 256) && ++spins < (1 << 20)) __nanosleep(40);
            }
            named_sync(2, 256);
#pragma unroll
            for (int u = 0; u < 2; u++) {
                const float2 yy = __ldcg((const float2*)(g_y + u * DM + 2 * mtid));
                const float sig = rbf(1.f / (1.f + __expf(-rv[u])));
                const float o0 = hx[u][0] + rbf(xo[u][0] + rbf(rbf(yy.x) * sig));
                const float o1 = hx[u][1] + rbf(xo[u][1] + rbf(rbf(yy.y) * sig));
                *(uint32_t*)(out + (size_t)idx[u] * DM + 2 * mtid) = pack_bf16(o0, o1);
            }
            if (mtid == 0) g_epoch = g_epoch + 1u;
            if (mtid == 0) TSTAMP0(3, 4);
        }
    }
}

typedef CUresult (*PFN_encodeTiled)(CUtensorMap*, CUtensorMapDataType, cuuint32_t, void*, const cuuint64_t*, const cuuint64_t*,
                                    const cuuint32_t*, const cuuint32_t*, CUtensorMapInterleave, CUtensorMapSwizzle,
                                    CUtensorMapL2promotion, CUtensorMapFloatOOBfill);

void make_map(PFN_encodeTiled enc, CUtensorMap* m, const void* ptr, uint64_t cols, uint64_t rows, uint32_t bcols, uint32_t brows) {
    cuuint64_t dims[2] = {cols, rows};
    cuuint64_t strides[1] = {cols * 2};
    cuuint32_t box[2] = {bcols, brows};
    cuuint32_t es[2] = {1, 1};
    enc(m, CU_TENSOR_MAP_DATA_TYPE_BFLOAT16, 2, const_cast<void*>(ptr), dims, strides, box, es, CU_TENSOR_MAP_INTERLEAVE_NONE,
        CU_TENSOR_MAP_SWIZZLE_128B, CU_TENSOR_MAP_L2_PROMOTION_L2_256B, CU_TENSOR_MAP_FLOAT_OOB_FILL_NONE);
}

void make_map3(PFN_encodeTiled enc, CUtensorMap* m, const void* ptr, uint64_t d0, uint64_t rows, uint64_t d2, uint64_t row_stride_bytes,
               uint64_t d2_stride_bytes, uint32_t b0, uint32_t b1, uint32_t b2) {
    cuuint64_t dims[3] = {d0, rows, d2};
    cuuint64_t strides[2] = {row_stride_bytes, d2_stride_bytes};
    cuuint32_t box[3] = {b0, b1, b2};
    cuuint32_t es[3] = {1, 1, 1};
    enc(m, CU_TENSOR_MAP_DATA_TYPE_BFLOAT16, 3, const_cast<void*>(ptr), dims, strides, box, es, CU_TENSOR_MAP_INTERLEAVE_NONE,
        CU_TENSOR_MAP_SWIZZLE_128B, CU_TENSOR_MAP_L2_PROMOTION_L2_256B, CU_TENSOR_MAP_FLOAT_OOB_FILL_NONE);
}

void make_map_plain(PFN_encodeTiled enc, CUtensorMap* m, const void* ptr, uint64_t cols, uint64_t rows, uint32_t bcols, uint32_t brows) {
    cuuint64_t dims[2] = {cols, rows};
    cuuint64_t strides[1] = {cols * 2};
    cuuint32_t box[2] = {bcols, brows};
    cuuint32_t es[2] = {1, 1};
    enc(m, CU_TENSOR_MAP_DATA_TYPE_BFLOAT16, 2, const_cast<void*>(ptr), dims, strides, box, es, CU_TENSOR_MAP_INTERLEAVE_NONE,
        CU_TENSOR_MAP_SWIZZLE_NONE, CU_TENSOR_MAP_L2_PROMOTION_NONE, CU_TENSOR_MAP_FLOAT_OOB_FILL_NONE);
}

template <typename... KArgs, typename... Args>
void launch(void (*kern)(KArgs...), int grid, int block, int smem, bool pdl, Args... args) {
    cudaLaunchConfig_t cfg = {};
    cfg.gridDim = dim3(grid);
    cfg.blockDim = dim3(block);
    cfg.dynamicSmemBytes = smem;
    cfg.stream = cudaStreamPerThread;
    cudaLaunchAttribute at[1];
    at[0].id = cudaLaunchAttributeProgrammaticStreamSerialization;
    at[0].val.programmaticStreamSerializationAllowed = 1;
    cfg.attrs = at;
    cfg.numAttrs = pdl ? 1 : 0;
    cudaLaunchKernelEx(&cfg, kern, KArgs(args)...);
}

}

extern "C" void kernel_launch(void* const* d_in, const int* in_sizes, int n_in, void* d_out, int out_size) {
    const __nv_bfloat16* x = (const __nv_bfloat16*)d_in[0];
    const __nv_bfloat16* wqkv = (const __nv_bfloat16*)d_in[1];
    const __nv_bfloat16* wo = (const __nv_bfloat16*)d_in[2];
    const __nv_bfloat16* w_r = (const __nv_bfloat16*)d_in[4];
    const __nv_bfloat16* w_gate = (const __nv_bfloat16*)d_in[5];
    const __nv_bfloat16* w_up = (const __nv_bfloat16*)d_in[6];
    const __nv_bfloat16* w_down = (const __nv_bfloat16*)d_in[7];
    __nv_bfloat16* out = (__nv_bfloat16*)d_out;

    static PFN_encodeTiled enc = nullptr;
    static void* g_o_ptr = nullptr;
    if (!enc) {
        cudaDriverEntryPointQueryResult qres;
        void* fn = nullptr;
        cudaGetDriverEntryPoint("cuTensorMapEncodeTiled", &fn, cudaEnableDefault, &qres);
        enc = (PFN_encodeTiled)fn;
        cudaGetSymbolAddress(&g_o_ptr, g_o);
        cudaFuncSetAttribute(k1_qkv, cudaFuncAttributeMaxDynamicSharedMemorySize, K1_SMEM);
        cudaFuncSetAttribute(kf_main, cudaFuncAttributeMaxDynamicSharedMemorySize, KF_SMEM);
    }
    CUtensorMap tm_x, tm_w, tm_o, tm_wo, tm_g, tm_u;
    make_map_plain(enc, &tm_g, w_gate, FF, DM, 16, 128);
    make_map_plain(enc, &tm_u, w_up, FF, DM, 16, 128);
    make_map(enc, &tm_x, x, DM, SEQ, 64, 128);
    make_map3(enc, &tm_w, wqkv, DM, DM, 3, 3 * DM * 2, DM * 2, 64, 64, 3);
    make_map3(enc, &tm_o, g_o_ptr, 64, SEQ, 8, DM * 2, 128, 64, 64, 2);
    make_map3(enc, &tm_wo, wo, 64, DM, 8, DM * 2, 128, 64, 64, 2);

    const bool pdl = true;
    launch(k1_qkv, 128, 544, K1_SMEM, false, tm_x, tm_w, x);
    launch(kf_main, 128, 512, KF_SMEM, pdl, tm_o, tm_wo, tm_g, tm_u, x, wo, w_r, w_gate, w_up, w_down, out);
}
```

```cpp
#include <cuda_runtime.h>
#include <cuda_bf16.h>
#include <cuda.h>
#include <stdint.h>

namespace {

constexpr int SEQ = 2048, DM = 512, NH = 32, FF = 1792;

__device__ __align__(1024) uint8_t g_q[NH * 2 * SEQ * 16];
__device__ __align__(1024) uint8_t g_kv[NH * 8 * 16384];
__device__ float g_norm[16 * NH * 3];
__device__ __align__(1024) __nv_bfloat16 g_o[SEQ * DM];
__device__ __align__(1024) __nv_bfloat16 g_h[SEQ * DM];
__device__ __align__(16) uint4 g_cand[64];
__device__ unsigned int g_oflag[32 * 32];
__device__ unsigned int g_hflag[32];
__device__ unsigned int g_sflag[32];
__device__ unsigned int g_act[FF];
__device__ unsigned int g_epoch;
__device__ __align__(16) float4 g_ln1[SEQ];
__device__ __align__(16) float4 g_part[32 * 8 * 64];

#define TSTAMP(K, I)
#define TSTAMP0(K, I)
__device__ __forceinline__ uint32_t smem_u32(const void* p) { return (uint32_t)__cvta_generic_to_shared(p); }
__device__ __forceinline__ void wg_fence() { asm volatile("wgmma.fence.sync.aligned;" ::: "memory"); }
__device__ __forceinline__ void wg_commit() { asm volatile("wgmma.commit_group.sync.aligned;" ::: "memory"); }
template <int N> __device__ __forceinline__ void wg_wait() { asm volatile("wgmma.wait_group.sync.aligned %0;" ::"n"(N) : "memory"); }
template <int N> __device__ __forceinline__ void fence_regs(float (&r)[N]) {
#pragma unroll
    for (int i = 0; i < N; i++) asm volatile("" : "+f"(r[i])::"memory");
}
__device__ __forceinline__ uint64_t make_desc(uint32_t addr, uint32_t lbo, uint32_t sbo, uint32_t swz) {
    uint64_t d = 0;
    d |= (uint64_t)((addr & 0x3FFFF) >> 4);
    d |= (uint64_t)((lbo & 0x3FFFF) >> 4) << 16;
    d |= (uint64_t)((sbo & 0x3FFFF) >> 4) << 32;
    d |= (uint64_t)swz << 62;
    return d;
}
__device__ __forceinline__ void mbar_init(uint32_t bar, uint32_t cnt) {
    asm volatile("mbarrier.init.shared::cta.b64 [%0], %1;" ::"r"(bar), "r"(cnt) : "memory");
}
__device__ __forceinline__ void mbar_expect_tx(uint32_t bar, uint32_t bytes) {
    asm volatile("mbarrier.arrive.expect_tx.shared::cta.b64 _, [%0], %1;" ::"r"(bar), "r"(bytes) : "memory");
}
__device__ __forceinline__ void mbar_arrive(uint32_t bar) {
    asm volatile("mbarrier.arrive.shared::cta.b64 _, [%0];" ::"r"(bar) : "memory");
}
__device__ __forceinline__ void mbar_wait(uint32_t bar, uint32_t parity) {
    asm volatile(
        "{\n.reg .pred p;\nWAIT_%=:\n"
        "mbarrier.try_wait.parity.shared::cta.b64 p, [%0], %1;\n"
        "@p bra DONE_%=;\nbra WAIT_%=;\nDONE_%=:\n}\n" ::"r"(bar), "r"(parity) : "memory");
}
__device__ __forceinline__ void bulk_g2s(uint32_t dst, const void* src, uint32_t bytes, uint32_t bar) {
    asm volatile("cp.async.bulk.shared::cluster.global.mbarrier::complete_tx::bytes [%0], [%1], %2, [%3];" ::"r"(dst),
                 "l"(src), "r"(bytes), "r"(bar) : "memory");
}
__device__ __forceinline__ void bulk_s2g(void* dst, uint32_t src, uint32_t bytes) {
    asm volatile("cp.async.bulk.global.shared::cta.bulk_group [%0], [%1], %2;" ::"l"(dst), "r"(src), "r"(bytes) : "memory");
}
__device__ __forceinline__ void tma_load_2d(uint32_t dst, const CUtensorMap* tm, int c0, int c1, uint32_t bar) {
    asm volatile("cp.async.bulk.tensor.2d.shared::cluster.global.mbarrier::complete_tx::bytes [%0], [%1, {%3, %4}], [%2];" ::"r"(dst),
                 "l"(tm), "r"(bar), "r"(c0), "r"(c1) : "memory");
}
__device__ __forceinline__ void tma_load_3d(uint32_t dst, const CUtensorMap* tm, int c0, int c1, int c2, uint32_t bar) {
    asm volatile("cp.async.bulk.tensor.3d.shared::cluster.global.mbarrier::complete_tx::bytes [%0], [%1, {%3, %4, %5}], [%2];" ::"r"(dst),
                 "l"(tm), "r"(bar), "r"(c0), "r"(c1), "r"(c2) : "memory");
}
__device__ __forceinline__ void tma_load_2d_mc(uint32_t dst, const CUtensorMap* tm, int c0, int c1, uint32_t bar, uint16_t mask) {
    asm volatile("cp.async.bulk.tensor.2d.shared::cluster.global.mbarrier::complete_tx::bytes.multicast::cluster [%0], [%1, {%3, %4}], [%2], %5;" ::"r"(dst),
                 "l"(tm), "r"(bar), "r"(c0), "r"(c1), "h"(mask) : "memory");
}
__device__ __forceinline__ void mbar_arrive_cluster(uint32_t bar, uint32_t cta) {
    asm volatile("{\n.reg .b32 ra;\nmapa.shared::cluster.u32 ra, %0, %1;\nmbarrier.arrive.release.cluster.shared::cluster.b64 _, [ra];\n}" ::"r"(bar), "r"(cta) : "memory");
}
__device__ __forceinline__ void cluster_sync() {
    asm volatile("barrier.cluster.arrive.release.aligned;\nbarrier.cluster.wait.acquire.aligned;" ::: "memory");
}
__device__ __forceinline__ void prefetch_l2(const void* p, uint32_t bytes) {
    asm volatile("cp.async.bulk.prefetch.L2.global [%0], %1;" ::"l"(p), "r"(bytes) : "memory");
}
__device__ __forceinline__ void fence_proxy_async() { asm volatile("fence.proxy.async.shared::cta;" ::: "memory"); }
__device__ __forceinline__ void fence_barrier_init() { asm volatile("fence.mbarrier_init.release.cluster;" ::: "memory"); }
__device__ __forceinline__ void pdl_launch() { asm volatile("griddepcontrol.launch_dependents;" ::: "memory"); }
__device__ __forceinline__ void pdl_wait() { asm volatile("griddepcontrol.wait;" ::: "memory"); }
__device__ __forceinline__ void named_sync(int id, int n) { asm volatile("bar.sync %0, %1;" ::"r"(id), "r"(n) : "memory"); }
__device__ __forceinline__ void named_arrive(int id, int n) { asm volatile("bar.arrive %0, %1;" ::"r"(id), "r"(n) : "memory"); }

__device__ __forceinline__ float ex2f(float x) { float y; asm("ex2.approx.ftz.f32 %0, %1;" : "=f"(y) : "f"(x)); return y; }
__device__ __forceinline__ uint32_t pack_bf16(float lo, float hi) {
    uint32_t r; asm("cvt.rn.bf16x2.f32 %0, %1, %2;" : "=r"(r) : "f"(hi), "f"(lo)); return r;
}
__device__ __forceinline__ float bf_lo(uint32_t v) { return __uint_as_float(v << 16); }
__device__ __forceinline__ float bf_hi(uint32_t v) { return __uint_as_float(v & 0xFFFF0000u); }
__device__ __forceinline__ float rbf(float x) { return __bfloat162float(__float2bfloat16_rn(x)); }
__device__ __forceinline__ uint32_t fma_bf16x2(uint32_t a, uint32_t b, uint32_t c) {
    uint32_t r; asm("fma.rn.bf16x2 %0, %1, %2, %3;" : "=r"(r) : "r"(a), "r"(b), "r"(c)); return r;
}
__device__ __forceinline__ void stmatrix_x4(uint32_t addr, uint32_t r0, uint32_t r1, uint32_t r2, uint32_t r3) {
    asm volatile("stmatrix.sync.aligned.m8n8.x4.shared.b16 [%0], {%1, %2, %3, %4};" ::"r"(addr), "r"(r0), "r"(r1), "r"(r2), "r"(r3) : "memory");
}
__device__ __forceinline__ void stmatrix_x4_trans(uint32_t addr, uint32_t r0, uint32_t r1, uint32_t r2, uint32_t r3) {
    asm volatile("stmatrix.sync.aligned.m8n8.x4.trans.shared.b16 [%0], {%1, %2, %3, %4};" ::"r"(addr), "r"(r0), "r"(r1), "r"(r2), "r"(r3) : "memory");
}

__device__ __forceinline__ void wgmma_k1_n136(float (&d)[68], uint64_t desca, uint64_t descb, int scale_d) {
  asm volatile("{\n.reg .pred p;\nsetp.ne.b32 p, %70, 0;\n"
    "wgmma.mma_async.sync.aligned.m64n136k16.f32.bf16.bf16 "
    "{%0, %1, %2, %3, %4, %5, %6, %7, %8, %9, %10, %11, %12, %13, %14, %15, %16, %17, %18, %19, %20, %21, %22, %23, %24, %25, %26, %27, %28, %29, %30, %31, %32, %33, %34, %35, %36, %37, %38, %39, %40, %41, %42, %43, %44, %45, %46, %47, %48, %49, %50, %51, %52, %53, %54, %55, %56, %57, %58, %59, %60, %61, %62, %63, %64, %65, %66, %67}, "
    "%68, %69, p, 1, 1, 1, 0;\n}\n"
    : "+f"(d[0]), "+f"(d[1]), "+f"(d[2]), "+f"(d[3]), "+f"(d[4]), "+f"(d[5]), "+f"(d[6]), "+f"(d[7]), "+f"(d[8]), "+f"(d[9]), "+f"(d[10]), "+f"(d[11]), "+f"(d[12]), "+f"(d[13]), "+f"(d[14]), "+f"(d[15]), "+f"(d[16]), "+f"(d[17]), "+f"(d[18]), "+f"(d[19]), "+f"(d[20]), "+f"(d[21]), "+f"(d[22]), "+f"(d[23]), "+f"(d[24]), "+f"(d[25]), "+f"(d[26]), "+f"(d[27]), "+f"(d[28]), "+f"(d[29]), "+f"(d[30]), "+f"(d[31]), "+f"(d[32]), "+f"(d[33]), "+f"(d[34]), "+f"(d[35]), "+f"(d[36]), "+f"(d[37]), "+f"(d[38]), "+f"(d[39]), "+f"(d[40]), "+f"(d[41]), "+f"(d[42]), "+f"(d[43]), "+f"(d[44]), "+f"(d[45]), "+f"(d[46]), "+f"(d[47]), "+f"(d[48]), "+f"(d[49]), "+f"(d[50]), "+f"(d[51]), "+f"(d[52]), "+f"(d[53]), "+f"(d[54]), "+f"(d[55]), "+f"(d[56]), "+f"(d[57]), "+f"(d[58]), "+f"(d[59]), "+f"(d[60]), "+f"(d[61]), "+f"(d[62]), "+f"(d[63]), "+f"(d[64]), "+f"(d[65]), "+f"(d[66]), "+f"(d[67])
    : "l"(desca), "l"(descb), "r"(scale_d));
}
__device__ __forceinline__ void wgmma_qk_n64(float (&d)[32], uint32_t a0, uint32_t a1, uint32_t a2, uint32_t a3, uint64_t descb) {
  asm volatile("{\n.reg .pred p;\nsetp.ne.b32 p, 0, 0;\n"
    "wgmma.mma_async.sync.aligned.m64n64k16.f32.bf16.bf16 "
    "{%0, %1, %2, %3, %4, %5, %6, %7, %8, %9, %10, %11, %12, %13, %14, %15, %16, %17, %18, %19, %20, %21, %22, %23, %24, %25, %26, %27, %28, %29, %30, %31}, "
    "{%32, %33, %34, %35}, %36, p, 1, 1, 0;\n}\n"
    : "=f"(d[0]), "=f"(d[1]), "=f"(d[2]), "=f"(d[3]), "=f"(d[4]), "=f"(d[5]), "=f"(d[6]), "=f"(d[7]), "=f"(d[8]), "=f"(d[9]), "=f"(d[10]), "=f"(d[11]), "=f"(d[12]), "=f"(d[13]), "=f"(d[14]), "=f"(d[15]), "=f"(d[16]), "=f"(d[17]), "=f"(d[18]), "=f"(d[19]), "=f"(d[20]), "=f"(d[21]), "=f"(d[22]), "=f"(d[23]), "=f"(d[24]), "=f"(d[25]), "=f"(d[26]), "=f"(d[27]), "=f"(d[28]), "=f"(d[29]), "=f"(d[30]), "=f"(d[31])
    : "r"(a0), "r"(a1), "r"(a2), "r"(a3), "l"(descb));
}
__device__ __forceinline__ void wgmma_pv_n24(float (&d)[12], uint32_t a0, uint32_t a1, uint32_t a2, uint32_t a3, uint64_t descb) {
  asm volatile("{\n.reg .pred p;\nsetp.eq.b32 p, 0, 0;\n"
    "wgmma.mma_async.sync.aligned.m64n24k16.f32.bf16.bf16 "
    "{%0, %1, %2, %3, %4, %5, %6, %7, %8, %9, %10, %11}, "
    "{%12, %13, %14, %15}, %16, p, 1, 1, 1;\n}\n"
    : "+f"(d[0]), "+f"(d[1]), "+f"(d[2]), "+f"(d[3]), "+f"(d[4]), "+f"(d[5]), "+f"(d[6]), "+f"(d[7]), "+f"(d[8]), "+f"(d[9]), "+f"(d[10]), "+f"(d[11])
    : "r"(a0), "r"(a1), "r"(a2), "r"(a3), "l"(descb));
}
__device__ __forceinline__ void wgmma_k3_n64(float (&d)[32], uint64_t desca, uint64_t descb, int scale_d) {
  asm volatile("{\n.reg .pred p;\nsetp.ne.b32 p, %34, 0;\n"
    "wgmma.mma_async.sync.aligned.m64n64k16.f32.bf16.bf16 "
    "{%0, %1, %2, %3, %4, %5, %6, %7, %8, %9, %10, %11, %12, %13, %14, %15, %16, %17, %18, %19, %20, %21, %22, %23, %24, %25, %26, %27, %28, %29, %30, %31}, "
    "%32, %33, p, 1, 1, 0, 1;\n}\n"
    : "+f"(d[0]), "+f"(d[1]), "+f"(d[2]), "+f"(d[3]), "+f"(d[4]), "+f"(d[5]), "+f"(d[6]), "+f"(d[7]), "+f"(d[8]), "+f"(d[9]), "+f"(d[10]), "+f"(d[11]), "+f"(d[12]), "+f"(d[13]), "+f"(d[14]), "+f"(d[15]), "+f"(d[16]), "+f"(d[17]), "+f"(d[18]), "+f"(d[19]), "+f"(d[20]), "+f"(d[21]), "+f"(d[22]), "+f"(d[23]), "+f"(d[24]), "+f"(d[25]), "+f"(d[26]), "+f"(d[27]), "+f"(d[28]), "+f"(d[29]), "+f"(d[30]), "+f"(d[31])
    : "l"(desca), "l"(descb), "r"(scale_d));
}

constexpr int K1_XS = 17408;
constexpr int K1_WS = 24576;
constexpr int K1_ST = K1_XS + K1_WS;
constexpr int K1_NST = 5;
constexpr int K1_OFF_MISC = K1_NST * K1_ST;
constexpr int K1_SMEM = K1_OFF_MISC + 2048 + 1024;
constexpr float QSCALE = 0.25f * 1.4426950408889634f;

__global__ void __launch_bounds__(544, 1)
k1_qkv(const __grid_constant__ CUtensorMap tm_x, const __grid_constant__ CUtensorMap tm_w, const __nv_bfloat16* __restrict__ x) {
    extern __shared__ uint8_t smem_raw[];
    const uint32_t sraw = smem_u32(smem_raw);
    const uint32_t sb = (sraw + 1023) & ~1023u;
    uint8_t* sp = smem_raw + (sb - sraw);
    const uint32_t full = sb + K1_OFF_MISC;
    const uint32_t empty = full + 64;
    float* s_m = (float*)(sp + K1_OFF_MISC + 256);
    float* s_r = s_m + 128;

    const int tid = threadIdx.x, warp = tid >> 5, lane = tid & 31;
    const int mt = blockIdx.x >> 3, nt = blockIdx.x & 7;
    if (tid == 0) TSTAMP0(0, 0);
    pdl_launch();
    if (tid == 512) {
        for (int i = 0; i < K1_NST; i++) { mbar_init(full + 8 * i, 1); mbar_init(empty + 8 * i, 3); }
        fence_barrier_init();
        for (int kb = 0; kb < K1_NST; kb++) {
            mbar_expect_tx(full + 8 * kb, 16384 + K1_WS);
            tma_load_2d(sb + kb * K1_ST, &tm_x, kb * 64, mt * 128, full + 8 * kb);
            tma_load_3d(sb + kb * K1_ST + K1_XS, &tm_w, nt * 64, kb * 64, 0, full + 8 * kb);
        }
    }
    if (tid < K1_NST * 64) {
        *(uint4*)(sp + (tid >> 6) * K1_ST + 16384 + (tid & 63) * 16) =
            make_uint4(0x3F803F80u, 0x3F803F80u, 0x3F803F80u, 0x3F803F80u);
    }
    fence_proxy_async();
    __syncthreads();

    if (warp == 16) {
        if (lane == 0) {
            for (int kb = K1_NST; kb < 8; kb++) {
                const int s = kb % K1_NST;
                mbar_wait(empty + 8 * s, 0);
                mbar_expect_tx(full + 8 * s, 16384 + K1_WS);
                tma_load_2d(sb + s * K1_ST, &tm_x, kb * 64, mt * 128, full + 8 * s);
                tma_load_3d(sb + s * K1_ST + K1_XS, &tm_w, nt * 64, kb * 64, 0, full + 8 * s);
            }
        }
        __syncwarp();
        if (lane < FF / 128) g_act[blockIdx.x * (FF / 128) + lane] = 0xFFFFFFFFu;
        for (int i = lane; i < 128; i += 32) g_part[blockIdx.x * 128 + i] = make_float4(0.f, 0.f, 0.f, 0.f);
        if (blockIdx.x == 1) { g_cand[lane] = make_uint4(0, 0, 0, 0); g_cand[lane + 32] = make_uint4(0, 0, 0, 0); g_oflag[lane * 32] = 0; g_hflag[lane] = 0; g_sflag[lane] = 0; }
    } else if (warp >= 12) {
        const int r = tid - 384;
        const unsigned int tag = *(volatile unsigned int*)&g_epoch + 1u;
        {
            const int row = mt * 128 + nt * 16 + (r >> 3);
            const uint4* xp = (const uint4*)(x + (size_t)row * DM) + (r & 7);
            uint4 v[8];
#pragma unroll
            for (int i = 0; i < 8; i++) v[i] = __ldg(xp + i * 8);
            float s1 = 0.f;
#pragma unroll
            for (int i = 0; i < 8; i++)
                s1 += ((bf_lo(v[i].x) + bf_hi(v[i].x)) + (bf_lo(v[i].y) + bf_hi(v[i].y))) + ((bf_lo(v[i].z) + bf_hi(v[i].z)) + (bf_lo(v[i].w) + bf_hi(v[i].w)));
#pragma unroll
            for (int o = 1; o < 8; o <<= 1) s1 += __shfl_xor_sync(0xffffffffu, s1, o);
            const float mean = s1 * (1.f / DM);
            float q0 = 0.f, q1 = 0.f;
#pragma unroll
            for (int i = 0; i < 8; i++) {
                const uint32_t w[4] = {v[i].x, v[i].y, v[i].z, v[i].w};
#pragma unroll
                for (int j = 0; j < 4; j++) {
                    const float a = bf_lo(w[j]) - mean, b = bf_hi(w[j]) - mean;
                    q0 = fmaf(a, a, q0); q1 = fmaf(b, b, q1);
                }
            }
            float q = q0 + q1;
#pragma unroll
            for (int o = 1; o < 8; o <<= 1) q += __shfl_xor_sync(0xffffffffu, q, o);
            const float den = rbf(sqrtf(rbf(rbf(q * (1.f / DM)) + 1e-5f)));
            if ((r & 7) == 0)
                asm volatile("st.relaxed.gpu.global.v4.f32 [%0], {%1, %2, %3, %4};" ::"l"(g_ln1 + row), "f"(rbf(mean)), "f"(1.f / den),
                             "f"(__uint_as_float(tag)), "f"(0.f) : "memory");
        }
        if (r == 0) TSTAMP0(0, 6);
        {
            float4 v;
            int spins = 0;
            do {
                asm volatile("ld.relaxed.gpu.global.v4.f32 {%0, %1, %2, %3}, [%4];" : "=f"(v.x), "=f"(v.y), "=f"(v.z), "=f"(v.w) : "l"(g_ln1 + mt * 128 + r) : "memory");
            } while (__float_as_uint(v.z) != tag && ++spins < (1 << 22));
            s_m[r] = v.x;
            s_r[r] = v.y;
        }
        if (r == 0) TSTAMP0(0, 7);
        named_arrive(1, 512);
    } else {
        const int part = warp >> 2, hw = warp & 3;
        float acc[68];
#pragma unroll
        for (int i = 0; i < 68; i++) acc[i] = 0.f;
        fence_regs(acc);
#pragma unroll 1
        for (int kb = 0; kb < 8; kb++) {
            const int s = kb % K1_NST;
            mbar_wait(full + 8 * s, (kb / K1_NST) & 1);
            const uint64_t da = make_desc(sb + s * K1_ST + K1_XS + part * 8192, 1024, 1024, 1);
            const uint64_t db = make_desc(sb + s * K1_ST, 16, 1024, 1);
            wg_fence();
#pragma unroll
            for (int k = 0; k < 4; k++) wgmma_k1_n136(acc, da + k * 128, db + k * 2, (kb | k) != 0);
            wg_commit();
            if (kb > 0 && kb <= 8 - K1_NST) {
                wg_wait<1>();
                if ((tid & 127) == 0) mbar_arrive(empty + 8 * (kb - 1));
            }
        }
        wg_wait<0>();
        fence_regs(acc);
        if (tid == 0) TSTAMP0(0, 1);
        named_sync(1, 512);
        if (tid == 0) TSTAMP0(0, 2);

        const int t = lane & 3;
        const float cs0 = acc[64], cs1 = acc[66];
        const float sc = (part == 0) ? QSCALE : 1.f;
        const uint32_t stg = sb + (hw >> 1) * K1_ST + K1_XS + part * 8192 + (hw & 1) * 4096;
        const uint32_t st_addr = stg + ((lane >> 3) & 1) * 2048 + ((lane >> 4) * 8 + (lane & 7)) * 16;
#pragma unroll
        for (int j = 0; j < 16; j += 2) {
            uint32_t rr[4];
#pragma unroll
            for (int u = 0; u < 2; u++) {
                const int jj = j + u;
                const float2 m2 = *(const float2*)(s_m + 8 * jj + 2 * t);
                const float2 r2 = *(const float2*)(s_r + 8 * jj + 2 * t);
                const float ra = r2.x * sc, rb = r2.y * sc;
                rr[2 * u] = pack_bf16((acc[4 * jj] - m2.x * cs0) * ra, (acc[4 * jj + 1] - m2.y * cs0) * rb);
                rr[2 * u + 1] = pack_bf16((acc[4 * jj + 2] - m2.x * cs1) * ra, (acc[4 * jj + 3] - m2.y * cs1) * rb);
            }
            stmatrix_x4_trans(st_addr + j * 128, rr[0], rr[1], rr[2], rr[3]);
        }
        fence_proxy_async();
        __syncwarp();
        if (tid == 0) TSTAMP0(0, 4);
        const int head = nt * 4 + hw;
        if (lane == 0) {
            uint8_t* dst;
            uint32_t hstride;
            if (part == 0) { dst = g_q + (size_t)head * 65536 + mt * 2048; hstride = 32768; }
            else { dst = g_kv + (size_t)head * 131072 + (mt >> 1) * 16384 + (part - 1) * 8192 + (mt & 1) * 2048; hstride = 4096; }
            bulk_s2g(dst, stg, 2048);
            bulk_s2g(dst + hstride, stg + 2048, 2048);
            asm volatile("cp.async.bulk.commit_group;" ::: "memory");
        }
        float nmax = 0.f;
#pragma unroll
        for (int i = 0; i < 4; i++) {
            const int tok = lane + 32 * i;
            const uint4 a = *(const uint4*)(sp + (stg - sb) + tok * 16);
            const uint4 b = *(const uint4*)(sp + (stg - sb) + 2048 + tok * 16);
            const uint32_t w[8] = {a.x, a.y, a.z, a.w, b.x, b.y, b.z, b.w};
            float n2 = 0.f, n3 = 0.f;
#pragma unroll
            for (int q = 0; q < 8; q++) {
                const float lo = bf_lo(w[q]), hi = bf_hi(w[q]);
                n2 = fmaf(lo, lo, n2); n3 = fmaf(hi, hi, n3);
            }
            n2 += n3;
            nmax = (n2 > nmax || n2 != n2) ? n2 : nmax;
        }
#pragma unroll
        for (int o = 16; o > 0; o >>= 1) {
            const float v = __shfl_xor_sync(0xffffffffu, nmax, o);
            nmax = (v > nmax || v != v) ? v : nmax;
        }
        if (tid == 0) TSTAMP0(0, 5);
        if (lane == 0) {
            g_norm[(mt * NH + head) * 3 + part] = nmax;
            asm volatile("cp.async.bulk.wait_group.read 0;" ::: "memory");
            if (tid == 0) TSTAMP0(0, 3);
        }
    }
}

constexpr int KF_CH_G = 16384, KF_CH_S = 20480, KF_NCH = 8;
constexpr int KF_OFF_WO = KF_NCH * KF_CH_S;
constexpr int KF_OFF_MISC = KF_OFF_WO + 65536;
constexpr int KF_SMEM = KF_OFF_MISC + 1280 + 1024;

__device__ __forceinline__ uint32_t exp2_pair_poly(float s0, float s1) {
    const float KB = 65536.0f + 127.0f;
    const float t0 = s0 + KB, t1 = s1 + KB;
    const uint32_t w = __byte_perm(__float_as_uint(t0), __float_as_uint(t1), 0x5410);
    uint32_t z;
    asm("lop3.b32 %0, %1, %2, %3, 0xEA;" : "=r"(z) : "r"(w), "r"(0x007F007Fu), "r"(0x3F803F80u));
    uint32_t p = fma_bf16x2(0x3eab3eabu, z, 0xbc73bc73u);
    p = fma_bf16x2(p, z, 0x3f2f3f2fu);
    return p + w - z;
}
constexpr uint32_t KF_EMASK = 0x5757u;
template <int LO, int HI>
__device__ __forceinline__ void softmax_part(const float (&s)[32], uint32_t (&p)[16]) {
#pragma unroll
    for (int i = LO; i < HI; i++) {
        if ((KF_EMASK >> i) & 1) p[i] = exp2_pair_poly(s[2 * i], s[2 * i + 1]);
        else p[i] = pack_bf16(ex2f(s[2 * i]), ex2f(s[2 * i + 1]));
    }
}
#define KF_PV(P, OFF)                                                                              \
    _Pragma("unroll") for (int kk = 0; kk < 4; kk++)                                               \
        wgmma_pv_n24(o, P[4 * kk], P[4 * kk + 1], P[4 * kk + 2], P[4 * kk + 3], dv + ((OFF) + kk * 16));

__device__ __forceinline__ unsigned long long cand_key(const uint4& c) {
    return ((unsigned long long)c.x << 32) | (uint32_t)(0x7FFFFFFF - (int)c.y);
}
__device__ __forceinline__ uint32_t order_bits(float v) {
    const uint32_t u = __float_as_uint(v);
    return (u & 0x80000000u) ? ~u : (u | 0x80000000u);
}
__device__ __forceinline__ float order_value(uint32_t u) {
    return __uint_as_float((u & 0x80000000u) ? (u & 0x7FFFFFFFu) : ~u);
}
__device__ __forceinline__ void warp_top2(unsigned long long& a, unsigned long long& b) {
#pragma unroll
    for (int o = 16; o > 0; o >>= 1) {
        const unsigned long long c = __shfl_xor_sync(0xffffffffu, a, o);
        const unsigned long long d = __shfl_xor_sync(0xffffffffu, b, o);
        const unsigned long long hi = a > c ? a : c, lo = a > c ? c : a;
        const unsigned long long m = b > d ? b : d;
        a = hi;
        b = lo > m ? lo : m;
    }
}
__device__ __forceinline__ unsigned int ld_acquire(const unsigned int* p) {
    unsigned int v; asm volatile("ld.acquire.gpu.global.u32 %0, [%1];" : "=r"(v) : "l"(p) : "memory"); return v;
}
__device__ __forceinline__ void red_release_add(unsigned int* p) {
    asm volatile("red.release.gpu.global.add.u32 [%0], 1;" ::"l"(p) : "memory");
}

__global__ void __launch_bounds__(512, 1)
kf_main(const __grid_constant__ CUtensorMap tm_o, const __grid_constant__ CUtensorMap tm_wo,
        const __grid_constant__ CUtensorMap tm_g, const __grid_constant__ CUtensorMap tm_u, const __grid_constant__ CUtensorMap tm_d,
        const __nv_bfloat16* __restrict__ x, const __nv_bfloat16* __restrict__ wo, const __nv_bfloat16* __restrict__ w_r,
        const __nv_bfloat16* __restrict__ w_gate, const __nv_bfloat16* __restrict__ w_up, const __nv_bfloat16* __restrict__ w_down,
        __nv_bfloat16* __restrict__ out) {
    extern __shared__ uint8_t smem_raw[];
    const uint32_t sraw = smem_u32(smem_raw);
    const uint32_t sb = (sraw + 1023) & ~1023u;
    uint8_t* sp = smem_raw + (sb - sraw);
    const uint32_t kvbar = sb + KF_OFF_MISC;
    const uint32_t wbar = kvbar + 64;
    const uint32_t obar = wbar + 64;
    const uint32_t gbar = obar + 32;
    const uint32_t dbar = gbar + 8;
    unsigned int* s_cnt = (unsigned int*)(sp + KF_OFF_MISC + 192);
    unsigned long long* s_key = (unsigned long long*)(sp + KF_OFF_MISC + 256);
    float* s_gu = (float*)(sp + KF_OFF_MISC + 768);
    uint4* s_sel = (uint4*)(sp + KF_OFF_MISC + 1024);
    const int tid = threadIdx.x;
    const int head = blockIdx.x >> 2, quarter = blockIdx.x & 3;
    const int mt = blockIdx.x >> 2, nt = blockIdx.x & 3;
    if (tid == 0) TSTAMP0(1, 0);
    if (tid == 0) {
        for (int c = 0; c < 22; c++) mbar_init(kvbar + 8 * c, 1);
        for (int c = 0; c < 4; c++) s_cnt[c] = 0;
        fence_barrier_init();
        for (int kb = 0; kb < 4; kb++) {
            mbar_expect_tx(wbar + 8 * kb, 16384);
            tma_load_3d(sb + KF_OFF_WO + kb * 16384, &tm_wo, 0, kb * 64, nt * 2, wbar + 8 * kb);
        }
    }
    if (tid == 32) {
        prefetch_l2((const uint8_t*)wo + blockIdx.x * 4096, 4096);
        prefetch_l2((const uint8_t*)w_gate + blockIdx.x * 14336, 14336);
        prefetch_l2((const uint8_t*)w_up + blockIdx.x * 14336, 14336);
        prefetch_l2((const uint8_t*)w_down + blockIdx.x * 14336, 14336);
    }
    for (int i = tid; i < KF_NCH * 256; i += 512)
        *(uint4*)(sp + (i >> 8) * KF_CH_S + 16384 + (i & 255) * 16) =
            make_uint4(0x3F803F80u, 0x3F803F80u, 0x3F803F80u, 0x3F803F80u);
    fence_proxy_async();
    __syncthreads();
    pdl_wait();
    if (tid == 0) TSTAMP0(1, 1);
    if (tid == 0) {
        const uint8_t* src = g_kv + (size_t)head * (KF_NCH * KF_CH_G);
        for (int c = 0; c < KF_NCH; c++) {
            mbar_expect_tx(kvbar + 8 * c, KF_CH_G);
            bulk_g2s(sb + c * KF_CH_S, src + c * KF_CH_G, KF_CH_G, kvbar + 8 * c);
        }
    }
    const int wg = tid >> 7, warp = (tid >> 5) & 3, lane = tid & 31, g = lane >> 2, t = lane & 3;
    uint32_t qn2[2][4];
#pragma unroll
    for (int ps = 0; ps < 2; ps++) {
        const uint8_t* qb = g_q + (size_t)head * 65536 + (quarter * 512 + ps * 256 + wg * 64 + warp * 16 + g) * 16 + t * 4;
        qn2[ps][0] = *(const uint32_t*)(qb);
        qn2[ps][1] = *(const uint32_t*)(qb + 128);
        qn2[ps][2] = *(const uint32_t*)(qb + 32768);
        qn2[ps][3] = *(const uint32_t*)(qb + 32768 + 128);
    }

    bool fast;
    {
        const int m16 = lane & 15;
        float kn = g_norm[(m16 * NH + head) * 3 + 1];
        float vn = g_norm[(m16 * NH + head) * 3 + 2];
        float qn = g_norm[((quarter * 4 + (lane & 3)) * NH + head) * 3 + 0];
        bool bad = !(kn < 1e30f) || !(vn < 1e30f) || !(qn < 1e30f);
#pragma unroll
        for (int o = 8; o > 0; o >>= 1) {
            kn = fmaxf(kn, __shfl_xor_sync(0xffffffffu, kn, o));
            qn = fmaxf(qn, __shfl_xor_sync(0xffffffffu, qn, o));
        }
        fast = __all_sync(0xffffffffu, !bad && (qn * kn <= 3500.f));
    }
    const uint64_t dk0 = make_desc(sb, 4096, 128, 0);
    const uint64_t dv0 = make_desc(sb + 8192, 128, 4096, 0);

#pragma unroll 1
    for (int pass = 0; pass < 2; pass++) {
        const int row0 = quarter * 512 + pass * 256 + wg * 64 + warp * 16 + g;
        uint32_t qa[4];
#pragma unroll
        for (int i = 0; i < 4; i++) qa[i] = pass ? qn2[1][i] : qn2[0][i];
        float o[12];
#pragma unroll
        for (int i = 0; i < 12; i++) o[i] = 0.f;
        fence_regs(o);
#define KF_RELEASE_CHUNK(c)                                                                          \
        if (pass == 1 && (c) >= 1 && (c) <= 4) {                                                     \
            named_sync(4 + wg, 128);            \
            if ((tid & 127) == 0 && atomicAdd(&s_cnt[(c) - 1], 1u) == 3u) {                          \
                mbar_expect_tx(wbar + 8 * (3 + (c)), 16384);                                         \
                tma_load_3d(sb + ((c) - 1) * KF_CH_S, &tm_wo, 0, (3 + (c)) * 64, nt * 2, wbar + 8 * (3 + (c))); \
            }                                                                                        \
        }
        if (fast) {
#pragma unroll 1
            for (int c = 0; c < KF_NCH; c++) {
                const uint64_t dk = dk0 + (uint64_t)(c * (KF_CH_S >> 4));
                const uint64_t dv = dv0 + (uint64_t)(c * (KF_CH_S >> 4));
                float s0[32], s1[32], s2[32], s3[32];
                uint32_t p0[16], p1[16], p2[16], p3[16];
                mbar_wait(kvbar + 8 * c, 0);
                wg_wait<1>();
                wg_fence();
                wgmma_qk_n64(s0, qa[0], qa[1], qa[2], qa[3], dk);
                wg_commit();
                wg_wait<1>();
                KF_RELEASE_CHUNK(c);
                wg_fence();
                wgmma_qk_n64(s1, qa[0], qa[1], qa[2], qa[3], dk + 64);
                wg_commit();
                wg_wait<1>();
                fence_regs(s0);
                softmax_part<0, 16>(s0, p0);
                wg_fence();
                KF_PV(p0, 0);
                wg_commit();
                wg_wait<1>();
                fence_regs(s1);
                softmax_part<0, 8>(s1, p1);
                wg_wait<0>();
                wg_fence();
                wgmma_qk_n64(s2, qa[0], qa[1], qa[2], qa[3], dk + 128);
                wg_commit();
                softmax_part<8, 16>(s1, p1);
                wg_fence();
                KF_PV(p1, 64);
                wg_commit();
                wg_wait<1>();
                fence_regs(s2);
                softmax_part<0, 8>(s2, p2);
                wg_wait<0>();
                wg_fence();
                wgmma_qk_n64(s3, qa[0], qa[1], qa[2], qa[3], dk + 192);
                wg_commit();
                softmax_part<8, 16>(s2, p2);
                wg_fence();
                KF_PV(p2, 128);
                wg_commit();
                wg_wait<1>();
                fence_regs(s3);
                softmax_part<0, 16>(s3, p3);
                wg_fence();
                KF_PV(p3, 192);
                wg_commit();
            }
            wg_wait<0>();
            fence_regs(o);
        } else {
            float m0 = -INFINITY, m1 = -INFINITY;
#pragma unroll 1
            for (int b = 0; b < 32; b++) {
                const int c = b >> 2;
                const uint64_t dk = dk0 + (uint64_t)(c * (KF_CH_S >> 4) + (b & 3) * 64);
                const uint64_t dv = dv0 + (uint64_t)(c * (KF_CH_S >> 4) + (b & 3) * 64);
                float s[32];
                uint32_t p[16];
                mbar_wait(kvbar + 8 * c, 0);
                wg_fence();
                wgmma_qk_n64(s, qa[0], qa[1], qa[2], qa[3], dk);
                wg_commit();
                if ((b & 3) == 0) { KF_RELEASE_CHUNK(c); }
                wg_wait<0>();
                fence_regs(s);
                float x0 = s[0], x1 = s[2];
#pragma unroll
                for (int j = 0; j < 8; j++) {
                    x0 = fmaxf(x0, fmaxf(s[4 * j], s[4 * j + 1]));
                    x1 = fmaxf(x1, fmaxf(s[4 * j + 2], s[4 * j + 3]));
                }
                x0 = fmaxf(x0, __shfl_xor_sync(0xffffffffu, x0, 1));
                x0 = fmaxf(x0, __shfl_xor_sync(0xffffffffu, x0, 2));
                x1 = fmaxf(x1, __shfl_xor_sync(0xffffffffu, x1, 1));
                x1 = fmaxf(x1, __shfl_xor_sync(0xffffffffu, x1, 2));
                const float n0 = fmaxf(m0, x0), n1 = fmaxf(m1, x1);
                const float c0 = ex2f(m0 - n0), c1 = ex2f(m1 - n1);
                m0 = n0; m1 = n1;
#pragma unroll
                for (int j = 0; j < 3; j++) {
                    o[4 * j] *= c0; o[4 * j + 1] *= c0; o[4 * j + 2] *= c1; o[4 * j + 3] *= c1;
                }
#pragma unroll
                for (int j = 0; j < 8; j++) {
                    p[2 * j] = pack_bf16(ex2f(s[4 * j] - n0), ex2f(s[4 * j + 1] - n0));
                    p[2 * j + 1] = pack_bf16(ex2f(s[4 * j + 2] - n1), ex2f(s[4 * j + 3] - n1));
                }
                fence_regs(o);
                wg_fence();
                KF_PV(p, 0);
                wg_commit();
                wg_wait<0>();
                fence_regs(o);
            }
        }
        const float inv0 = 1.f / o[8], inv1 = 1.f / o[10];
        {
            uint32_t v0 = pack_bf16(o[0] * inv0, o[1] * inv0), v1 = pack_bf16(o[4] * inv0, o[5] * inv0);
            uint32_t v2 = pack_bf16(o[2] * inv1, o[3] * inv1), v3 = pack_bf16(o[6] * inv1, o[7] * inv1);
            const bool o1 = t & 1, o2 = t & 2;
            uint32_t s0 = o1 ? v0 : v1, s1 = o1 ? v2 : v3;
            s0 = __shfl_xor_sync(0xffffffffu, s0, 1); s1 = __shfl_xor_sync(0xffffffffu, s1, 1);
            uint32_t a0 = o1 ? s0 : v0, a1 = o1 ? v1 : s0, b0 = o1 ? s1 : v2, b1 = o1 ? v3 : s1;
            uint32_t x0 = o2 ? a0 : b0, x1 = o2 ? a1 : b1;
            x0 = __shfl_xor_sync(0xffffffffu, x0, 2); x1 = __shfl_xor_sync(0xffffffffu, x1, 2);
            uint4 r;
            r.x = o2 ? x0 : a0; r.y = o2 ? x1 : a1; r.z = o2 ? b0 : x0; r.w = o2 ? b1 : x1;
            *(uint4*)(g_o + (size_t)(row0 + (t >> 1) * 8) * DM + head * 16 + (t & 1) * 8) = r;
        }
        named_sync(4 + wg, 128);
        if ((tid & 127) == 0) red_release_add(&g_oflag[(quarter * 8 + pass * 4 + wg) * 32]);
        if (tid == 0) TSTAMP0(1, 2 + pass);
    }

    if (wg < 2) {
        const int wi = warp;
        const int r0 = mt * 64 + wi * 16 + g;
        const int cb = nt * 128 + wg * 64;
        uint32_t xr[16], wr[8];
#pragma unroll
        for (int j = 0; j < 8; j++) {
            xr[2 * j] = __ldg((const uint32_t*)(x + (size_t)r0 * DM + cb + 8 * j + 2 * t));
            xr[2 * j + 1] = __ldg((const uint32_t*)(x + (size_t)(r0 + 8) * DM + cb + 8 * j + 2 * t));
            wr[j] = __ldg((const uint32_t*)(w_r + cb + 8 * j + 2 * t));
        }
        if (tid == 0) {
            int spins = 0;
            while (ld_acquire(&g_oflag[mt * 32]) < 32u && ++spins < (1 << 20)) __nanosleep(64);
        }
        named_sync(1, 512);
        if (tid == 128 && blockIdx.x < FF / 16) {
            mbar_expect_tx(gbar, 32768);
            for (int i = 0; i < 4; i++) {
                tma_load_2d(sb + i * KF_CH_S + 16384, &tm_g, blockIdx.x * 16, i * 128, gbar);
                tma_load_2d(sb + (4 + i) * KF_CH_S + 16384, &tm_u, blockIdx.x * 16, i * 128, gbar);
            }
        }
        if (tid == 0) {
            asm volatile("fence.proxy.async;" ::: "memory");
            TSTAMP0(2, 1);
            for (int k2 = 0; k2 < 4; k2++) {
                mbar_expect_tx(obar + 8 * k2, 16384);
                tma_load_3d(sb + (4 + k2) * KF_CH_S, &tm_o, 0, mt * 64, k2 * 2, obar + 8 * k2);
            }
        }
        float wsum = 0.f;
        {
            const uint4 a = __ldg((const uint4*)(w_r + lane * 16)), b = __ldg((const uint4*)(w_r + lane * 16 + 8));
            const uint32_t w[8] = {a.x, a.y, a.z, a.w, b.x, b.y, b.z, b.w};
#pragma unroll
            for (int i = 0; i < 8; i++) wsum += bf_lo(w[i]) + bf_hi(w[i]);
#pragma unroll
            for (int o = 16; o > 0; o >>= 1) wsum += __shfl_xor_sync(0xffffffffu, wsum, o);
        }
        float acc[32];
#pragma unroll
        for (int i = 0; i < 32; i++) acc[i] = 0.f;
        fence_regs(acc);
#pragma unroll 1
        for (int kb = 0; kb < 8; kb++) {
            mbar_wait(wbar + 8 * kb, 0);
            mbar_wait(obar + 8 * (kb >> 1), 0);
            const uint32_t wa = (kb < 4) ? (KF_OFF_WO + kb * 16384) : ((kb - 4) * KF_CH_S);
            const uint64_t da = make_desc(sb + (4 + (kb >> 1)) * KF_CH_S + (kb & 1) * 8192, 16, 1024, 1);
            const uint64_t db = make_desc(sb + wa + wg * 8192, 1024, 1024, 1);
            wg_fence();
#pragma unroll
            for (int k = 0; k < 4; k++) wgmma_k3_n64(acc, da + k * 2, db + k * 128, (kb | k) != 0);
            wg_commit();
        }
        wg_wait<0>();
        fence_regs(acc);
        if (tid == 0) TSTAMP0(2, 2);
        float hv[32];
        float s0 = 0.f, s1 = 0.f, d0 = 0.f, d1 = 0.f;
#pragma unroll
        for (int j = 0; j < 8; j++) {
            hv[4 * j] = rbf(bf_lo(xr[2 * j]) + rbf(acc[4 * j]));
            hv[4 * j + 1] = rbf(bf_hi(xr[2 * j]) + rbf(acc[4 * j + 1]));
            hv[4 * j + 2] = rbf(bf_lo(xr[2 * j + 1]) + rbf(acc[4 * j + 2]));
            hv[4 * j + 3] = rbf(bf_hi(xr[2 * j + 1]) + rbf(acc[4 * j + 3]));
            const float wl = bf_lo(wr[j]), wh = bf_hi(wr[j]);
            s0 += hv[4 * j] + hv[4 * j + 1];
            s1 += hv[4 * j + 2] + hv[4 * j + 3];
            d0 = fmaf(hv[4 * j], wl, fmaf(hv[4 * j + 1], wh, d0));
            d1 = fmaf(hv[4 * j + 2], wl, fmaf(hv[4 * j + 3], wh, d1));
        }
#pragma unroll
        for (int o = 1; o < 4; o <<= 1) {
            s0 += __shfl_xor_sync(0xffffffffu, s0, o);
            s1 += __shfl_xor_sync(0xffffffffu, s1, o);
            d0 += __shfl_xor_sync(0xffffffffu, d0, o);
            d1 += __shfl_xor_sync(0xffffffffu, d1, o);
        }
        const float mu0 = s0 * (1.f / 64), mu1 = s1 * (1.f / 64);
        float q0 = 0.f, q1 = 0.f;
#pragma unroll
        for (int j = 0; j < 8; j++) {
            float a = hv[4 * j] - mu0, b = hv[4 * j + 1] - mu0, c = hv[4 * j + 2] - mu1, d = hv[4 * j + 3] - mu1;
            q0 = fmaf(a, a, fmaf(b, b, q0));
            q1 = fmaf(c, c, fmaf(d, d, q1));
        }
#pragma unroll
        for (int o = 1; o < 4; o <<= 1) {
            q0 += __shfl_xor_sync(0xffffffffu, q0, o);
            q1 += __shfl_xor_sync(0xffffffffu, q1, o);
        }
        float4* part = g_part + (size_t)mt * 512 + wi * 16 + g;
        if (t < 2) {
            float4* dst = part + (nt * 2 + wg) * 64 + t * 8;
            const float a = t ? mu1 : mu0, b = t ? q1 : q0, c = t ? d1 : d0;
            asm volatile("st.relaxed.gpu.global.v4.f32 [%0], {%1, %2, %3, %4};" ::"l"(dst), "f"(a), "f"(b), "f"(c), "f"(1.0f) : "memory");
        }
        const uint32_t stg_off = KF_OFF_WO + (wi >> 1) * 16384 + wg * 8192 + (wi & 1) * 4096;
        const uint32_t stg_o = sb + stg_off, stg_h = stg_o + 2048;
        const int srow = (lane & 7) + ((lane >> 3) & 1) * 8;
        const int sj = lane >> 4;
        named_sync(4 + wg, 128);
#pragma unroll
        for (int j = 0; j < 8; j += 2) {
            const uint32_t off = srow * 128 + (((j + sj) ^ (srow & 7)) << 4);
            stmatrix_x4(stg_h + off, pack_bf16(hv[4 * j], hv[4 * j + 1]), pack_bf16(hv[4 * j + 2], hv[4 * j + 3]),
                        pack_bf16(hv[4 * j + 4], hv[4 * j + 5]), pack_bf16(hv[4 * j + 6], hv[4 * j + 7]));
        }
        __syncwarp();
#pragma unroll
        for (int i = 0; i < 4; i++) {
            const int row = i * 4 + (lane >> 3), ch = lane & 7;
            const uint4 vh = *(const uint4*)(sp + stg_off + 2048 + row * 128 + ((ch ^ (row & 7)) << 4));
            *(uint4*)(g_h + (size_t)(mt * 64 + wi * 16 + row) * DM + cb + ch * 8) = vh;
        }
        named_arrive(8, 288);
        float mean[2], den[2], rr[2];
        {
            float4 v[4];
            int spins = 0;
            while (true) {
#pragma unroll
                for (int i = 0; i < 4; i++) {
                    const float4* p = part + (t + (i & 1) * 4) * 64 + (i >> 1) * 8;
                    asm volatile("ld.relaxed.gpu.global.v4.f32 {%0, %1, %2, %3}, [%4];" : "=f"(v[i].x), "=f"(v[i].y), "=f"(v[i].z), "=f"(v[i].w) : "l"(p) : "memory");
                }
                const bool ok = (v[0].w != 0.f) && (v[1].w != 0.f) && (v[2].w != 0.f) && (v[3].w != 0.f);
                if (__all_sync(0xffffffffu, ok) || ++spins > (1 << 20)) break;
                __nanosleep(40);
            }
#pragma unroll
            for (int u = 0; u < 2; u++) {
                float mu = v[2 * u].x + v[2 * u + 1].x, m2 = v[2 * u].y + v[2 * u + 1].y, hw = v[2 * u].z + v[2 * u + 1].z;
#pragma unroll
                for (int o = 1; o < 4; o <<= 1) {
                    mu += __shfl_xor_sync(0xffffffffu, mu, o);
                    m2 += __shfl_xor_sync(0xffffffffu, m2, o);
                    hw += __shfl_xor_sync(0xffffffffu, hw, o);
                }
                mu *= 0.125f;
                const float da = v[2 * u].x - mu, db = v[2 * u + 1].x - mu;
                float dd = 64.f * (da * da + db * db);
#pragma unroll
                for (int o = 1; o < 4; o <<= 1) dd += __shfl_xor_sync(0xffffffffu, dd, o);
                m2 += dd;
                mean[u] = rbf(mu);
                den[u] = rbf(sqrtf(rbf(rbf(m2 * (1.f / DM)) + 1e-5f)));
                rr[u] = rbf((hw - mean[u] * wsum) / den[u]);
            }
        }
        if (tid == 0) TSTAMP0(2, 3);
        named_arrive(3, 512);
        if (nt == 0 && wg == 0) {
            float2* s_st = (float2*)(sp + KF_OFF_WO + 49152);
            if (t == 0) {
                s_key[wi * 16 + g] = ((unsigned long long)order_bits(rr[0]) << 32) | (uint32_t)(0x7FFFFFFF - (r0 + 1));
                s_key[wi * 16 + g + 8] = ((unsigned long long)order_bits(rr[1]) << 32) | (uint32_t)(0x7FFFFFFF - (r0 + 9));
                s_st[wi * 16 + g] = make_float2(mean[0], den[0]);
                s_st[wi * 16 + g + 8] = make_float2(mean[1], den[1]);
            }
            named_sync(4, 128);
            if (warp == 0) {
                unsigned long long a = s_key[lane], b = s_key[lane + 32];
                if (b > a) { const unsigned long long c = a; a = b; b = c; }
                warp_top2(a, b);
                if (lane < 2) {
                    const unsigned long long k = lane ? b : a;
                    const int tok1 = 0x7FFFFFFF - (int)(uint32_t)k;
                    const float2 st = s_st[(tok1 - 1) & 63];
                    asm volatile("st.relaxed.gpu.global.v4.u32 [%0], {%1, %2, %3, %4};" ::"l"(g_cand + mt * 2 + lane), "r"((uint32_t)(k >> 32)),
                                 "r"((uint32_t)tok1), "r"(__float_as_uint(st.x)), "r"(__float_as_uint(st.y)) : "memory");
                }
            }
        }
        const float i0 = 1.f / den[0], i1 = 1.f / den[1];
#pragma unroll
        for (int j = 0; j < 8; j += 2) {
            uint32_t ro[4];
#pragma unroll
            for (int u = 0; u < 2; u++) {
                const int jj = j + u;
                const float a = hv[4 * jj], b = hv[4 * jj + 1], c = hv[4 * jj + 2], d = hv[4 * jj + 3];
                const float na = rbf(rbf(a - mean[0]) * i0), nb = rbf(rbf(b - mean[0]) * i0);
                const float nc = rbf(rbf(c - mean[1]) * i1), nd = rbf(rbf(d - mean[1]) * i1);
                ro[2 * u] = pack_bf16(a + na, b + nb);
                ro[2 * u + 1] = pack_bf16(c + nc, d + nd);
            }
            const uint32_t off = srow * 128 + (((j + sj) ^ (srow & 7)) << 4);
            stmatrix_x4(stg_o + off, ro[0], ro[1], ro[2], ro[3]);
        }
        __syncwarp();
#pragma unroll
        for (int i = 0; i < 4; i++) {
            const int row = i * 4 + (lane >> 3), ch = lane & 7;
            const uint4 vo = *(const uint4*)(sp + stg_off + row * 128 + ((ch ^ (row & 7)) << 4));
            *(uint4*)(out + (size_t)(mt * 64 + wi * 16 + row) * DM + cb + ch * 8) = vo;
        }
        named_sync(4 + wg, 128);
        if ((tid & 127) == 0) red_release_add(&g_sflag[mt]);
        if (tid == 0) TSTAMP0(2, 4);
    } else {
        named_arrive(1, 512);
        const bool worker = blockIdx.x < FF / 16;
        const bool downer = blockIdx.x >= 64;
        const int mtid = tid - 256, mwarp = mtid >> 5;
        const int c0 = (blockIdx.x - 64) * 8;
        float* s_x = (float*)(sp + KF_OFF_WO + 49152 + 8192);
        float* s_red = (float*)(sp + KF_OFF_WO + 49152 + 8192 + 4096);
        if (mwarp == 1) {
            named_sync(8, 288);
            if (lane == 0) {
                red_release_add(&g_hflag[mt]);
                if (downer) {
                    mbar_expect_tx(dbar, 7 * 4096);
                    for (int i = 0; i < 7; i++) tma_load_2d(sb + (4 + (i >> 2)) * KF_CH_S + (i & 3) * 4096, &tm_d, c0, i * 256, dbar);
                }
            }
            __syncwarp();
        }
        if (mtid == 0) TSTAMP0(3, 0);
        named_sync(3, 512);
        if (mwarp == 0) {
            uint4 ca, cb4;
            int spins = 0;
            while (true) {
                asm volatile("ld.relaxed.gpu.global.v4.u32 {%0, %1, %2, %3}, [%4];" : "=r"(ca.x), "=r"(ca.y), "=r"(ca.z), "=r"(ca.w) : "l"(g_cand + 2 * lane) : "memory");
                asm volatile("ld.relaxed.gpu.global.v4.u32 {%0, %1, %2, %3}, [%4];" : "=r"(cb4.x), "=r"(cb4.y), "=r"(cb4.z), "=r"(cb4.w) : "l"(g_cand + 2 * lane + 1) : "memory");
                const unsigned int hf = ld_acquire(&g_hflag[lane]);
                const bool ok = ca.y != 0 && cb4.y != 0 && hf >= 4u;
                if (__all_sync(0xffffffffu, ok) || ++spins > (1 << 20)) break;
                __nanosleep(20);
            }
            unsigned long long ka = cand_key(ca), kb = cand_key(cb4);
            const unsigned long long mya = ka, myb = kb;
            warp_top2(ka, kb);
            if (mya == ka) s_sel[0] = ca;
            if (myb == ka) s_sel[0] = cb4;
            if (mya == kb) s_sel[1] = ca;
            if (myb == kb) s_sel[1] = cb4;
        }
        named_sync(2, 256);
        if (mtid == 0) TSTAMP0(3, 1);
        int idx[2];
        float mean[2], inv[2], rv[2];
#pragma unroll
        for (int u = 0; u < 2; u++) {
            const uint4 c = s_sel[u];
            idx[u] = (int)c.y - 1;
            rv[u] = order_value(c.x);
            mean[u] = __uint_as_float(c.z);
            inv[u] = 1.f / __uint_as_float(c.w);
        }
        float hfin = 0.f;
        if (downer && mtid < 16) hfin = __bfloat162float(__ldcg((const __nv_bfloat16*)(g_h + (size_t)((mtid >> 3) ? idx[1] : idx[0]) * DM + c0 + (mtid & 7))));
        if (worker) {
#pragma unroll
            for (int u = 0; u < 2; u++) {
                const uint32_t ho = __ldcg((const uint32_t*)(g_h + (size_t)idx[u] * DM + 2 * mtid));
                *(float2*)(s_x + u * 512 + 2 * mtid) = make_float2(rbf(rbf(bf_lo(ho) - mean[u]) * inv[u]), rbf(rbf(bf_hi(ho) - mean[u]) * inv[u]));
            }
            mbar_wait(gbar, 0);
            named_sync(2, 256);
            float acc[8];
#pragma unroll
            for (int i = 0; i < 8; i++) acc[i] = 0.f;
            const uint8_t* wbase = sp + (mwarp >> 2) * (4 * KF_CH_S) + 16384 + lane * 32 + (mwarp & 3) * 8;
#pragma unroll
            for (int k = 0; k < 16; k++) {
                const uint2 w = *(const uint2*)(wbase + (k >> 2) * KF_CH_S + (k & 3) * 1024);
                const float x0 = s_x[lane + 32 * k], x1 = s_x[512 + lane + 32 * k];
                const float w0 = bf_lo(w.x), w1 = bf_hi(w.x), w2 = bf_lo(w.y), w3 = bf_hi(w.y);
                acc[0] = fmaf(x0, w0, acc[0]); acc[1] = fmaf(x0, w1, acc[1]); acc[2] = fmaf(x0, w2, acc[2]); acc[3] = fmaf(x0, w3, acc[3]);
                acc[4] = fmaf(x1, w0, acc[4]); acc[5] = fmaf(x1, w1, acc[5]); acc[6] = fmaf(x1, w2, acc[6]); acc[7] = fmaf(x1, w3, acc[7]);
            }
#define KF_STEP(O, N)                                                          \
            {                                                                  \
                const bool up = (lane & (O)) != 0;                             \
                _Pragma("unroll") for (int i = 0; i < (N); i++) {              \
                    const float send = up ? acc[i] : acc[i + (N)];             \
                    const float keep = up ? acc[i + (N)] : acc[i];             \
                    acc[i] = keep + __shfl_xor_sync(0xffffffffu, send, (O));   \
                }                                                              \
            }
            KF_STEP(16, 4) KF_STEP(8, 2) KF_STEP(4, 1)
            acc[0] += __shfl_xor_sync(0xffffffffu, acc[0], 2);
            acc[0] += __shfl_xor_sync(0xffffffffu, acc[0], 1);
            if ((lane & 3) == 0) {
                const int v = ((lane & 16) ? 4 : 0) + ((lane & 8) ? 2 : 0) + ((lane & 4) ? 1 : 0);
                s_gu[(v >> 2) * 32 + mwarp * 4 + (v & 3)] = acc[0];
            }
            named_sync(2, 256);
            if (mtid < 16) {
                uint32_t a2 = 0;
#pragma unroll
                for (int u = 0; u < 2; u++) {
                    const float gb = rbf(s_gu[u * 32 + mtid]);
                    const float sg = rbf(gb / (1.f + __expf(-gb)));
                    float a = sg * rbf(s_gu[u * 32 + 16 + mtid]);
                    uint32_t ab = (uint32_t)__bfloat16_as_ushort(__float2bfloat16_rn(a));
                    if (ab == 0xFFFFu) ab = 0x7FFFu;
                    a2 |= ab << (16 * u);
                }
                asm volatile("st.relaxed.gpu.global.u32 [%0], %1;" ::"l"(g_act + blockIdx.x * 16 + mtid), "r"(a2) : "memory");
            }
            if (mtid == 0) TSTAMP0(3, 2);
        }
        if (downer) {
            uint32_t av[7];
            {
                int spins = 0;
                while (true) {
                    bool ok = true;
#pragma unroll
                    for (int j = 0; j < 7; j++) {
                        asm volatile("ld.relaxed.gpu.global.u32 %0, [%1];" : "=r"(av[j]) : "l"(g_act + mtid + 256 * j) : "memory");
                        ok = ok && ((av[j] & 0xFFFFu) != 0xFFFFu) && ((av[j] >> 16) != 0xFFFFu);
                    }
                    if (mtid < 2) ok = ok && (ld_acquire(&g_sflag[(mtid ? idx[1] : idx[0]) >> 6]) >= 8u);
                    if (__all_sync(0xffffffffu, ok) || ++spins > (1 << 20)) break;
                    __nanosleep(20);
                }
            }
            if (mtid == 0) TSTAMP0(3, 3);
            mbar_wait(dbar, 0);
            float acc[16];
#pragma unroll
            for (int i = 0; i < 16; i++) acc[i] = 0.f;
#pragma unroll
            for (int j = 0; j < 7; j++) {
                const uint4 w = *(const uint4*)(sp + (4 + (j >> 2)) * KF_CH_S + (j & 3) * 4096 + mtid * 16);
                const float a0 = bf_lo(av[j]), a1 = bf_hi(av[j]);
                const uint32_t ww[4] = {w.x, w.y, w.z, w.w};
#pragma unroll
                for (int q = 0; q < 4; q++) {
                    const float wl = bf_lo(ww[q]), wh = bf_hi(ww[q]);
                    acc[2 * q] = fmaf(a0, wl, acc[2 * q]); acc[2 * q + 1] = fmaf(a0, wh, acc[2 * q + 1]);
                    acc[8 + 2 * q] = fmaf(a1, wl, acc[8 + 2 * q]); acc[8 + 2 * q + 1] = fmaf(a1, wh, acc[8 + 2 * q + 1]);
                }
            }
            KF_STEP(16, 8) KF_STEP(8, 4) KF_STEP(4, 2) KF_STEP(2, 1)
            acc[0] += __shfl_xor_sync(0xffffffffu, acc[0], 1);
            if ((lane & 1) == 0) {
                const int v = ((lane & 16) ? 8 : 0) + ((lane & 8) ? 4 : 0) + ((lane & 4) ? 2 : 0) + ((lane & 2) ? 1 : 0);
                s_red[mwarp * 16 + v] = acc[0];
            }
            named_sync(2, 256);
            if (mtid < 16) {
                const int u = mtid >> 3;
                float y = 0.f;
#pragma unroll
                for (int w = 0; w < 8; w++) y += s_red[w * 16 + mtid];
                const float sig = rbf(1.f / (1.f + __expf(-(u ? rv[1] : rv[0]))));
                const float xn = rbf(rbf(hfin - (u ? mean[1] : mean[0])) * (u ? inv[1] : inv[0]));
                const float ov = hfin + rbf(xn + rbf(rbf(y) * sig));
                out[(size_t)(u ? idx[1] : idx[0]) * DM + c0 + (mtid & 7)] = __float2bfloat16_rn(ov);
            }
            if (blockIdx.x == gridDim.x - 1 && mtid == 0) g_epoch = g_epoch + 1u;
            if (mtid == 0) TSTAMP0(3, 4);
        }
    }
}

typedef CUresult (*PFN_encodeTiled)(CUtensorMap*, CUtensorMapDataType, cuuint32_t, void*, const cuuint64_t*, const cuuint64_t*,
                                    const cuuint32_t*, const cuuint32_t*, CUtensorMapInterleave, CUtensorMapSwizzle,
                                    CUtensorMapL2promotion, CUtensorMapFloatOOBfill);

void make_map(PFN_encodeTiled enc, CUtensorMap* m, const void* ptr, uint64_t cols, uint64_t rows, uint32_t bcols, uint32_t brows) {
    cuuint64_t dims[2] = {cols, rows};
    cuuint64_t strides[1] = {cols * 2};
    cuuint32_t box[2] = {bcols, brows};
    cuuint32_t es[2] = {1, 1};
    enc(m, CU_TENSOR_MAP_DATA_TYPE_BFLOAT16, 2, const_cast<void*>(ptr), dims, strides, box, es, CU_TENSOR_MAP_INTERLEAVE_NONE,
        CU_TENSOR_MAP_SWIZZLE_128B, CU_TENSOR_MAP_L2_PROMOTION_L2_256B, CU_TENSOR_MAP_FLOAT_OOB_FILL_NONE);
}

void make_map3(PFN_encodeTiled enc, CUtensorMap* m, const void* ptr, uint64_t d0, uint64_t rows, uint64_t d2, uint64_t row_stride_bytes,
               uint64_t d2_stride_bytes, uint32_t b0, uint32_t b1, uint32_t b2) {
    cuuint64_t dims[3] = {d0, rows, d2};
    cuuint64_t strides[2] = {row_stride_bytes, d2_stride_bytes};
    cuuint32_t box[3] = {b0, b1, b2};
    cuuint32_t es[3] = {1, 1, 1};
    enc(m, CU_TENSOR_MAP_DATA_TYPE_BFLOAT16, 3, const_cast<void*>(ptr), dims, strides, box, es, CU_TENSOR_MAP_INTERLEAVE_NONE,
        CU_TENSOR_MAP_SWIZZLE_128B, CU_TENSOR_MAP_L2_PROMOTION_L2_256B, CU_TENSOR_MAP_FLOAT_OOB_FILL_NONE);
}

void make_map_plain(PFN_encodeTiled enc, CUtensorMap* m, const void* ptr, uint64_t cols, uint64_t rows, uint32_t bcols, uint32_t brows) {
    cuuint64_t dims[2] = {cols, rows};
    cuuint64_t strides[1] = {cols * 2};
    cuuint32_t box[2] = {bcols, brows};
    cuuint32_t es[2] = {1, 1};
    enc(m, CU_TENSOR_MAP_DATA_TYPE_BFLOAT16, 2, const_cast<void*>(ptr), dims, strides, box, es, CU_TENSOR_MAP_INTERLEAVE_NONE,
        CU_TENSOR_MAP_SWIZZLE_NONE, CU_TENSOR_MAP_L2_PROMOTION_NONE, CU_TENSOR_MAP_FLOAT_OOB_FILL_NONE);
}

template <typename... KArgs, typename... Args>
void launch(void (*kern)(KArgs...), int grid, int block, int smem, bool pdl, Args... args) {
    cudaLaunchConfig_t cfg = {};
    cfg.gridDim = dim3(grid);
    cfg.blockDim = dim3(block);
    cfg.dynamicSmemBytes = smem;
    cfg.stream = cudaStreamPerThread;
    cudaLaunchAttribute at[1];
    at[0].id = cudaLaunchAttributeProgrammaticStreamSerialization;
    at[0].val.programmaticStreamSerializationAllowed = 1;
    cfg.attrs = at;
    cfg.numAttrs = pdl ? 1 : 0;
    cudaLaunchKernelEx(&cfg, kern, KArgs(args)...);
}

}

extern "C" void kernel_launch(void* const* d_in, const int* in_sizes, int n_in, void* d_out, int out_size) {
    const __nv_bfloat16* x = (const __nv_bfloat16*)d_in[0];
    const __nv_bfloat16* wqkv = (const __nv_bfloat16*)d_in[1];
    const __nv_bfloat16* wo = (const __nv_bfloat16*)d_in[2];
    const __nv_bfloat16* w_r = (const __nv_bfloat16*)d_in[4];
    const __nv_bfloat16* w_gate = (const __nv_bfloat16*)d_in[5];
    const __nv_bfloat16* w_up = (const __nv_bfloat16*)d_in[6];
    const __nv_bfloat16* w_down = (const __nv_bfloat16*)d_in[7];
    __nv_bfloat16* out = (__nv_bfloat16*)d_out;

    static PFN_encodeTiled enc = nullptr;
    static void* g_o_ptr = nullptr;
    if (!enc) {
        cudaDriverEntryPointQueryResult qres;
        void* fn = nullptr;
        cudaGetDriverEntryPoint("cuTensorMapEncodeTiled", &fn, cudaEnableDefault, &qres);
        enc = (PFN_encodeTiled)fn;
        cudaGetSymbolAddress(&g_o_ptr, g_o);
        cudaFuncSetAttribute(k1_qkv, cudaFuncAttributeMaxDynamicSharedMemorySize, K1_SMEM);
        cudaFuncSetAttribute(kf_main, cudaFuncAttributeMaxDynamicSharedMemorySize, KF_SMEM);
    }
    CUtensorMap tm_x, tm_w, tm_o, tm_wo, tm_g, tm_u, tm_d;
    make_map_plain(enc, &tm_d, w_down, DM, FF, 8, 256);
    make_map_plain(enc, &tm_g, w_gate, FF, DM, 16, 128);
    make_map_plain(enc, &tm_u, w_up, FF, DM, 16, 128);
    make_map(enc, &tm_x, x, DM, SEQ, 64, 128);
    make_map3(enc, &tm_w, wqkv, DM, DM, 3, 3 * DM * 2, DM * 2, 64, 64, 3);
    make_map3(enc, &tm_o, g_o_ptr, 64, SEQ, 8, DM * 2, 128, 64, 64, 2);
    make_map3(enc, &tm_wo, wo, 64, DM, 8, DM * 2, 128, 64, 64, 2);

    const bool pdl = true;
    launch(k1_qkv, 128, 544, K1_SMEM, false, tm_x, tm_w, x);
    launch(kf_main, 128, 512, KF_SMEM, pdl, tm_o, tm_wo, tm_g, tm_u, tm_d, x, wo, w_r, w_gate, w_up, w_down, out);
}
```

```cpp
#include <cuda_runtime.h>
#include <cuda_bf16.h>
#include <cuda.h>
#include <stdint.h>

namespace {

constexpr int SEQ = 2048, DM = 512, NH = 32, FF = 1792;

__device__ __align__(1024) uint8_t g_q[NH * 2 * SEQ * 16];
__device__ __align__(1024) uint8_t g_kv[NH * 8 * 16384];
__device__ float g_norm[16 * NH * 3];
__device__ __align__(1024) __nv_bfloat16 g_o[SEQ * DM];
__device__ __align__(1024) __nv_bfloat16 g_h[SEQ * DM];
__device__ __align__(16) uint4 g_cand[64];
__device__ unsigned int g_oflag[32 * 32];
__device__ unsigned int g_hflag[32];
__device__ unsigned int g_sflag[32];
__device__ unsigned int g_act[FF];
__device__ unsigned int g_epoch;
__device__ __align__(16) float4 g_ln1[SEQ];
__device__ __align__(16) float4 g_part[32 * 8 * 64];

#define TSTAMP(K, I)
#define TSTAMP0(K, I)
__device__ __forceinline__ uint32_t smem_u32(const void* p) { return (uint32_t)__cvta_generic_to_shared(p); }
__device__ __forceinline__ void wg_fence() { asm volatile("wgmma.fence.sync.aligned;" ::: "memory"); }
__device__ __forceinline__ void wg_commit() { asm volatile("wgmma.commit_group.sync.aligned;" ::: "memory"); }
template <int N> __device__ __forceinline__ void wg_wait() { asm volatile("wgmma.wait_group.sync.aligned %0;" ::"n"(N) : "memory"); }
template <int N> __device__ __forceinline__ void fence_regs(float (&r)[N]) {
#pragma unroll
    for (int i = 0; i < N; i++) asm volatile("" : "+f"(r[i])::"memory");
}
__device__ __forceinline__ uint64_t make_desc(uint32_t addr, uint32_t lbo, uint32_t sbo, uint32_t swz) {
    uint64_t d = 0;
    d |= (uint64_t)((addr & 0x3FFFF) >> 4);
    d |= (uint64_t)((lbo & 0x3FFFF) >> 4) << 16;
    d |= (uint64_t)((sbo & 0x3FFFF) >> 4) << 32;
    d |= (uint64_t)swz << 62;
    return d;
}
__device__ __forceinline__ void mbar_init(uint32_t bar, uint32_t cnt) {
    asm volatile("mbarrier.init.shared::cta.b64 [%0], %1;" ::"r"(bar), "r"(cnt) : "memory");
}
__device__ __forceinline__ void mbar_expect_tx(uint32_t bar, uint32_t bytes) {
    asm volatile("mbarrier.arrive.expect_tx.shared::cta.b64 _, [%0], %1;" ::"r"(bar), "r"(bytes) : "memory");
}
__device__ __forceinline__ void mbar_arrive(uint32_t bar) {
    asm volatile("mbarrier.arrive.shared::cta.b64 _, [%0];" ::"r"(bar) : "memory");
}
__device__ __forceinline__ void mbar_wait(uint32_t bar, uint32_t parity) {
    asm volatile(
        "{\n.reg .pred p;\nWAIT_%=:\n"
        "mbarrier.try_wait.parity.shared::cta.b64 p, [%0], %1;\n"
        "@p bra DONE_%=;\nbra WAIT_%=;\nDONE_%=:\n}\n" ::"r"(bar), "r"(parity) : "memory");
}
__device__ __forceinline__ void bulk_g2s(uint32_t dst, const void* src, uint32_t bytes, uint32_t bar) {
    asm volatile("cp.async.bulk.shared::cluster.global.mbarrier::complete_tx::bytes [%0], [%1], %2, [%3];" ::"r"(dst),
                 "l"(src), "r"(bytes), "r"(bar) : "memory");
}
__device__ __forceinline__ void bulk_s2g(void* dst, uint32_t src, uint32_t bytes) {
    asm volatile("cp.async.bulk.global.shared::cta.bulk_group [%0], [%1], %2;" ::"l"(dst), "r"(src), "r"(bytes) : "memory");
}
__device__ __forceinline__ void tma_load_2d(uint32_t dst, const CUtensorMap* tm, int c0, int c1, uint32_t bar) {
    asm volatile("cp.async.bulk.tensor.2d.shared::cluster.global.mbarrier::complete_tx::bytes [%0], [%1, {%3, %4}], [%2];" ::"r"(dst),
                 "l"(tm), "r"(bar), "r"(c0), "r"(c1) : "memory");
}
__device__ __forceinline__ void tma_load_3d(uint32_t dst, const CUtensorMap* tm, int c0, int c1, int c2, uint32_t bar) {
    asm volatile("cp.async.bulk.tensor.3d.shared::cluster.global.mbarrier::complete_tx::bytes [%0], [%1, {%3, %4, %5}], [%2];" ::"r"(dst),
                 "l"(tm), "r"(bar), "r"(c0), "r"(c1), "r"(c2) : "memory");
}
__device__ __forceinline__ void tma_load_2d_mc(uint32_t dst, const CUtensorMap* tm, int c0, int c1, uint32_t bar, uint16_t mask) {
    asm volatile("cp.async.bulk.tensor.2d.shared::cluster.global.mbarrier::complete_tx::bytes.multicast::cluster [%0], [%1, {%3, %4}], [%2], %5;" ::"r"(dst),
                 "l"(tm), "r"(bar), "r"(c0), "r"(c1), "h"(mask) : "memory");
}
__device__ __forceinline__ void mbar_arrive_cluster(uint32_t bar, uint32_t cta) {
    asm volatile("{\n.reg .b32 ra;\nmapa.shared::cluster.u32 ra, %0, %1;\nmbarrier.arrive.release.cluster.shared::cluster.b64 _, [ra];\n}" ::"r"(bar), "r"(cta) : "memory");
}
__device__ __forceinline__ void cluster_sync() {
    asm volatile("barrier.cluster.arrive.release.aligned;\nbarrier.cluster.wait.acquire.aligned;" ::: "memory");
}
__device__ __forceinline__ void prefetch_l2(const void* p, uint32_t bytes) {
    asm volatile("cp.async.bulk.prefetch.L2.global [%0], %1;" ::"l"(p), "r"(bytes) : "memory");
}
__device__ __forceinline__ void fence_proxy_async() { asm volatile("fence.proxy.async.shared::cta;" ::: "memory"); }
__device__ __forceinline__ void fence_barrier_init() { asm volatile("fence.mbarrier_init.release.cluster;" ::: "memory"); }
__device__ __forceinline__ void pdl_launch() { asm volatile("griddepcontrol.launch_dependents;" ::: "memory"); }
__device__ __forceinline__ void pdl_wait() { asm volatile("griddepcontrol.wait;" ::: "memory"); }
__device__ __forceinline__ void named_sync(int id, int n) { asm volatile("bar.sync %0, %1;" ::"r"(id), "r"(n) : "memory"); }
__device__ __forceinline__ void named_arrive(int id, int n) { asm volatile("bar.arrive %0, %1;" ::"r"(id), "r"(n) : "memory"); }

__device__ __forceinline__ float ex2f(float x) { float y; asm("ex2.approx.ftz.f32 %0, %1;" : "=f"(y) : "f"(x)); return y; }
__device__ __forceinline__ uint32_t pack_bf16(float lo, float hi) {
    uint32_t r; asm("cvt.rn.bf16x2.f32 %0, %1, %2;" : "=r"(r) : "f"(hi), "f"(lo)); return r;
}
__device__ __forceinline__ float bf_lo(uint32_t v) { return __uint_as_float(v << 16); }
__device__ __forceinline__ float bf_hi(uint32_t v) { return __uint_as_float(v & 0xFFFF0000u); }
__device__ __forceinline__ float rbf(float x) { return __bfloat162float(__float2bfloat16_rn(x)); }
__device__ __forceinline__ uint32_t fma_bf16x2(uint32_t a, uint32_t b, uint32_t c) {
    uint32_t r; asm("fma.rn.bf16x2 %0, %1, %2, %3;" : "=r"(r) : "r"(a), "r"(b), "r"(c)); return r;
}
__device__ __forceinline__ void stmatrix_x4(uint32_t addr, uint32_t r0, uint32_t r1, uint32_t r2, uint32_t r3) {
    asm volatile("stmatrix.sync.aligned.m8n8.x4.shared.b16 [%0], {%1, %2, %3, %4};" ::"r"(addr), "r"(r0), "r"(r1), "r"(r2), "r"(r3) : "memory");
}
__device__ __forceinline__ void stmatrix_x4_trans(uint32_t addr, uint32_t r0, uint32_t r1, uint32_t r2, uint32_t r3) {
    asm volatile("stmatrix.sync.aligned.m8n8.x4.trans.shared.b16 [%0], {%1, %2, %3, %4};" ::"r"(addr), "r"(r0), "r"(r1), "r"(r2), "r"(r3) : "memory");
}

__device__ __forceinline__ void wgmma_k1_n136(float (&d)[68], uint64_t desca, uint64_t descb, int scale_d) {
  asm volatile("{\n.reg .pred p;\nsetp.ne.b32 p, %70, 0;\n"
    "wgmma.mma_async.sync.aligned.m64n136k16.f32.bf16.bf16 "
    "{%0, %1, %2, %3, %4, %5, %6, %7, %8, %9, %10, %11, %12, %13, %14, %15, %16, %17, %18, %19, %20, %21, %22, %23, %24, %25, %26, %27, %28, %29, %30, %31, %32, %33, %34, %35, %36, %37, %38, %39, %40, %41, %42, %43, %44, %45, %46, %47, %48, %49, %50, %51, %52, %53, %54, %55, %56, %57, %58, %59, %60, %61, %62, %63, %64, %65, %66, %67}, "
    "%68, %69, p, 1, 1, 1, 0;\n}\n"
    : "+f"(d[0]), "+f"(d[1]), "+f"(d[2]), "+f"(d[3]), "+f"(d[4]), "+f"(d[5]), "+f"(d[6]), "+f"(d[7]), "+f"(d[8]), "+f"(d[9]), "+f"(d[10]), "+f"(d[11]), "+f"(d[12]), "+f"(d[13]), "+f"(d[14]), "+f"(d[15]), "+f"(d[16]), "+f"(d[17]), "+f"(d[18]), "+f"(d[19]), "+f"(d[20]), "+f"(d[21]), "+f"(d[22]), "+f"(d[23]), "+f"(d[24]), "+f"(d[25]), "+f"(d[26]), "+f"(d[27]), "+f"(d[28]), "+f"(d[29]), "+f"(d[30]), "+f"(d[31]), "+f"(d[32]), "+f"(d[33]), "+f"(d[34]), "+f"(d[35]), "+f"(d[36]), "+f"(d[37]), "+f"(d[38]), "+f"(d[39]), "+f"(d[40]), "+f"(d[41]), "+f"(d[42]), "+f"(d[43]), "+f"(d[44]), "+f"(d[45]), "+f"(d[46]), "+f"(d[47]), "+f"(d[48]), "+f"(d[49]), "+f"(d[50]), "+f"(d[51]), "+f"(d[52]), "+f"(d[53]), "+f"(d[54]), "+f"(d[55]), "+f"(d[56]), "+f"(d[57]), "+f"(d[58]), "+f"(d[59]), "+f"(d[60]), "+f"(d[61]), "+f"(d[62]), "+f"(d[63]), "+f"(d[64]), "+f"(d[65]), "+f"(d[66]), "+f"(d[67])
    : "l"(desca), "l"(descb), "r"(scale_d));
}
__device__ __forceinline__ void wgmma_qk_n64(float (&d)[32], uint32_t a0, uint32_t a1, uint32_t a2, uint32_t a3, uint64_t descb) {
  asm volatile("{\n.reg .pred p;\nsetp.ne.b32 p, 0, 0;\n"
    "wgmma.mma_async.sync.aligned.m64n64k16.f32.bf16.bf16 "
    "{%0, %1, %2, %3, %4, %5, %6, %7, %8, %9, %10, %11, %12, %13, %14, %15, %16, %17, %18, %19, %20, %21, %22, %23, %24, %25, %26, %27, %28, %29, %30, %31}, "
    "{%32, %33, %34, %35}, %36, p, 1, 1, 0;\n}\n"
    : "=f"(d[0]), "=f"(d[1]), "=f"(d[2]), "=f"(d[3]), "=f"(d[4]), "=f"(d[5]), "=f"(d[6]), "=f"(d[7]), "=f"(d[8]), "=f"(d[9]), "=f"(d[10]), "=f"(d[11]), "=f"(d[12]), "=f"(d[13]), "=f"(d[14]), "=f"(d[15]), "=f"(d[16]), "=f"(d[17]), "=f"(d[18]), "=f"(d[19]), "=f"(d[20]), "=f"(d[21]), "=f"(d[22]), "=f"(d[23]), "=f"(d[24]), "=f"(d[25]), "=f"(d[26]), "=f"(d[27]), "=f"(d[28]), "=f"(d[29]), "=f"(d[30]), "=f"(d[31])
    : "r"(a0), "r"(a1), "r"(a2), "r"(a3), "l"(descb));
}
__device__ __forceinline__ void wgmma_pv_n24(float (&d)[12], uint32_t a0, uint32_t a1, uint32_t a2, uint32_t a3, uint64_t descb) {
  asm volatile("{\n.reg .pred p;\nsetp.eq.b32 p, 0, 0;\n"
    "wgmma.mma_async.sync.aligned.m64n24k16.f32.bf16.bf16 "
    "{%0, %1, %2, %3, %4, %5, %6, %7, %8, %9, %10, %11}, "
    "{%12, %13, %14, %15}, %16, p, 1, 1, 1;\n}\n"
    : "+f"(d[0]), "+f"(d[1]), "+f"(d[2]), "+f"(d[3]), "+f"(d[4]), "+f"(d[5]), "+f"(d[6]), "+f"(d[7]), "+f"(d[8]), "+f"(d[9]), "+f"(d[10]), "+f"(d[11])
    : "r"(a0), "r"(a1), "r"(a2), "r"(a3), "l"(descb));
}
__device__ __forceinline__ void wgmma_k3_n64(float (&d)[32], uint64_t desca, uint64_t descb, int scale_d) {
  asm volatile("{\n.reg .pred p;\nsetp.ne.b32 p, %34, 0;\n"
    "wgmma.mma_async.sync.aligned.m64n64k16.f32.bf16.bf16 "
    "{%0, %1, %2, %3, %4, %5, %6, %7, %8, %9, %10, %11, %12, %13, %14, %15, %16, %17, %18, %19, %20, %21, %22, %23, %24, %25, %26, %27, %28, %29, %30, %31}, "
    "%32, %33, p, 1, 1, 0, 1;\n}\n"
    : "+f"(d[0]), "+f"(d[1]), "+f"(d[2]), "+f"(d[3]), "+f"(d[4]), "+f"(d[5]), "+f"(d[6]), "+f"(d[7]), "+f"(d[8]), "+f"(d[9]), "+f"(d[10]), "+f"(d[11]), "+f"(d[12]), "+f"(d[13]), "+f"(d[14]), "+f"(d[15]), "+f"(d[16]), "+f"(d[17]), "+f"(d[18]), "+f"(d[19]), "+f"(d[20]), "+f"(d[21]), "+f"(d[22]), "+f"(d[23]), "+f"(d[24]), "+f"(d[25]), "+f"(d[26]), "+f"(d[27]), "+f"(d[28]), "+f"(d[29]), "+f"(d[30]), "+f"(d[31])
    : "l"(desca), "l"(descb), "r"(scale_d));
}

constexpr int K1_XS = 17408;
constexpr int K1_WS = 24576;
constexpr int K1_ST = K1_XS + K1_WS;
constexpr int K1_NST = 5;
constexpr int K1_OFF_MISC = K1_NST * K1_ST;
constexpr int K1_SMEM = K1_OFF_MISC + 2048 + 1024;
constexpr float QSCALE = 0.25f * 1.4426950408889634f;

__global__ void __launch_bounds__(544, 1)
k1_qkv(const __grid_constant__ CUtensorMap tm_x, const __grid_constant__ CUtensorMap tm_w, const __nv_bfloat16* __restrict__ x) {
    extern __shared__ uint8_t smem_raw[];
    const uint32_t sraw = smem_u32(smem_raw);
    const uint32_t sb = (sraw + 1023) & ~1023u;
    uint8_t* sp = smem_raw + (sb - sraw);
    const uint32_t full = sb + K1_OFF_MISC;
    const uint32_t empty = full + 64;
    float* s_m = (float*)(sp + K1_OFF_MISC + 256);
    float* s_r = s_m + 128;

    const int tid = threadIdx.x, warp = tid >> 5, lane = tid & 31;
    const int mt = blockIdx.x >> 3, nt = blockIdx.x & 7;
    if (tid == 0) TSTAMP0(0, 0);
    pdl_launch();
    if (tid == 512) {
        for (int i = 0; i < K1_NST; i++) { mbar_init(full + 8 * i, 1); mbar_init(empty + 8 * i, 3); }
        fence_barrier_init();
        for (int kb = 0; kb < K1_NST; kb++) {
            mbar_expect_tx(full + 8 * kb, 16384 + K1_WS);
            tma_load_2d(sb + kb * K1_ST, &tm_x, kb * 64, mt * 128, full + 8 * kb);
            tma_load_3d(sb + kb * K1_ST + K1_XS, &tm_w, nt * 64, kb * 64, 0, full + 8 * kb);
        }
    }
    if (tid < K1_NST * 64) {
        *(uint4*)(sp + (tid >> 6) * K1_ST + 16384 + (tid & 63) * 16) =
            make_uint4(0x3F803F80u, 0x3F803F80u, 0x3F803F80u, 0x3F803F80u);
    }
    fence_proxy_async();
    __syncthreads();

    if (warp == 16) {
        if (lane == 0) {
            for (int kb = K1_NST; kb < 8; kb++) {
                const int s = kb % K1_NST;
                mbar_wait(empty + 8 * s, 0);
                mbar_expect_tx(full + 8 * s, 16384 + K1_WS);
                tma_load_2d(sb + s * K1_ST, &tm_x, kb * 64, mt * 128, full + 8 * s);
                tma_load_3d(sb + s * K1_ST + K1_XS, &tm_w, nt * 64, kb * 64, 0, full + 8 * s);
            }
        }
        __syncwarp();
        if (lane < FF / 128) g_act[blockIdx.x * (FF / 128) + lane] = 0xFFFFFFFFu;
        for (int i = lane; i < 128; i += 32) g_part[blockIdx.x * 128 + i] = make_float4(0.f, 0.f, 0.f, 0.f);
        if (blockIdx.x == 1) { g_cand[lane] = make_uint4(0, 0, 0, 0); g_cand[lane + 32] = make_uint4(0, 0, 0, 0); g_oflag[lane * 32] = 0; g_hflag[lane] = 0; g_sflag[lane] = 0; }
    } else if (warp >= 12) {
        const int r = tid - 384;
        const unsigned int tag = *(volatile unsigned int*)&g_epoch + 1u;
        {
            const int row = mt * 128 + nt * 16 + (r >> 3);
            const uint4* xp = (const uint4*)(x + (size_t)row * DM) + (r & 7);
            uint4 v[8];
#pragma unroll
            for (int i = 0; i < 8; i++) v[i] = __ldg(xp + i * 8);
            float s1 = 0.f;
#pragma unroll
            for (int i = 0; i < 8; i++)
                s1 += ((bf_lo(v[i].x) + bf_hi(v[i].x)) + (bf_lo(v[i].y) + bf_hi(v[i].y))) + ((bf_lo(v[i].z) + bf_hi(v[i].z)) + (bf_lo(v[i].w) + bf_hi(v[i].w)));
#pragma unroll
            for (int o = 1; o < 8; o <<= 1) s1 += __shfl_xor_sync(0xffffffffu, s1, o);
            const float mean = s1 * (1.f / DM);
            float q0 = 0.f, q1 = 0.f;
#pragma unroll
            for (int i = 0; i < 8; i++) {
                const uint32_t w[4] = {v[i].x, v[i].y, v[i].z, v[i].w};
#pragma unroll
                for (int j = 0; j < 4; j++) {
                    const float a = bf_lo(w[j]) - mean, b = bf_hi(w[j]) - mean;
                    q0 = fmaf(a, a, q0); q1 = fmaf(b, b, q1);
                }
            }
            float q = q0 + q1;
#pragma unroll
            for (int o = 1; o < 8; o <<= 1) q += __shfl_xor_sync(0xffffffffu, q, o);
            const float den = rbf(sqrtf(rbf(rbf(q * (1.f / DM)) + 1e-5f)));
            if ((r & 7) == 0)
                asm volatile("st.relaxed.gpu.global.v4.f32 [%0], {%1, %2, %3, %4};" ::"l"(g_ln1 + row), "f"(rbf(mean)), "f"(1.f / den),
                             "f"(__uint_as_float(tag)), "f"(0.f) : "memory");
        }
        if (r == 0) TSTAMP0(0, 6);
        {
            float4 v;
            int spins = 0;
            do {
                asm volatile("ld.relaxed.gpu.global.v4.f32 {%0, %1, %2, %3}, [%4];" : "=f"(v.x), "=f"(v.y), "=f"(v.z), "=f"(v.w) : "l"(g_ln1 + mt * 128 + r) : "memory");
            } while (__float_as_uint(v.z) != tag && ++spins < (1 << 22));
            s_m[r] = v.x;
            s_r[r] = v.y;
        }
        if (r == 0) TSTAMP0(0, 7);
        named_arrive(1, 512);
    } else {
        const int part = warp >> 2, hw = warp & 3;
        float acc[68];
#pragma unroll
        for (int i = 0; i < 68; i++) acc[i] = 0.f;
        fence_regs(acc);
#pragma unroll 1
        for (int kb = 0; kb < 8; kb++) {
            const int s = kb % K1_NST;
            mbar_wait(full + 8 * s, (kb / K1_NST) & 1);
            const uint64_t da = make_desc(sb + s * K1_ST + K1_XS + part * 8192, 1024, 1024, 1);
            const uint64_t db = make_desc(sb + s * K1_ST, 16, 1024, 1);
            wg_fence();
#pragma unroll
            for (int k = 0; k < 4; k++) wgmma_k1_n136(acc, da + k * 128, db + k * 2, (kb | k) != 0);
            wg_commit();
            if (kb > 0 && kb <= 8 - K1_NST) {
                wg_wait<1>();
                if ((tid & 127) == 0) mbar_arrive(empty + 8 * (kb - 1));
            }
        }
        wg_wait<0>();
        fence_regs(acc);
        if (tid == 0) TSTAMP0(0, 1);
        named_sync(1, 512);
        if (tid == 0) TSTAMP0(0, 2);

        const int t = lane & 3;
        const float cs0 = acc[64], cs1 = acc[66];
        const float sc = (part == 0) ? QSCALE : 1.f;
        const uint32_t stg = sb + (hw >> 1) * K1_ST + K1_XS + part * 8192 + (hw & 1) * 4096;
        const uint32_t st_addr = stg + ((lane >> 3) & 1) * 2048 + ((lane >> 4) * 8 + (lane & 7)) * 16;
#pragma unroll
        for (int j = 0; j < 16; j += 2) {
            uint32_t rr[4];
#pragma unroll
            for (int u = 0; u < 2; u++) {
                const int jj = j + u;
                const float2 m2 = *(const float2*)(s_m + 8 * jj + 2 * t);
                const float2 r2 = *(const float2*)(s_r + 8 * jj + 2 * t);
                const float ra = r2.x * sc, rb = r2.y * sc;
                rr[2 * u] = pack_bf16((acc[4 * jj] - m2.x * cs0) * ra, (acc[4 * jj + 1] - m2.y * cs0) * rb);
                rr[2 * u + 1] = pack_bf16((acc[4 * jj + 2] - m2.x * cs1) * ra, (acc[4 * jj + 3] - m2.y * cs1) * rb);
            }
            stmatrix_x4_trans(st_addr + j * 128, rr[0], rr[1], rr[2], rr[3]);
        }
        fence_proxy_async();
        __syncwarp();
        if (tid == 0) TSTAMP0(0, 4);
        const int head = nt * 4 + hw;
        if (lane == 0) {
            uint8_t* dst;
            uint32_t hstride;
            if (part == 0) { dst = g_q + (size_t)head * 65536 + mt * 2048; hstride = 32768; }
            else { dst = g_kv + (size_t)head * 131072 + (mt >> 1) * 16384 + (part - 1) * 8192 + (mt & 1) * 2048; hstride = 4096; }
            bulk_s2g(dst, stg, 2048);
            bulk_s2g(dst + hstride, stg + 2048, 2048);
            asm volatile("cp.async.bulk.commit_group;" ::: "memory");
        }
        float nmax = 0.f;
#pragma unroll
        for (int i = 0; i < 4; i++) {
            const int tok = lane + 32 * i;
            const uint4 a = *(const uint4*)(sp + (stg - sb) + tok * 16);
            const uint4 b = *(const uint4*)(sp + (stg - sb) + 2048 + tok * 16);
            const uint32_t w[8] = {a.x, a.y, a.z, a.w, b.x, b.y, b.z, b.w};
            float n2 = 0.f, n3 = 0.f;
#pragma unroll
            for (int q = 0; q < 8; q++) {
                const float lo = bf_lo(w[q]), hi = bf_hi(w[q]);
                n2 = fmaf(lo, lo, n2); n3 = fmaf(hi, hi, n3);
            }
            n2 += n3;
            nmax = (n2 > nmax || n2 != n2) ? n2 : nmax;
        }
#pragma unroll
        for (int o = 16; o > 0; o >>= 1) {
            const float v = __shfl_xor_sync(0xffffffffu, nmax, o);
            nmax = (v > nmax || v != v) ? v : nmax;
        }
        if (tid == 0) TSTAMP0(0, 5);
        if (lane == 0) {
            g_norm[(mt * NH + head) * 3 + part] = nmax;
            asm volatile("cp.async.bulk.wait_group.read 0;" ::: "memory");
            if (tid == 0) TSTAMP0(0, 3);
        }
    }
}

constexpr int KF_CH_G = 16384, KF_CH_S = 20480, KF_NCH = 8;
constexpr int KF_OFF_WO = KF_NCH * KF_CH_S;
constexpr int KF_OFF_MISC = KF_OFF_WO + 65536;
constexpr int KF_SMEM = KF_OFF_MISC + 1280 + 1024;

__device__ __forceinline__ uint32_t exp2_pair_poly(float s0, float s1) {
    const float KB = 65536.0f + 127.0f;
    const float t0 = s0 + KB, t1 = s1 + KB;
    const uint32_t w = __byte_perm(__float_as_uint(t0), __float_as_uint(t1), 0x5410);
    uint32_t z;
    asm("lop3.b32 %0, %1, %2, %3, 0xEA;" : "=r"(z) : "r"(w), "r"(0x007F007Fu), "r"(0x3F803F80u));
    uint32_t p = fma_bf16x2(0x3eab3eabu, z, 0xbc73bc73u);
    p = fma_bf16x2(p, z, 0x3f2f3f2fu);
    return p + w - z;
}
constexpr uint32_t KF_EMASK = 0x5757u;
template <int LO, int HI>
__device__ __forceinline__ void softmax_part(const float (&s)[32], uint32_t (&p)[16]) {
#pragma unroll
    for (int i = LO; i < HI; i++) {
        if ((KF_EMASK >> i) & 1) p[i] = exp2_pair_poly(s[2 * i], s[2 * i + 1]);
        else p[i] = pack_bf16(ex2f(s[2 * i]), ex2f(s[2 * i + 1]));
    }
}
#define KF_PV(P, OFF)                                                                              \
    _Pragma("unroll") for (int kk = 0; kk < 4; kk++)                                               \
        wgmma_pv_n24(o, P[4 * kk], P[4 * kk + 1], P[4 * kk + 2], P[4 * kk + 3], dv + ((OFF) + kk * 16));

__device__ __forceinline__ unsigned long long cand_key(const uint4& c) {
    return ((unsigned long long)c.x << 32) | (uint32_t)(0x7FFFFFFF - (int)c.y);
}
__device__ __forceinline__ uint32_t order_bits(float v) {
    const uint32_t u = __float_as_uint(v);
    return (u & 0x80000000u) ? ~u : (u | 0x80000000u);
}
__device__ __forceinline__ float order_value(uint32_t u) {
    return __uint_as_float((u & 0x80000000u) ? (u & 0x7FFFFFFFu) : ~u);
}
__device__ __forceinline__ void warp_top2(unsigned long long& a, unsigned long long& b) {
#pragma unroll
    for (int o = 16; o > 0; o >>= 1) {
        const unsigned long long c = __shfl_xor_sync(0xffffffffu, a, o);
        const unsigned long long d = __shfl_xor_sync(0xffffffffu, b, o);
        const unsigned long long hi = a > c ? a : c, lo = a > c ? c : a;
        const unsigned long long m = b > d ? b : d;
        a = hi;
        b = lo > m ? lo : m;
    }
}
__device__ __forceinline__ unsigned int ld_acquire(const unsigned int* p) {
    unsigned int v; asm volatile("ld.acquire.gpu.global.u32 %0, [%1];" : "=r"(v) : "l"(p) : "memory"); return v;
}
__device__ __forceinline__ void red_release_add(unsigned int* p) {
    asm volatile("red.release.gpu.global.add.u32 [%0], 1;" ::"l"(p) : "memory");
}

__global__ void __launch_bounds__(512, 1)
kf_main(const __grid_constant__ CUtensorMap tm_o, const __grid_constant__ CUtensorMap tm_wo,
        const __grid_constant__ CUtensorMap tm_g, const __grid_constant__ CUtensorMap tm_u, const __grid_constant__ CUtensorMap tm_d,
        const __nv_bfloat16* __restrict__ x, const __nv_bfloat16* __restrict__ wo, const __nv_bfloat16* __restrict__ w_r,
        const __nv_bfloat16* __restrict__ w_gate, const __nv_bfloat16* __restrict__ w_up, const __nv_bfloat16* __restrict__ w_down,
        __nv_bfloat16* __restrict__ out) {
    extern __shared__ uint8_t smem_raw[];
    const uint32_t sraw = smem_u32(smem_raw);
    const uint32_t sb = (sraw + 1023) & ~1023u;
    uint8_t* sp = smem_raw + (sb - sraw);
    const uint32_t kvbar = sb + KF_OFF_MISC;
    const uint32_t wbar = kvbar + 64;
    const uint32_t obar = wbar + 64;
    const uint32_t gbar = obar + 32;
    const uint32_t dbar = gbar + 8;
    unsigned int* s_cnt = (unsigned int*)(sp + KF_OFF_MISC + 192);
    unsigned long long* s_key = (unsigned long long*)(sp + KF_OFF_MISC + 256);
    float* s_gu = (float*)(sp + KF_OFF_MISC + 768);
    uint4* s_sel = (uint4*)(sp + KF_OFF_MISC + 1024);
    const int tid = threadIdx.x;
    const int head = blockIdx.x >> 2, quarter = blockIdx.x & 3;
    const int mt = blockIdx.x >> 2, nt = blockIdx.x & 3;
    if (tid == 0) TSTAMP0(1, 0);
    if (tid == 0) {
        for (int c = 0; c < 22; c++) mbar_init(kvbar + 8 * c, 1);
        for (int c = 0; c < 4; c++) s_cnt[c] = 0;
        fence_barrier_init();
        for (int kb = 0; kb < 4; kb++) {
            mbar_expect_tx(wbar + 8 * kb, 16384);
            tma_load_3d(sb + KF_OFF_WO + kb * 16384, &tm_wo, 0, kb * 64, nt * 2, wbar + 8 * kb);
        }
    }
    if (tid == 32) {
        prefetch_l2((const uint8_t*)wo + blockIdx.x * 4096, 4096);
        prefetch_l2((const uint8_t*)w_gate + blockIdx.x * 14336, 14336);
        prefetch_l2((const uint8_t*)w_up + blockIdx.x * 14336, 14336);
        prefetch_l2((const uint8_t*)w_down + blockIdx.x * 14336, 14336);
    }
    for (int i = tid; i < KF_NCH * 256; i += 512)
        *(uint4*)(sp + (i >> 8) * KF_CH_S + 16384 + (i & 255) * 16) =
            make_uint4(0x3F803F80u, 0x3F803F80u, 0x3F803F80u, 0x3F803F80u);
    fence_proxy_async();
    __syncthreads();
    pdl_wait();
    if (tid == 0) TSTAMP0(1, 1);
    if (tid == 0) {
        const uint8_t* src = g_kv + (size_t)head * (KF_NCH * KF_CH_G);
        for (int c = 0; c < KF_NCH; c++) {
            mbar_expect_tx(kvbar + 8 * c, KF_CH_G);
            bulk_g2s(sb + c * KF_CH_S, src + c * KF_CH_G, KF_CH_G, kvbar + 8 * c);
        }
    }
    const int wg = tid >> 7, warp = (tid >> 5) & 3, lane = tid & 31, g = lane >> 2, t = lane & 3;
    uint32_t qn2[2][4];
#pragma unroll
    for (int ps = 0; ps < 2; ps++) {
        const uint8_t* qb = g_q + (size_t)head * 65536 + (quarter * 512 + ps * 256 + wg * 64 + warp * 16 + g) * 16 + t * 4;
        qn2[ps][0] = *(const uint32_t*)(qb);
        qn2[ps][1] = *(const uint32_t*)(qb + 128);
        qn2[ps][2] = *(const uint32_t*)(qb + 32768);
        qn2[ps][3] = *(const uint32_t*)(qb + 32768 + 128);
    }

    bool fast;
    {
        const int m16 = lane & 15;
        float kn = g_norm[(m16 * NH + head) * 3 + 1];
        float vn = g_norm[(m16 * NH + head) * 3 + 2];
        float qn = g_norm[((quarter * 4 + (lane & 3)) * NH + head) * 3 + 0];
        bool bad = !(kn < 1e30f) || !(vn < 1e30f) || !(qn < 1e30f);
#pragma unroll
        for (int o = 8; o > 0; o >>= 1) {
            kn = fmaxf(kn, __shfl_xor_sync(0xffffffffu, kn, o));
            qn = fmaxf(qn, __shfl_xor_sync(0xffffffffu, qn, o));
        }
        fast = __all_sync(0xffffffffu, !bad && (qn * kn <= 3500.f));
    }
    if (tid == 0) TSTAMP0(1, 8);
    const uint64_t dk0 = make_desc(sb, 4096, 128, 0);
    const uint64_t dv0 = make_desc(sb + 8192, 128, 4096, 0);

#pragma unroll 1
    for (int pass = 0; pass < 2; pass++) {
        const int row0 = quarter * 512 + pass * 256 + wg * 64 + warp * 16 + g;
        uint32_t qa[4];
#pragma unroll
        for (int i = 0; i < 4; i++) qa[i] = pass ? qn2[1][i] : qn2[0][i];
        float o[12];
#pragma unroll
        for (int i = 0; i < 12; i++) o[i] = 0.f;
        fence_regs(o);
#define KF_RELEASE_CHUNK(c)                                                                          \
        if (pass == 1 && (c) >= 1 && (c) <= 4) {                                                     \
            named_sync(4 + wg, 128);            \
            if ((tid & 127) == 0 && atomicAdd(&s_cnt[(c) - 1], 1u) == 3u) {                          \
                mbar_expect_tx(wbar + 8 * (3 + (c)), 16384);                                         \
                tma_load_3d(sb + ((c) - 1) * KF_CH_S, &tm_wo, 0, (3 + (c)) * 64, nt * 2, wbar + 8 * (3 + (c))); \
            }                                                                                        \
        }
        if (fast) {
#pragma unroll 1
            for (int c = 0; c < KF_NCH; c++) {
                const uint64_t dk = dk0 + (uint64_t)(c * (KF_CH_S >> 4));
                const uint64_t dv = dv0 + (uint64_t)(c * (KF_CH_S >> 4));
                float s0[32], s1[32], s2[32], s3[32];
                uint32_t p0[16], p1[16], p2[16], p3[16];
                mbar_wait(kvbar + 8 * c, 0);
                wg_wait<1>();
                wg_fence();
                wgmma_qk_n64(s0, qa[0], qa[1], qa[2], qa[3], dk);
                wg_commit();
                wg_wait<1>();
                KF_RELEASE_CHUNK(c);
                wg_fence();
                wgmma_qk_n64(s1, qa[0], qa[1], qa[2], qa[3], dk + 64);
                wg_commit();
                wg_wait<1>();
                fence_regs(s0);
                softmax_part<0, 16>(s0, p0);
                wg_fence();
                KF_PV(p0, 0);
                wg_commit();
                wg_wait<1>();
                fence_regs(s1);
                softmax_part<0, 8>(s1, p1);
                wg_wait<0>();
                wg_fence();
                wgmma_qk_n64(s2, qa[0], qa[1], qa[2], qa[3], dk + 128);
                wg_commit();
                softmax_part<8, 16>(s1, p1);
                wg_fence();
                KF_PV(p1, 64);
                wg_commit();
                wg_wait<1>();
                fence_regs(s2);
                softmax_part<0, 8>(s2, p2);
                wg_wait<0>();
                wg_fence();
                wgmma_qk_n64(s3, qa[0], qa[1], qa[2], qa[3], dk + 192);
                wg_commit();
                softmax_part<8, 16>(s2, p2);
                wg_fence();
                KF_PV(p2, 128);
                wg_commit();
                wg_wait<1>();
                fence_regs(s3);
                softmax_part<0, 16>(s3, p3);
                wg_fence();
                KF_PV(p3, 192);
                wg_commit();
            }
            wg_wait<0>();
            fence_regs(o);
        } else {
            float m0 = -INFINITY, m1 = -INFINITY;
#pragma unroll 1
            for (int b = 0; b < 32; b++) {
                const int c = b >> 2;
                const uint64_t dk = dk0 + (uint64_t)(c * (KF_CH_S >> 4) + (b & 3) * 64);
                const uint64_t dv = dv0 + (uint64_t)(c * (KF_CH_S >> 4) + (b & 3) * 64);
                float s[32];
                uint32_t p[16];
                mbar_wait(kvbar + 8 * c, 0);
                wg_fence();
                wgmma_qk_n64(s, qa[0], qa[1], qa[2], qa[3], dk);
                wg_commit();
                if ((b & 3) == 0) { KF_RELEASE_CHUNK(c); }
                wg_wait<0>();
                fence_regs(s);
                float x0 = s[0], x1 = s[2];
#pragma unroll
                for (int j = 0; j < 8; j++) {
                    x0 = fmaxf(x0, fmaxf(s[4 * j], s[4 * j + 1]));
                    x1 = fmaxf(x1, fmaxf(s[4 * j + 2], s[4 * j + 3]));
                }
                x0 = fmaxf(x0, __shfl_xor_sync(0xffffffffu, x0, 1));
                x0 = fmaxf(x0, __shfl_xor_sync(0xffffffffu, x0, 2));
                x1 = fmaxf(x1, __shfl_xor_sync(0xffffffffu, x1, 1));
                x1 = fmaxf(x1, __shfl_xor_sync(0xffffffffu, x1, 2));
                const float n0 = fmaxf(m0, x0), n1 = fmaxf(m1, x1);
                const float c0 = ex2f(m0 - n0), c1 = ex2f(m1 - n1);
                m0 = n0; m1 = n1;
#pragma unroll
                for (int j = 0; j < 3; j++) {
                    o[4 * j] *= c0; o[4 * j + 1] *= c0; o[4 * j + 2] *= c1; o[4 * j + 3] *= c1;
                }
#pragma unroll
                for (int j = 0; j < 8; j++) {
                    p[2 * j] = pack_bf16(ex2f(s[4 * j] - n0), ex2f(s[4 * j + 1] - n0));
                    p[2 * j + 1] = pack_bf16(ex2f(s[4 * j + 2] - n1), ex2f(s[4 * j + 3] - n1));
                }
                fence_regs(o);
                wg_fence();
                KF_PV(p, 0);
                wg_commit();
                wg_wait<0>();
                fence_regs(o);
            }
        }
        const float inv0 = 1.f / o[8], inv1 = 1.f / o[10];
        {
            uint32_t v0 = pack_bf16(o[0] * inv0, o[1] * inv0), v1 = pack_bf16(o[4] * inv0, o[5] * inv0);
            uint32_t v2 = pack_bf16(o[2] * inv1, o[3] * inv1), v3 = pack_bf16(o[6] * inv1, o[7] * inv1);
            const bool o1 = t & 1, o2 = t & 2;
            uint32_t s0 = o1 ? v0 : v1, s1 = o1 ? v2 : v3;
            s0 = __shfl_xor_sync(0xffffffffu, s0, 1); s1 = __shfl_xor_sync(0xffffffffu, s1, 1);
            uint32_t a0 = o1 ? s0 : v0, a1 = o1 ? v1 : s0, b0 = o1 ? s1 : v2, b1 = o1 ? v3 : s1;
            uint32_t x0 = o2 ? a0 : b0, x1 = o2 ? a1 : b1;
            x0 = __shfl_xor_sync(0xffffffffu, x0, 2); x1 = __shfl_xor_sync(0xffffffffu, x1, 2);
            uint4 r;
            r.x = o2 ? x0 : a0; r.y = o2 ? x1 : a1; r.z = o2 ? b0 : x0; r.w = o2 ? b1 : x1;
            *(uint4*)(g_o + (size_t)(row0 + (t >> 1) * 8) * DM + head * 16 + (t & 1) * 8) = r;
        }
        if (tid == 0) TSTAMP0(1, 4 + pass);
    }
    if (wg >= 2) named_arrive(1, 512);
    named_sync(4 + wg, 128);
    if ((tid & 127) == 0) {
        asm volatile("fence.acq_rel.gpu;" ::: "memory");
        asm volatile("red.relaxed.gpu.global.add.u32 [%0], 1;" ::"l"(&g_oflag[(quarter * 8 + 4 + wg) * 32]) : "memory");
        asm volatile("red.relaxed.gpu.global.add.u32 [%0], 1;" ::"l"(&g_oflag[(quarter * 8 + wg) * 32]) : "memory");
    }
    if (tid == 0) TSTAMP0(1, 3);

    if (wg < 2) {
        const int wi = warp;
        const int r0 = mt * 64 + wi * 16 + g;
        const int cb = nt * 128 + wg * 64;
        uint32_t xr[16], wr[8];
#pragma unroll
        for (int j = 0; j < 8; j++) {
            xr[2 * j] = __ldg((const uint32_t*)(x + (size_t)r0 * DM + cb + 8 * j + 2 * t));
            xr[2 * j + 1] = __ldg((const uint32_t*)(x + (size_t)(r0 + 8) * DM + cb + 8 * j + 2 * t));
            wr[j] = __ldg((const uint32_t*)(w_r + cb + 8 * j + 2 * t));
        }
        if (tid == 0) {
            int spins = 0;
            while (ld_acquire(&g_oflag[mt * 32]) < 32u && ++spins < (1 << 20)) __nanosleep(20);
        }
        if (tid == 0) TSTAMP0(2, 7);
        named_sync(1, 512);
        if (tid == 128 && blockIdx.x < FF / 16) {
            mbar_expect_tx(gbar, 32768);
            for (int i = 0; i < 4; i++) {
                tma_load_2d(sb + i * KF_CH_S + 16384, &tm_g, blockIdx.x * 16, i * 128, gbar);
                tma_load_2d(sb + (4 + i) * KF_CH_S + 16384, &tm_u, blockIdx.x * 16, i * 128, gbar);
            }
        }
        if (tid == 0) {
            asm volatile("fence.proxy.async;" ::: "memory");
            TSTAMP0(2, 1);
            for (int k2 = 0; k2 < 4; k2++) {
                mbar_expect_tx(obar + 8 * k2, 16384);
                tma_load_3d(sb + (4 + k2) * KF_CH_S, &tm_o, 0, mt * 64, k2 * 2, obar + 8 * k2);
            }
        }
        float wsum = 0.f;
        {
            const uint4 a = __ldg((const uint4*)(w_r + lane * 16)), b = __ldg((const uint4*)(w_r + lane * 16 + 8));
            const uint32_t w[8] = {a.x, a.y, a.z, a.w, b.x, b.y, b.z, b.w};
#pragma unroll
            for (int i = 0; i < 8; i++) wsum += bf_lo(w[i]) + bf_hi(w[i]);
#pragma unroll
            for (int o = 16; o > 0; o >>= 1) wsum += __shfl_xor_sync(0xffffffffu, wsum, o);
        }
        float acc[32];
#pragma unroll
        for (int i = 0; i < 32; i++) acc[i] = 0.f;
        fence_regs(acc);
#pragma unroll 1
        for (int kb = 0; kb < 8; kb++) {
            mbar_wait(wbar + 8 * kb, 0);
            mbar_wait(obar + 8 * (kb >> 1), 0);
            const uint32_t wa = (kb < 4) ? (KF_OFF_WO + kb * 16384) : ((kb - 4) * KF_CH_S);
            const uint64_t da = make_desc(sb + (4 + (kb >> 1)) * KF_CH_S + (kb & 1) * 8192, 16, 1024, 1);
            const uint64_t db = make_desc(sb + wa + wg * 8192, 1024, 1024, 1);
            wg_fence();
#pragma unroll
            for (int k = 0; k < 4; k++) wgmma_k3_n64(acc, da + k * 2, db + k * 128, (kb | k) != 0);
            wg_commit();
        }
        wg_wait<0>();
        fence_regs(acc);
        if (tid == 0) TSTAMP0(2, 2);
        float hv[32];
        uint32_t hp[16];
        float s0 = 0.f, s1 = 0.f, d0 = 0.f, d1 = 0.f;
#pragma unroll
        for (int j = 0; j < 8; j++) {
            const uint32_t a01 = pack_bf16(acc[4 * j], acc[4 * j + 1]), a23 = pack_bf16(acc[4 * j + 2], acc[4 * j + 3]);
            hp[2 * j] = pack_bf16(bf_lo(xr[2 * j]) + bf_lo(a01), bf_hi(xr[2 * j]) + bf_hi(a01));
            hp[2 * j + 1] = pack_bf16(bf_lo(xr[2 * j + 1]) + bf_lo(a23), bf_hi(xr[2 * j + 1]) + bf_hi(a23));
            hv[4 * j] = bf_lo(hp[2 * j]); hv[4 * j + 1] = bf_hi(hp[2 * j]);
            hv[4 * j + 2] = bf_lo(hp[2 * j + 1]); hv[4 * j + 3] = bf_hi(hp[2 * j + 1]);
            const float wl = bf_lo(wr[j]), wh = bf_hi(wr[j]);
            s0 += hv[4 * j] + hv[4 * j + 1];
            s1 += hv[4 * j + 2] + hv[4 * j + 3];
            d0 = fmaf(hv[4 * j], wl, fmaf(hv[4 * j + 1], wh, d0));
            d1 = fmaf(hv[4 * j + 2], wl, fmaf(hv[4 * j + 3], wh, d1));
        }
        float mu0 = s0 * (1.f / 16), mu1 = s1 * (1.f / 16);
        float q0 = 0.f, q1 = 0.f;
#pragma unroll
        for (int j = 0; j < 8; j++) {
            float a = hv[4 * j] - mu0, b = hv[4 * j + 1] - mu0, c = hv[4 * j + 2] - mu1, d = hv[4 * j + 3] - mu1;
            q0 = fmaf(a, a, fmaf(b, b, q0));
            q1 = fmaf(c, c, fmaf(d, d, q1));
        }
#pragma unroll
        for (int o = 1; o < 4; o <<= 1) {
            const float m0 = __shfl_xor_sync(0xffffffffu, mu0, o), m1 = __shfl_xor_sync(0xffffffffu, mu1, o);
            const float e0 = __shfl_xor_sync(0xffffffffu, q0, o), e1 = __shfl_xor_sync(0xffffffffu, q1, o);
            d0 += __shfl_xor_sync(0xffffffffu, d0, o);
            d1 += __shfl_xor_sync(0xffffffffu, d1, o);
            const float f0 = mu0 - m0, f1 = mu1 - m1;
            q0 = q0 + e0 + f0 * f0 * (8.f * o);
            q1 = q1 + e1 + f1 * f1 * (8.f * o);
            mu0 = 0.5f * (mu0 + m0); mu1 = 0.5f * (mu1 + m1);
        }
        float4* part = g_part + (size_t)mt * 512 + wi * 16 + g;
        if (t < 2) {
            float4* dst = part + (nt * 2 + wg) * 64 + t * 8;
            const float a = t ? mu1 : mu0, b = t ? q1 : q0, c = t ? d1 : d0;
            asm volatile("st.relaxed.gpu.global.v4.f32 [%0], {%1, %2, %3, %4};" ::"l"(dst), "f"(a), "f"(b), "f"(c), "f"(1.0f) : "memory");
        }
        if (tid == 0) TSTAMP0(2, 5);
        const uint32_t stg_off = KF_OFF_WO + (wi >> 1) * 16384 + wg * 8192 + (wi & 1) * 4096;
        const uint32_t stg_o = sb + stg_off, stg_h = stg_o + 2048;
        const int srow = (lane & 7) + ((lane >> 3) & 1) * 8;
        const int sj = lane >> 4;
        named_sync(4 + wg, 128);
#pragma unroll
        for (int j = 0; j < 8; j += 2) {
            const uint32_t off = srow * 128 + (((j + sj) ^ (srow & 7)) << 4);
            stmatrix_x4(stg_h + off, hp[2 * j], hp[2 * j + 1], hp[2 * j + 2], hp[2 * j + 3]);
        }
        __syncwarp();
#pragma unroll
        for (int i = 0; i < 4; i++) {
            const int row = i * 4 + (lane >> 3), ch = lane & 7;
            const uint4 vh = *(const uint4*)(sp + stg_off + 2048 + row * 128 + ((ch ^ (row & 7)) << 4));
            *(uint4*)(g_h + (size_t)(mt * 64 + wi * 16 + row) * DM + cb + ch * 8) = vh;
        }
        named_arrive(8, 288);
        if (tid == 0) TSTAMP0(2, 6);
        float mean[2], den[2], rr[2];
        {
            float4 v[4];
            int spins = 0;
            while (true) {
#pragma unroll
                for (int i = 0; i < 4; i++) {
                    const float4* p = part + (t + (i & 1) * 4) * 64 + (i >> 1) * 8;
                    asm volatile("ld.relaxed.gpu.global.v4.f32 {%0, %1, %2, %3}, [%4];" : "=f"(v[i].x), "=f"(v[i].y), "=f"(v[i].z), "=f"(v[i].w) : "l"(p) : "memory");
                }
                const bool ok = (v[0].w != 0.f) && (v[1].w != 0.f) && (v[2].w != 0.f) && (v[3].w != 0.f);
                if (__all_sync(0xffffffffu, ok) || ++spins > (1 << 20)) break;
                __nanosleep(40);
            }
#pragma unroll
            for (int u = 0; u < 2; u++) {
                float mu = v[2 * u].x + v[2 * u + 1].x, m2 = v[2 * u].y + v[2 * u + 1].y, hw = v[2 * u].z + v[2 * u + 1].z;
#pragma unroll
                for (int o = 1; o < 4; o <<= 1) {
                    mu += __shfl_xor_sync(0xffffffffu, mu, o);
                    m2 += __shfl_xor_sync(0xffffffffu, m2, o);
                    hw += __shfl_xor_sync(0xffffffffu, hw, o);
                }
                mu *= 0.125f;
                const float da = v[2 * u].x - mu, db = v[2 * u + 1].x - mu;
                float dd = 64.f * (da * da + db * db);
#pragma unroll
                for (int o = 1; o < 4; o <<= 1) dd += __shfl_xor_sync(0xffffffffu, dd, o);
                m2 += dd;
                mean[u] = rbf(mu);
                den[u] = rbf(sqrtf(rbf(rbf(m2 * (1.f / DM)) + 1e-5f)));
                rr[u] = rbf((hw - mean[u] * wsum) / den[u]);
            }
        }
        if (tid == 0) TSTAMP0(2, 3);
        named_arrive(3, 512);
        if (nt == 0 && wg == 0) {
            float2* s_st = (float2*)(sp + KF_OFF_WO + 49152);
            if (t == 0) {
                s_key[wi * 16 + g] = ((unsigned long long)order_bits(rr[0]) << 32) | (uint32_t)(0x7FFFFFFF - (r0 + 1));
                s_key[wi * 16 + g + 8] = ((unsigned long long)order_bits(rr[1]) << 32) | (uint32_t)(0x7FFFFFFF - (r0 + 9));
                s_st[wi * 16 + g] = make_float2(mean[0], den[0]);
                s_st[wi * 16 + g + 8] = make_float2(mean[1], den[1]);
            }
            named_sync(4, 128);
            if (warp == 0) {
                unsigned long long a = s_key[lane], b = s_key[lane + 32];
                if (b > a) { const unsigned long long c = a; a = b; b = c; }
                warp_top2(a, b);
                if (lane < 2) {
                    const unsigned long long k = lane ? b : a;
                    const int tok1 = 0x7FFFFFFF - (int)(uint32_t)k;
                    const float2 st = s_st[(tok1 - 1) & 63];
                    asm volatile("st.relaxed.gpu.global.v4.u32 [%0], {%1, %2, %3, %4};" ::"l"(g_cand + mt * 2 + lane), "r"((uint32_t)(k >> 32)),
                                 "r"((uint32_t)tok1), "r"(__float_as_uint(st.x)), "r"(__float_as_uint(st.y)) : "memory");
                }
            }
        }
        const float i0 = 1.f / den[0], i1 = 1.f / den[1];
#pragma unroll
        for (int j = 0; j < 8; j += 2) {
            uint32_t ro[4];
#pragma unroll
            for (int u = 0; u < 2; u++) {
                const int jj = j + u;
                const float a = hv[4 * jj], b = hv[4 * jj + 1], c = hv[4 * jj + 2], d = hv[4 * jj + 3];
                const uint32_t u01 = pack_bf16(a - mean[0], b - mean[0]), u23 = pack_bf16(c - mean[1], d - mean[1]);
                const uint32_t n01 = pack_bf16(bf_lo(u01) * i0, bf_hi(u01) * i0), n23 = pack_bf16(bf_lo(u23) * i1, bf_hi(u23) * i1);
                ro[2 * u] = pack_bf16(a + bf_lo(n01), b + bf_hi(n01));
                ro[2 * u + 1] = pack_bf16(c + bf_lo(n23), d + bf_hi(n23));
            }
            const uint32_t off = srow * 128 + (((j + sj) ^ (srow & 7)) << 4);
            stmatrix_x4(stg_o + off, ro[0], ro[1], ro[2], ro[3]);
        }
        __syncwarp();
#pragma unroll
        for (int i = 0; i < 4; i++) {
            const int row = i * 4 + (lane >> 3), ch = lane & 7;
            const uint4 vo = *(const uint4*)(sp + stg_off + row * 128 + ((ch ^ (row & 7)) << 4));
            *(uint4*)(out + (size_t)(mt * 64 + wi * 16 + row) * DM + cb + ch * 8) = vo;
        }
        named_sync(4 + wg, 128);
        if ((tid & 127) == 0) red_release_add(&g_sflag[mt]);
        if (tid == 0) TSTAMP0(2, 4);
    } else {
        const bool worker = blockIdx.x < FF / 16;
        const bool downer = blockIdx.x >= 64;
        const int mtid = tid - 256, mwarp = mtid >> 5;
        const int c0 = (blockIdx.x - 64) * 8;
        float* s_x = (float*)(sp + KF_OFF_WO + 49152 + 8192);
        float* s_red = (float*)(sp + KF_OFF_WO + 49152 + 8192 + 4096);
        if (mwarp == 1) {
            named_sync(8, 288);
            if (lane == 0) {
                red_release_add(&g_hflag[mt]);
                if (downer) {
                    mbar_expect_tx(dbar, 7 * 4096);
                    for (int i = 0; i < 7; i++) tma_load_2d(sb + (4 + (i >> 2)) * KF_CH_S + (i & 3) * 4096, &tm_d, c0, i * 256, dbar);
                }
            }
            __syncwarp();
        }
        if (mtid == 0) TSTAMP0(3, 0);
        named_sync(3, 512);
        if (mwarp == 0) {
            uint4 ca, cb4;
            int spins = 0;
            while (true) {
                asm volatile("ld.relaxed.gpu.global.v4.u32 {%0, %1, %2, %3}, [%4];" : "=r"(ca.x), "=r"(ca.y), "=r"(ca.z), "=r"(ca.w) : "l"(g_cand + 2 * lane) : "memory");
                asm volatile("ld.relaxed.gpu.global.v4.u32 {%0, %1, %2, %3}, [%4];" : "=r"(cb4.x), "=r"(cb4.y), "=r"(cb4.z), "=r"(cb4.w) : "l"(g_cand + 2 * lane + 1) : "memory");
                const unsigned int hf = ld_acquire(&g_hflag[lane]);
                const bool ok = ca.y != 0 && cb4.y != 0 && hf >= 4u;
                if (__all_sync(0xffffffffu, ok) || ++spins > (1 << 20)) break;
                __nanosleep(20);
            }
            unsigned long long ka = cand_key(ca), kb = cand_key(cb4);
            const unsigned long long mya = ka, myb = kb;
            warp_top2(ka, kb);
            if (mya == ka) s_sel[0] = ca;
            if (myb == ka) s_sel[0] = cb4;
            if (mya == kb) s_sel[1] = ca;
            if (myb == kb) s_sel[1] = cb4;
        }
        named_sync(2, 256);
        if (mtid == 0) TSTAMP0(3, 1);
        int idx[2];
        float mean[2], inv[2], rv[2];
#pragma unroll
        for (int u = 0; u < 2; u++) {
            const uint4 c = s_sel[u];
            idx[u] = (int)c.y - 1;
            rv[u] = order_value(c.x);
            mean[u] = __uint_as_float(c.z);
            inv[u] = 1.f / __uint_as_float(c.w);
        }
        float hfin = 0.f;
        if (downer && mtid < 16) hfin = __bfloat162float(__ldcg((const __nv_bfloat16*)(g_h + (size_t)((mtid >> 3) ? idx[1] : idx[0]) * DM + c0 + (mtid & 7))));
        if (worker) {
#pragma unroll
            for (int u = 0; u < 2; u++) {
                const uint32_t ho = __ldcg((const uint32_t*)(g_h + (size_t)idx[u] * DM + 2 * mtid));
                *(float2*)(s_x + u * 512 + 2 * mtid) = make_float2(rbf(rbf(bf_lo(ho) - mean[u]) * inv[u]), rbf(rbf(bf_hi(ho) - mean[u]) * inv[u]));
            }
            if (mtid == 0) TSTAMP0(3, 5);
            mbar_wait(gbar, 0);
            named_sync(2, 256);
            if (mtid == 0) TSTAMP0(3, 6);
            float acc[8];
#pragma unroll
            for (int i = 0; i < 8; i++) acc[i] = 0.f;
            const uint8_t* wbase = sp + (mwarp >> 2) * (4 * KF_CH_S) + 16384 + lane * 32 + (mwarp & 3) * 8;
#pragma unroll
            for (int k = 0; k < 16; k++) {
                const uint2 w = *(const uint2*)(wbase + (k >> 2) * KF_CH_S + (k & 3) * 1024);
                const float x0 = s_x[lane + 32 * k], x1 = s_x[512 + lane + 32 * k];
                const float w0 = bf_lo(w.x), w1 = bf_hi(w.x), w2 = bf_lo(w.y), w3 = bf_hi(w.y);
                acc[0] = fmaf(x0, w0, acc[0]); acc[1] = fmaf(x0, w1, acc[1]); acc[2] = fmaf(x0, w2, acc[2]); acc[3] = fmaf(x0, w3, acc[3]);
                acc[4] = fmaf(x1, w0, acc[4]); acc[5] = fmaf(x1, w1, acc[5]); acc[6] = fmaf(x1, w2, acc[6]); acc[7] = fmaf(x1, w3, acc[7]);
            }
#define KF_STEP(O, N)                                                          \
            {                                                                  \
                const bool up = (lane & (O)) != 0;                             \
                _Pragma("unroll") for (int i = 0; i < (N); i++) {              \
                    const float send = up ? acc[i] : acc[i + (N)];             \
                    const float keep = up ? acc[i + (N)] : acc[i];             \
                    acc[i] = keep + __shfl_xor_sync(0xffffffffu, send, (O));   \
                }                                                              \
            }
            KF_STEP(16, 4) KF_STEP(8, 2) KF_STEP(4, 1)
            acc[0] += __shfl_xor_sync(0xffffffffu, acc[0], 2);
            acc[0] += __shfl_xor_sync(0xffffffffu, acc[0], 1);
            if ((lane & 3) == 0) {
                const int v = ((lane & 16) ? 4 : 0) + ((lane & 8) ? 2 : 0) + ((lane & 4) ? 1 : 0);
                s_gu[(v >> 2) * 32 + mwarp * 4 + (v & 3)] = acc[0];
            }
            named_sync(2, 256);
            if (mtid < 16) {
                uint32_t a2 = 0;
#pragma unroll
                for (int u = 0; u < 2; u++) {
                    const float gb = rbf(s_gu[u * 32 + mtid]);
                    const float sg = rbf(gb / (1.f + __expf(-gb)));
                    float a = sg * rbf(s_gu[u * 32 + 16 + mtid]);
                    uint32_t ab = (uint32_t)__bfloat16_as_ushort(__float2bfloat16_rn(a));
                    if (ab == 0xFFFFu) ab = 0x7FFFu;
                    a2 |= ab << (16 * u);
                }
                asm volatile("st.relaxed.gpu.global.u32 [%0], %1;" ::"l"(g_act + blockIdx.x * 16 + mtid), "r"(a2) : "memory");
            }
            if (mtid == 0) TSTAMP0(3, 2);
        }
        if (downer) {
            uint32_t av[7];
            {
                int spins = 0;
                while (true) {
                    bool ok = true;
#pragma unroll
                    for (int j = 0; j < 7; j++) {
                        asm volatile("ld.relaxed.gpu.global.u32 %0, [%1];" : "=r"(av[j]) : "l"(g_act + mtid + 256 * j) : "memory");
                        ok = ok && ((av[j] & 0xFFFFu) != 0xFFFFu) && ((av[j] >> 16) != 0xFFFFu);
                    }
                    if (mtid < 2) ok = ok && (ld_acquire(&g_sflag[(mtid ? idx[1] : idx[0]) >> 6]) >= 8u);
                    if (__all_sync(0xffffffffu, ok) || ++spins > (1 << 20)) break;
                    __nanosleep(20);
                }
            }
            if (mtid == 0) TSTAMP0(3, 3);
            mbar_wait(dbar, 0);
            float acc[16];
#pragma unroll
            for (int i = 0; i < 16; i++) acc[i] = 0.f;
#pragma unroll
            for (int j = 0; j < 7; j++) {
                const uint4 w = *(const uint4*)(sp + (4 + (j >> 2)) * KF_CH_S + (j & 3) * 4096 + mtid * 16);
                const float a0 = bf_lo(av[j]), a1 = bf_hi(av[j]);
                const uint32_t ww[4] = {w.x, w.y, w.z, w.w};
#pragma unroll
                for (int q = 0; q < 4; q++) {
                    const float wl = bf_lo(ww[q]), wh = bf_hi(ww[q]);
                    acc[2 * q] = fmaf(a0, wl, acc[2 * q]); acc[2 * q + 1] = fmaf(a0, wh, acc[2 * q + 1]);
                    acc[8 + 2 * q] = fmaf(a1, wl, acc[8 + 2 * q]); acc[8 + 2 * q + 1] = fmaf(a1, wh, acc[8 + 2 * q + 1]);
                }
            }
            KF_STEP(16, 8) KF_STEP(8, 4) KF_STEP(4, 2) KF_STEP(2, 1)
            acc[0] += __shfl_xor_sync(0xffffffffu, acc[0], 1);
            if ((lane & 1) == 0) {
                const int v = ((lane & 16) ? 8 : 0) + ((lane & 8) ? 4 : 0) + ((lane & 4) ? 2 : 0) + ((lane & 2) ? 1 : 0);
                s_red[mwarp * 16 + v] = acc[0];
            }
            named_sync(2, 256);
            if (mtid < 16) {
                const int u = mtid >> 3;
                float y = 0.f;
#pragma unroll
                for (int w = 0; w < 8; w++) y += s_red[w * 16 + mtid];
                const float sig = rbf(1.f / (1.f + __expf(-(u ? rv[1] : rv[0]))));
                const float xn = rbf(rbf(hfin - (u ? mean[1] : mean[0])) * (u ? inv[1] : inv[0]));
                const float ov = hfin + rbf(xn + rbf(rbf(y) * sig));
                out[(size_t)(u ? idx[1] : idx[0]) * DM + c0 + (mtid & 7)] = __float2bfloat16_rn(ov);
            }
            if (blockIdx.x == gridDim.x - 1 && mtid == 0) g_epoch = g_epoch + 1u;
            if (mtid == 0) TSTAMP0(3, 4);
        }
    }
}

typedef CUresult (*PFN_encodeTiled)(CUtensorMap*, CUtensorMapDataType, cuuint32_t, void*, const cuuint64_t*, const cuuint64_t*,
                                    const cuuint32_t*, const cuuint32_t*, CUtensorMapInterleave, CUtensorMapSwizzle,
                                    CUtensorMapL2promotion, CUtensorMapFloatOOBfill);

void make_map(PFN_encodeTiled enc, CUtensorMap* m, const void* ptr, uint64_t cols, uint64_t rows, uint32_t bcols, uint32_t brows) {
    cuuint64_t dims[2] = {cols, rows};
    cuuint64_t strides[1] = {cols * 2};
    cuuint32_t box[2] = {bcols, brows};
    cuuint32_t es[2] = {1, 1};
    enc(m, CU_TENSOR_MAP_DATA_TYPE_BFLOAT16, 2, const_cast<void*>(ptr), dims, strides, box, es, CU_TENSOR_MAP_INTERLEAVE_NONE,
        CU_TENSOR_MAP_SWIZZLE_128B, CU_TENSOR_MAP_L2_PROMOTION_L2_256B, CU_TENSOR_MAP_FLOAT_OOB_FILL_NONE);
}

void make_map3(PFN_encodeTiled enc, CUtensorMap* m, const void* ptr, uint64_t d0, uint64_t rows, uint64_t d2, uint64_t row_stride_bytes,
               uint64_t d2_stride_bytes, uint32_t b0, uint32_t b1, uint32_t b2) {
    cuuint64_t dims[3] = {d0, rows, d2};
    cuuint64_t strides[2] = {row_stride_bytes, d2_stride_bytes};
    cuuint32_t box[3] = {b0, b1, b2};
    cuuint32_t es[3] = {1, 1, 1};
    enc(m, CU_TENSOR_MAP_DATA_TYPE_BFLOAT16, 3, const_cast<void*>(ptr), dims, strides, box, es, CU_TENSOR_MAP_INTERLEAVE_NONE,
        CU_TENSOR_MAP_SWIZZLE_128B, CU_TENSOR_MAP_L2_PROMOTION_L2_256B, CU_TENSOR_MAP_FLOAT_OOB_FILL_NONE);
}

void make_map_plain(PFN_encodeTiled enc, CUtensorMap* m, const void* ptr, uint64_t cols, uint64_t rows, uint32_t bcols, uint32_t brows) {
    cuuint64_t dims[2] = {cols, rows};
    cuuint64_t strides[1] = {cols * 2};
    cuuint32_t box[2] = {bcols, brows};
    cuuint32_t es[2] = {1, 1};
    enc(m, CU_TENSOR_MAP_DATA_TYPE_BFLOAT16, 2, const_cast<void*>(ptr), dims, strides, box, es, CU_TENSOR_MAP_INTERLEAVE_NONE,
        CU_TENSOR_MAP_SWIZZLE_NONE, CU_TENSOR_MAP_L2_PROMOTION_NONE, CU_TENSOR_MAP_FLOAT_OOB_FILL_NONE);
}

template <typename... KArgs, typename... Args>
void launch(void (*kern)(KArgs...), int grid, int block, int smem, bool pdl, Args... args) {
    cudaLaunchConfig_t cfg = {};
    cfg.gridDim = dim3(grid);
    cfg.blockDim = dim3(block);
    cfg.dynamicSmemBytes = smem;
    cfg.stream = cudaStreamPerThread;
    cudaLaunchAttribute at[1];
    at[0].id = cudaLaunchAttributeProgrammaticStreamSerialization;
    at[0].val.programmaticStreamSerializationAllowed = 1;
    cfg.attrs = at;
    cfg.numAttrs = pdl ? 1 : 0;
    cudaLaunchKernelEx(&cfg, kern, KArgs(args)...);
}

}

extern "C" void kernel_launch(void* const* d_in, const int* in_sizes, int n_in, void* d_out, int out_size) {
    const __nv_bfloat16* x = (const __nv_bfloat16*)d_in[0];
    const __nv_bfloat16* wqkv = (const __nv_bfloat16*)d_in[1];
    const __nv_bfloat16* wo = (const __nv_bfloat16*)d_in[2];
    const __nv_bfloat16* w_r = (const __nv_bfloat16*)d_in[4];
    const __nv_bfloat16* w_gate = (const __nv_bfloat16*)d_in[5];
    const __nv_bfloat16* w_up = (const __nv_bfloat16*)d_in[6];
    const __nv_bfloat16* w_down = (const __nv_bfloat16*)d_in[7];
    __nv_bfloat16* out = (__nv_bfloat16*)d_out;

    static PFN_encodeTiled enc = nullptr;
    static void* g_o_ptr = nullptr;
    if (!enc) {
        cudaDriverEntryPointQueryResult qres;
        void* fn = nullptr;
        cudaGetDriverEntryPoint("cuTensorMapEncodeTiled", &fn, cudaEnableDefault, &qres);
        enc = (PFN_encodeTiled)fn;
        cudaGetSymbolAddress(&g_o_ptr, g_o);
        cudaFuncSetAttribute(k1_qkv, cudaFuncAttributeMaxDynamicSharedMemorySize, K1_SMEM);
        cudaFuncSetAttribute(kf_main, cudaFuncAttributeMaxDynamicSharedMemorySize, KF_SMEM);
    }
    CUtensorMap tm_x, tm_w, tm_o, tm_wo, tm_g, tm_u, tm_d;
    make_map_plain(enc, &tm_d, w_down, DM, FF, 8, 256);
    make_map_plain(enc, &tm_g, w_gate, FF, DM, 16, 128);
    make_map_plain(enc, &tm_u, w_up, FF, DM, 16, 128);
    make_map(enc, &tm_x, x, DM, SEQ, 64, 128);
    make_map3(enc, &tm_w, wqkv, DM, DM, 3, 3 * DM * 2, DM * 2, 64, 64, 3);
    make_map3(enc, &tm_o, g_o_ptr, 64, SEQ, 8, DM * 2, 128, 64, 64, 2);
    make_map3(enc, &tm_wo, wo, 64, DM, 8, DM * 2, 128, 64, 64, 2);

    const bool pdl = true;
    launch(k1_qkv, 128, 544, K1_SMEM, false, tm_x, tm_w, x);
    launch(kf_main, 128, 512, KF_SMEM, pdl, tm_o, tm_wo, tm_g, tm_u, tm_d, x, wo, w_r, w_gate, w_up, w_down, out);
}
```

```cpp
#include <cuda_runtime.h>
#include <cuda_bf16.h>
#include <cuda.h>
#include <stdint.h>

namespace {

constexpr int SEQ = 2048, DM = 512, NH = 32, FF = 1792;

__device__ __align__(1024) uint8_t g_q[NH * 2 * SEQ * 16];
__device__ __align__(1024) uint8_t g_kv[NH * 8 * 16384];
__device__ float g_norm[16 * NH * 3];
__device__ __align__(1024) __nv_bfloat16 g_o[SEQ * DM];
__device__ __align__(1024) __nv_bfloat16 g_h[SEQ * DM];
__device__ __align__(16) uint4 g_cand[64];
__device__ unsigned int g_oflag[32 * 32];
__device__ unsigned int g_hflag[32];
__device__ unsigned int g_sflag[32];
__device__ unsigned int g_act[FF];
__device__ unsigned int g_epoch;
__device__ __align__(16) float4 g_ln1[SEQ];
__device__ __align__(16) float4 g_part[32 * 8 * 64];

#define TSTAMP(K, I)
#define TSTAMP0(K, I)
__device__ __forceinline__ uint32_t smem_u32(const void* p) { return (uint32_t)__cvta_generic_to_shared(p); }
__device__ __forceinline__ void wg_fence() { asm volatile("wgmma.fence.sync.aligned;" ::: "memory"); }
__device__ __forceinline__ void wg_commit() { asm volatile("wgmma.commit_group.sync.aligned;" ::: "memory"); }
template <int N> __device__ __forceinline__ void wg_wait() { asm volatile("wgmma.wait_group.sync.aligned %0;" ::"n"(N) : "memory"); }
template <int N> __device__ __forceinline__ void fence_regs(float (&r)[N]) {
#pragma unroll
    for (int i = 0; i < N; i++) asm volatile("" : "+f"(r[i])::"memory");
}
__device__ __forceinline__ uint64_t make_desc(uint32_t addr, uint32_t lbo, uint32_t sbo, uint32_t swz) {
    uint64_t d = 0;
    d |= (uint64_t)((addr & 0x3FFFF) >> 4);
    d |= (uint64_t)((lbo & 0x3FFFF) >> 4) << 16;
    d |= (uint64_t)((sbo & 0x3FFFF) >> 4) << 32;
    d |= (uint64_t)swz << 62;
    return d;
}
__device__ __forceinline__ void mbar_init(uint32_t bar, uint32_t cnt) {
    asm volatile("mbarrier.init.shared::cta.b64 [%0], %1;" ::"r"(bar), "r"(cnt) : "memory");
}
__device__ __forceinline__ void mbar_expect_tx(uint32_t bar, uint32_t bytes) {
    asm volatile("mbarrier.arrive.expect_tx.shared::cta.b64 _, [%0], %1;" ::"r"(bar), "r"(bytes) : "memory");
}
__device__ __forceinline__ void mbar_arrive(uint32_t bar) {
    asm volatile("mbarrier.arrive.shared::cta.b64 _, [%0];" ::"r"(bar) : "memory");
}
__device__ __forceinline__ void mbar_wait(uint32_t bar, uint32_t parity) {
    asm volatile(
        "{\n.reg .pred p;\nWAIT_%=:\n"
        "mbarrier.try_wait.parity.shared::cta.b64 p, [%0], %1;\n"
        "@p bra DONE_%=;\nbra WAIT_%=;\nDONE_%=:\n}\n" ::"r"(bar), "r"(parity) : "memory");
}
__device__ __forceinline__ void bulk_g2s(uint32_t dst, const void* src, uint32_t bytes, uint32_t bar) {
    asm volatile("cp.async.bulk.shared::cluster.global.mbarrier::complete_tx::bytes [%0], [%1], %2, [%3];" ::"r"(dst),
                 "l"(src), "r"(bytes), "r"(bar) : "memory");
}
__device__ __forceinline__ void bulk_s2g(void* dst, uint32_t src, uint32_t bytes) {
    asm volatile("cp.async.bulk.global.shared::cta.bulk_group [%0], [%1], %2;" ::"l"(dst), "r"(src), "r"(bytes) : "memory");
}
__device__ __forceinline__ void tma_load_2d(uint32_t dst, const CUtensorMap* tm, int c0, int c1, uint32_t bar) {
    asm volatile("cp.async.bulk.tensor.2d.shared::cluster.global.mbarrier::complete_tx::bytes [%0], [%1, {%3, %4}], [%2];" ::"r"(dst),
                 "l"(tm), "r"(bar), "r"(c0), "r"(c1) : "memory");
}
__device__ __forceinline__ void tma_load_3d(uint32_t dst, const CUtensorMap* tm, int c0, int c1, int c2, uint32_t bar) {
    asm volatile("cp.async.bulk.tensor.3d.shared::cluster.global.mbarrier::complete_tx::bytes [%0], [%1, {%3, %4, %5}], [%2];" ::"r"(dst),
                 "l"(tm), "r"(bar), "r"(c0), "r"(c1), "r"(c2) : "memory");
}
__device__ __forceinline__ void tma_load_2d_mc(uint32_t dst, const CUtensorMap* tm, int c0, int c1, uint32_t bar, uint16_t mask) {
    asm volatile("cp.async.bulk.tensor.2d.shared::cluster.global.mbarrier::complete_tx::bytes.multicast::cluster [%0], [%1, {%3, %4}], [%2], %5;" ::"r"(dst),
                 "l"(tm), "r"(bar), "r"(c0), "r"(c1), "h"(mask) : "memory");
}
__device__ __forceinline__ void mbar_arrive_cluster(uint32_t bar, uint32_t cta) {
    asm volatile("{\n.reg .b32 ra;\nmapa.shared::cluster.u32 ra, %0, %1;\nmbarrier.arrive.release.cluster.shared::cluster.b64 _, [ra];\n}" ::"r"(bar), "r"(cta) : "memory");
}
__device__ __forceinline__ void cluster_sync() {
    asm volatile("barrier.cluster.arrive.release.aligned;\nbarrier.cluster.wait.acquire.aligned;" ::: "memory");
}
__device__ __forceinline__ void prefetch_l2(const void* p, uint32_t bytes) {
    asm volatile("cp.async.bulk.prefetch.L2.global [%0], %1;" ::"l"(p), "r"(bytes) : "memory");
}
__device__ __forceinline__ void fence_proxy_async() { asm volatile("fence.proxy.async.shared::cta;" ::: "memory"); }
__device__ __forceinline__ void fence_barrier_init() { asm volatile("fence.mbarrier_init.release.cluster;" ::: "memory"); }
__device__ __forceinline__ void pdl_launch() { asm volatile("griddepcontrol.launch_dependents;" ::: "memory"); }
__device__ __forceinline__ void pdl_wait() { asm volatile("griddepcontrol.wait;" ::: "memory"); }
__device__ __forceinline__ void named_sync(int id, int n) { asm volatile("bar.sync %0, %1;" ::"r"(id), "r"(n) : "memory"); }
__device__ __forceinline__ void named_arrive(int id, int n) { asm volatile("bar.arrive %0, %1;" ::"r"(id), "r"(n) : "memory"); }

__device__ __forceinline__ float ex2f(float x) { float y; asm("ex2.approx.ftz.f32 %0, %1;" : "=f"(y) : "f"(x)); return y; }
__device__ __forceinline__ uint32_t pack_bf16(float lo, float hi) {
    uint32_t r; asm("cvt.rn.bf16x2.f32 %0, %1, %2;" : "=r"(r) : "f"(hi), "f"(lo)); return r;
}
__device__ __forceinline__ float bf_lo(uint32_t v) { return __uint_as_float(v << 16); }
__device__ __forceinline__ float bf_hi(uint32_t v) { return __uint_as_float(v & 0xFFFF0000u); }
__device__ __forceinline__ float rbf(float x) { return __bfloat162float(__float2bfloat16_rn(x)); }
__device__ __forceinline__ uint32_t fma_bf16x2(uint32_t a, uint32_t b, uint32_t c) {
    uint32_t r; asm("fma.rn.bf16x2 %0, %1, %2, %3;" : "=r"(r) : "r"(a), "r"(b), "r"(c)); return r;
}
__device__ __forceinline__ void stmatrix_x4(uint32_t addr, uint32_t r0, uint32_t r1, uint32_t r2, uint32_t r3) {
    asm volatile("stmatrix.sync.aligned.m8n8.x4.shared.b16 [%0], {%1, %2, %3, %4};" ::"r"(addr), "r"(r0), "r"(r1), "r"(r2), "r"(r3) : "memory");
}
__device__ __forceinline__ void stmatrix_x4_trans(uint32_t addr, uint32_t r0, uint32_t r1, uint32_t r2, uint32_t r3) {
    asm volatile("stmatrix.sync.aligned.m8n8.x4.trans.shared.b16 [%0], {%1, %2, %3, %4};" ::"r"(addr), "r"(r0), "r"(r1), "r"(r2), "r"(r3) : "memory");
}

__device__ __forceinline__ void wgmma_k1_n136(float (&d)[68], uint64_t desca, uint64_t descb, int scale_d) {
  asm volatile("{\n.reg .pred p;\nsetp.ne.b32 p, %70, 0;\n"
    "wgmma.mma_async.sync.aligned.m64n136k16.f32.bf16.bf16 "
    "{%0, %1, %2, %3, %4, %5, %6, %7, %8, %9, %10, %11, %12, %13, %14, %15, %16, %17, %18, %19, %20, %21, %22, %23, %24, %25, %26, %27, %28, %29, %30, %31, %32, %33, %34, %35, %36, %37, %38, %39, %40, %41, %42, %43, %44, %45, %46, %47, %48, %49, %50, %51, %52, %53, %54, %55, %56, %57, %58, %59, %60, %61, %62, %63, %64, %65, %66, %67}, "
    "%68, %69, p, 1, 1, 1, 0;\n}\n"
    : "+f"(d[0]), "+f"(d[1]), "+f"(d[2]), "+f"(d[3]), "+f"(d[4]), "+f"(d[5]), "+f"(d[6]), "+f"(d[7]), "+f"(d[8]), "+f"(d[9]), "+f"(d[10]), "+f"(d[11]), "+f"(d[12]), "+f"(d[13]), "+f"(d[14]), "+f"(d[15]), "+f"(d[16]), "+f"(d[17]), "+f"(d[18]), "+f"(d[19]), "+f"(d[20]), "+f"(d[21]), "+f"(d[22]), "+f"(d[23]), "+f"(d[24]), "+f"(d[25]), "+f"(d[26]), "+f"(d[27]), "+f"(d[28]), "+f"(d[29]), "+f"(d[30]), "+f"(d[31]), "+f"(d[32]), "+f"(d[33]), "+f"(d[34]), "+f"(d[35]), "+f"(d[36]), "+f"(d[37]), "+f"(d[38]), "+f"(d[39]), "+f"(d[40]), "+f"(d[41]), "+f"(d[42]), "+f"(d[43]), "+f"(d[44]), "+f"(d[45]), "+f"(d[46]), "+f"(d[47]), "+f"(d[48]), "+f"(d[49]), "+f"(d[50]), "+f"(d[51]), "+f"(d[52]), "+f"(d[53]), "+f"(d[54]), "+f"(d[55]), "+f"(d[56]), "+f"(d[57]), "+f"(d[58]), "+f"(d[59]), "+f"(d[60]), "+f"(d[61]), "+f"(d[62]), "+f"(d[63]), "+f"(d[64]), "+f"(d[65]), "+f"(d[66]), "+f"(d[67])
    : "l"(desca), "l"(descb), "r"(scale_d));
}
__device__ __forceinline__ void wgmma_qk_n64(float (&d)[32], uint32_t a0, uint32_t a1, uint32_t a2, uint32_t a3, uint64_t descb) {
  asm volatile("{\n.reg .pred p;\nsetp.ne.b32 p, 0, 0;\n"
    "wgmma.mma_async.sync.aligned.m64n64k16.f32.bf16.bf16 "
    "{%0, %1, %2, %3, %4, %5, %6, %7, %8, %9, %10, %11, %12, %13, %14, %15, %16, %17, %18, %19, %20, %21, %22, %23, %24, %25, %26, %27, %28, %29, %30, %31}, "
    "{%32, %33, %34, %35}, %36, p, 1, 1, 0;\n}\n"
    : "=f"(d[0]), "=f"(d[1]), "=f"(d[2]), "=f"(d[3]), "=f"(d[4]), "=f"(d[5]), "=f"(d[6]), "=f"(d[7]), "=f"(d[8]), "=f"(d[9]), "=f"(d[10]), "=f"(d[11]), "=f"(d[12]), "=f"(d[13]), "=f"(d[14]), "=f"(d[15]), "=f"(d[16]), "=f"(d[17]), "=f"(d[18]), "=f"(d[19]), "=f"(d[20]), "=f"(d[21]), "=f"(d[22]), "=f"(d[23]), "=f"(d[24]), "=f"(d[25]), "=f"(d[26]), "=f"(d[27]), "=f"(d[28]), "=f"(d[29]), "=f"(d[30]), "=f"(d[31])
    : "r"(a0), "r"(a1), "r"(a2), "r"(a3), "l"(descb));
}
__device__ __forceinline__ void wgmma_pv_n24(float (&d)[12], uint32_t a0, uint32_t a1, uint32_t a2, uint32_t a3, uint64_t descb) {
  asm volatile("{\n.reg .pred p;\nsetp.eq.b32 p, 0, 0;\n"
    "wgmma.mma_async.sync.aligned.m64n24k16.f32.bf16.bf16 "
    "{%0, %1, %2, %3, %4, %5, %6, %7, %8, %9, %10, %11}, "
    "{%12, %13, %14, %15}, %16, p, 1, 1, 1;\n}\n"
    : "+f"(d[0]), "+f"(d[1]), "+f"(d[2]), "+f"(d[3]), "+f"(d[4]), "+f"(d[5]), "+f"(d[6]), "+f"(d[7]), "+f"(d[8]), "+f"(d[9]), "+f"(d[10]), "+f"(d[11])
    : "r"(a0), "r"(a1), "r"(a2), "r"(a3), "l"(descb));
}
__device__ __forceinline__ void wgmma_k3_n64(float (&d)[32], uint64_t desca, uint64_t descb, int scale_d) {
  asm volatile("{\n.reg .pred p;\nsetp.ne.b32 p, %34, 0;\n"
    "wgmma.mma_async.sync.aligned.m64n64k16.f32.bf16.bf16 "
    "{%0, %1, %2, %3, %4, %5, %6, %7, %8, %9, %10, %11, %12, %13, %14, %15, %16, %17, %18, %19, %20, %21, %22, %23, %24, %25, %26, %27, %28, %29, %30, %31}, "
    "%32, %33, p, 1, 1, 0, 1;\n}\n"
    : "+f"(d[0]), "+f"(d[1]), "+f"(d[2]), "+f"(d[3]), "+f"(d[4]), "+f"(d[5]), "+f"(d[6]), "+f"(d[7]), "+f"(d[8]), "+f"(d[9]), "+f"(d[10]), "+f"(d[11]), "+f"(d[12]), "+f"(d[13]), "+f"(d[14]), "+f"(d[15]), "+f"(d[16]), "+f"(d[17]), "+f"(d[18]), "+f"(d[19]), "+f"(d[20]), "+f"(d[21]), "+f"(d[22]), "+f"(d[23]), "+f"(d[24]), "+f"(d[25]), "+f"(d[26]), "+f"(d[27]), "+f"(d[28]), "+f"(d[29]), "+f"(d[30]), "+f"(d[31])
    : "l"(desca), "l"(descb), "r"(scale_d));
}

constexpr int K1_XS = 17408;
constexpr int K1_WS = 24576;
constexpr int K1_ST = K1_XS + K1_WS;
constexpr int K1_NST = 5;
constexpr int K1_OFF_MISC = K1_NST * K1_ST;
constexpr int K1_SMEM = K1_OFF_MISC + 2048 + 1024;
constexpr float QSCALE = 0.25f * 1.4426950408889634f;

__global__ void __launch_bounds__(544, 1)
k1_qkv(const __grid_constant__ CUtensorMap tm_x, const __grid_constant__ CUtensorMap tm_w, const __nv_bfloat16* __restrict__ x) {
    extern __shared__ uint8_t smem_raw[];
    const uint32_t sraw = smem_u32(smem_raw);
    const uint32_t sb = (sraw + 1023) & ~1023u;
    uint8_t* sp = smem_raw + (sb - sraw);
    const uint32_t full = sb + K1_OFF_MISC;
    const uint32_t empty = full + 64;
    float* s_m = (float*)(sp + K1_OFF_MISC + 256);
    float* s_r = s_m + 128;

    const int tid = threadIdx.x, warp = tid >> 5, lane = tid & 31;
    const int mt = blockIdx.x >> 3, nt = blockIdx.x & 7;
    if (tid == 0) TSTAMP0(0, 0);
    pdl_launch();
    if (tid == 512) {
        for (int i = 0; i < K1_NST; i++) { mbar_init(full + 8 * i, 1); mbar_init(empty + 8 * i, 3); }
        fence_barrier_init();
        for (int kb = 0; kb < K1_NST; kb++) {
            mbar_expect_tx(full + 8 * kb, 16384 + K1_WS);
            tma_load_2d(sb + kb * K1_ST, &tm_x, kb * 64, mt * 128, full + 8 * kb);
            tma_load_3d(sb + kb * K1_ST + K1_XS, &tm_w, nt * 64, kb * 64, 0, full + 8 * kb);
        }
    }
    if (tid < K1_NST * 64) {
        *(uint4*)(sp + (tid >> 6) * K1_ST + 16384 + (tid & 63) * 16) =
            make_uint4(0x3F803F80u, 0x3F803F80u, 0x3F803F80u, 0x3F803F80u);
    }
    fence_proxy_async();
    __syncthreads();

    if (warp == 16) {
        if (lane == 0) {
            for (int kb = K1_NST; kb < 8; kb++) {
                const int s = kb % K1_NST;
                mbar_wait(empty + 8 * s, 0);
                mbar_expect_tx(full + 8 * s, 16384 + K1_WS);
                tma_load_2d(sb + s * K1_ST, &tm_x, kb * 64, mt * 128, full + 8 * s);
                tma_load_3d(sb + s * K1_ST + K1_XS, &tm_w, nt * 64, kb * 64, 0, full + 8 * s);
            }
        }
        __syncwarp();
        if (lane < FF / 128) g_act[blockIdx.x * (FF / 128) + lane] = 0xFFFFFFFFu;
        for (int i = lane; i < 128; i += 32) g_part[blockIdx.x * 128 + i] = make_float4(0.f, 0.f, 0.f, 0.f);
        if (blockIdx.x == 1) { g_cand[lane] = make_uint4(0, 0, 0, 0); g_cand[lane + 32] = make_uint4(0, 0, 0, 0); g_oflag[lane * 32] = 0; g_hflag[lane] = 0; g_sflag[lane] = 0; }
    } else if (warp >= 12) {
        const int r = tid - 384;
        const unsigned int tag = *(volatile unsigned int*)&g_epoch + 1u;
        {
            const int row = mt * 128 + nt * 16 + (r >> 3);
            const uint4* xp = (const uint4*)(x + (size_t)row * DM) + (r & 7);
            uint4 v[8];
#pragma unroll
            for (int i = 0; i < 8; i++) v[i] = __ldg(xp + i * 8);
            float s1 = 0.f;
#pragma unroll
            for (int i = 0; i < 8; i++)
                s1 += ((bf_lo(v[i].x) + bf_hi(v[i].x)) + (bf_lo(v[i].y) + bf_hi(v[i].y))) + ((bf_lo(v[i].z) + bf_hi(v[i].z)) + (bf_lo(v[i].w) + bf_hi(v[i].w)));
#pragma unroll
            for (int o = 1; o < 8; o <<= 1) s1 += __shfl_xor_sync(0xffffffffu, s1, o);
            const float mean = s1 * (1.f / DM);
            float q0 = 0.f, q1 = 0.f;
#pragma unroll
            for (int i = 0; i < 8; i++) {
                const uint32_t w[4] = {v[i].x, v[i].y, v[i].z, v[i].w};
#pragma unroll
                for (int j = 0; j < 4; j++) {
                    const float a = bf_lo(w[j]) - mean, b = bf_hi(w[j]) - mean;
                    q0 = fmaf(a, a, q0); q1 = fmaf(b, b, q1);
                }
            }
            float q = q0 + q1;
#pragma unroll
            for (int o = 1; o < 8; o <<= 1) q += __shfl_xor_sync(0xffffffffu, q, o);
            const float den = rbf(sqrtf(rbf(rbf(q * (1.f / DM)) + 1e-5f)));
            if ((r & 7) == 0)
                asm volatile("st.relaxed.gpu.global.v4.f32 [%0], {%1, %2, %3, %4};" ::"l"(g_ln1 + row), "f"(rbf(mean)), "f"(1.f / den),
                             "f"(__uint_as_float(tag)), "f"(0.f) : "memory");
        }
        if (r == 0) TSTAMP0(0, 6);
        {
            float4 v;
            int spins = 0;
            do {
                asm volatile("ld.relaxed.gpu.global.v4.f32 {%0, %1, %2, %3}, [%4];" : "=f"(v.x), "=f"(v.y), "=f"(v.z), "=f"(v.w) : "l"(g_ln1 + mt * 128 + r) : "memory");
            } while (__float_as_uint(v.z) != tag && ++spins < (1 << 22));
            s_m[r] = v.x;
            s_r[r] = v.y;
        }
        if (r == 0) TSTAMP0(0, 7);
        named_arrive(1, 512);
    } else {
        const int part = warp >> 2, hw = warp & 3;
        float acc[68];
#pragma unroll
        for (int i = 0; i < 68; i++) acc[i] = 0.f;
        fence_regs(acc);
#pragma unroll 1
        for (int kb = 0; kb < 8; kb++) {
            const int s = kb % K1_NST;
            mbar_wait(full + 8 * s, (kb / K1_NST) & 1);
            const uint64_t da = make_desc(sb + s * K1_ST + K1_XS + part * 8192, 1024, 1024, 1);
            const uint64_t db = make_desc(sb + s * K1_ST, 16, 1024, 1);
            wg_fence();
#pragma unroll
            for (int k = 0; k < 4; k++) wgmma_k1_n136(acc, da + k * 128, db + k * 2, (kb | k) != 0);
            wg_commit();
            if (kb > 0 && kb <= 8 - K1_NST) {
                wg_wait<1>();
                if ((tid & 127) == 0) mbar_arrive(empty + 8 * (kb - 1));
            }
        }
        wg_wait<0>();
        fence_regs(acc);
        if (tid == 0) TSTAMP0(0, 1);
        named_sync(1, 512);
        if (tid == 0) TSTAMP0(0, 2);

        const int t = lane & 3;
        const float cs0 = acc[64], cs1 = acc[66];
        const float sc = (part == 0) ? QSCALE : 1.f;
        const uint32_t stg = sb + (hw >> 1) * K1_ST + K1_XS + part * 8192 + (hw & 1) * 4096;
        const uint32_t st_addr = stg + ((lane >> 3) & 1) * 2048 + ((lane >> 4) * 8 + (lane & 7)) * 16;
#pragma unroll
        for (int j = 0; j < 16; j += 2) {
            uint32_t rr[4];
#pragma unroll
            for (int u = 0; u < 2; u++) {
                const int jj = j + u;
                const float2 m2 = *(const float2*)(s_m + 8 * jj + 2 * t);
                const float2 r2 = *(const float2*)(s_r + 8 * jj + 2 * t);
                const float ra = r2.x * sc, rb = r2.y * sc;
                rr[2 * u] = pack_bf16((acc[4 * jj] - m2.x * cs0) * ra, (acc[4 * jj + 1] - m2.y * cs0) * rb);
                rr[2 * u + 1] = pack_bf16((acc[4 * jj + 2] - m2.x * cs1) * ra, (acc[4 * jj + 3] - m2.y * cs1) * rb);
            }
            stmatrix_x4_trans(st_addr + j * 128, rr[0], rr[1], rr[2], rr[3]);
        }
        fence_proxy_async();
        __syncwarp();
        if (tid == 0) TSTAMP0(0, 4);
        const int head = nt * 4 + hw;
        if (lane == 0) {
            uint8_t* dst;
            uint32_t hstride;
            if (part == 0) { dst = g_q + (size_t)head * 65536 + mt * 2048; hstride = 32768; }
            else { dst = g_kv + (size_t)head * 131072 + (mt >> 1) * 16384 + (part - 1) * 8192 + (mt & 1) * 2048; hstride = 4096; }
            bulk_s2g(dst, stg, 2048);
            bulk_s2g(dst + hstride, stg + 2048, 2048);
            asm volatile("cp.async.bulk.commit_group;" ::: "memory");
        }
        float nmax = 0.f;
#pragma unroll
        for (int i = 0; i < 4; i++) {
            const int tok = lane + 32 * i;
            const uint4 a = *(const uint4*)(sp + (stg - sb) + tok * 16);
            const uint4 b = *(const uint4*)(sp + (stg - sb) + 2048 + tok * 16);
            const uint32_t w[8] = {a.x, a.y, a.z, a.w, b.x, b.y, b.z, b.w};
            float n2 = 0.f, n3 = 0.f;
#pragma unroll
            for (int q = 0; q < 8; q++) {
                const float lo = bf_lo(w[q]), hi = bf_hi(w[q]);
                n2 = fmaf(lo, lo, n2); n3 = fmaf(hi, hi, n3);
            }
            n2 += n3;
            nmax = (n2 > nmax || n2 != n2) ? n2 : nmax;
        }
#pragma unroll
        for (int o = 16; o > 0; o >>= 1) {
            const float v = __shfl_xor_sync(0xffffffffu, nmax, o);
            nmax = (v > nmax || v != v) ? v : nmax;
        }
        if (tid == 0) TSTAMP0(0, 5);
        if (lane == 0) {
            g_norm[(head * 16 + mt) * 3 + part] = nmax;
            asm volatile("cp.async.bulk.wait_group.read 0;" ::: "memory");
            if (tid == 0) TSTAMP0(0, 3);
        }
    }
}

constexpr int KF_CH_G = 16384, KF_CH_S = 20480, KF_NCH = 8;
constexpr int KF_OFF_WO = KF_NCH * KF_CH_S;
constexpr int KF_OFF_MISC = KF_OFF_WO + 65536;
constexpr int KF_SMEM = KF_OFF_MISC + 1280 + 1024;

__device__ __forceinline__ uint32_t exp2_pair_poly(float s0, float s1) {
    const float KB = 65536.0f + 127.0f;
    const float t0 = s0 + KB, t1 = s1 + KB;
    const uint32_t w = __byte_perm(__float_as_uint(t0), __float_as_uint(t1), 0x5410);
    uint32_t z;
    asm("lop3.b32 %0, %1, %2, %3, 0xEA;" : "=r"(z) : "r"(w), "r"(0x007F007Fu), "r"(0x3F803F80u));
    uint32_t p = fma_bf16x2(0x3eab3eabu, z, 0xbc73bc73u);
    p = fma_bf16x2(p, z, 0x3f2f3f2fu);
    return p + w - z;
}
#define EMASK 0x5757u
constexpr uint32_t KF_EMASK = EMASK;
template <int LO, int HI>
__device__ __forceinline__ void softmax_part(const float (&s)[32], uint32_t (&p)[16]) {
#pragma unroll
    for (int i = LO; i < HI; i++) {
        if ((KF_EMASK >> i) & 1) p[i] = exp2_pair_poly(s[2 * i], s[2 * i + 1]);
        else p[i] = pack_bf16(ex2f(s[2 * i]), ex2f(s[2 * i + 1]));
    }
}
#define KF_PV(P, OFF)                                                                              \
    _Pragma("unroll") for (int kk = 0; kk < 4; kk++)                                               \
        wgmma_pv_n24(o, P[4 * kk], P[4 * kk + 1], P[4 * kk + 2], P[4 * kk + 3], dv + ((OFF) + kk * 16));

__device__ __forceinline__ uint32_t make_key(float r_bf16, int token) {
    const uint32_t u = __float_as_uint(r_bf16) >> 16;
    const uint32_t o = (u & 0x8000u) ? (~u & 0xFFFFu) : (u | 0x8000u);
    return (o << 16) | (uint32_t)(0xFFFF - token);
}
__device__ __forceinline__ float key_value(uint32_t k) {
    const uint32_t o = k >> 16;
    const uint32_t u = (o & 0x8000u) ? (o & 0x7FFFu) : (~o & 0xFFFFu);
    return __uint_as_float(u << 16);
}
__device__ __forceinline__ int key_token(uint32_t k) { return 0xFFFF - (int)(k & 0xFFFFu); }
__device__ __forceinline__ void warp_top2(uint32_t a, uint32_t b, uint32_t& k1, uint32_t& k2) {
    k1 = __reduce_max_sync(0xffffffffu, a > b ? a : b);
    const uint32_t a2 = (a == k1) ? 0u : a, b2 = (b == k1) ? 0u : b;
    k2 = __reduce_max_sync(0xffffffffu, a2 > b2 ? a2 : b2);
}
__device__ __forceinline__ unsigned int ld_acquire(const unsigned int* p) {
    unsigned int v; asm volatile("ld.acquire.gpu.global.u32 %0, [%1];" : "=r"(v) : "l"(p) : "memory"); return v;
}
__device__ __forceinline__ void red_release_add(unsigned int* p) {
    asm volatile("red.release.gpu.global.add.u32 [%0], 1;" ::"l"(p) : "memory");
}

__global__ void __launch_bounds__(512, 1)
kf_main(const __grid_constant__ CUtensorMap tm_o, const __grid_constant__ CUtensorMap tm_wo,
        const __grid_constant__ CUtensorMap tm_g, const __grid_constant__ CUtensorMap tm_u, const __grid_constant__ CUtensorMap tm_d,
        const __nv_bfloat16* __restrict__ x, const __nv_bfloat16* __restrict__ wo, const __nv_bfloat16* __restrict__ w_r,
        const __nv_bfloat16* __restrict__ w_gate, const __nv_bfloat16* __restrict__ w_up, const __nv_bfloat16* __restrict__ w_down,
        __nv_bfloat16* __restrict__ out) {
    extern __shared__ uint8_t smem_raw[];
    const uint32_t sraw = smem_u32(smem_raw);
    const uint32_t sb = (sraw + 1023) & ~1023u;
    uint8_t* sp = smem_raw + (sb - sraw);
    const uint32_t kvbar = sb + KF_OFF_MISC;
    const uint32_t wbar = kvbar + 64;
    const uint32_t obar = wbar + 64;
    const uint32_t gbar = obar + 32;
    const uint32_t dbar = gbar + 8;
    unsigned int* s_cnt = (unsigned int*)(sp + KF_OFF_MISC + 192);
    uint32_t* s_key = (uint32_t*)(sp + KF_OFF_MISC + 256);
    float* s_gu = (float*)(sp + KF_OFF_MISC + 768);
    uint4* s_sel = (uint4*)(sp + KF_OFF_MISC + 1024);
    const int tid = threadIdx.x;
    const int head = blockIdx.x >> 2, quarter = blockIdx.x & 3;
    const int mt = blockIdx.x >> 2, nt = blockIdx.x & 3;
    if (tid == 0) TSTAMP0(1, 0);
    if (tid == 0) {
        for (int c = 0; c < 22; c++) mbar_init(kvbar + 8 * c, 1);
        for (int c = 0; c < 4; c++) s_cnt[c] = 0;
        fence_barrier_init();
        for (int kb = 0; kb < 4; kb++) {
            mbar_expect_tx(wbar + 8 * kb, 16384);
            tma_load_3d(sb + KF_OFF_WO + kb * 16384, &tm_wo, 0, kb * 64, nt * 2, wbar + 8 * kb);
        }
    }
    if (tid == 32) {
        prefetch_l2((const uint8_t*)wo + blockIdx.x * 4096, 4096);
        prefetch_l2((const uint8_t*)w_gate + blockIdx.x * 14336, 14336);
        prefetch_l2((const uint8_t*)w_up + blockIdx.x * 14336, 14336);
        prefetch_l2((const uint8_t*)w_down + blockIdx.x * 14336, 14336);
    }
    for (int i = tid; i < KF_NCH * 256; i += 512)
        *(uint4*)(sp + (i >> 8) * KF_CH_S + 16384 + (i & 255) * 16) =
            make_uint4(0x3F803F80u, 0x3F803F80u, 0x3F803F80u, 0x3F803F80u);
    fence_proxy_async();
    __syncthreads();
    pdl_wait();
    if (tid == 0) TSTAMP0(1, 1);
    const uint8_t* kvsrc = g_kv + (size_t)head * (KF_NCH * KF_CH_G);
    if (tid == 32) {
        mbar_expect_tx(kvbar, KF_CH_G);
        bulk_g2s(sb, kvsrc, KF_CH_G, kvbar);
    }
    const int wg = tid >> 7, warp = (tid >> 5) & 3, lane = tid & 31, g = lane >> 2, t = lane & 3;
    if (tid < 32) {
        const int m16 = lane & 15;
        float kn = g_norm[(head * 16 + m16) * 3 + 1];
        float vn = g_norm[(head * 16 + m16) * 3 + 2];
        float qn = g_norm[(head * 16 + quarter * 4 + (lane & 3)) * 3 + 0];
        const bool bad = !(kn < 1e30f) || !(vn < 1e30f) || !(qn < 1e30f);
#pragma unroll
        for (int o = 8; o > 0; o >>= 1) {
            kn = fmaxf(kn, __shfl_xor_sync(0xffffffffu, kn, o));
            qn = fmaxf(qn, __shfl_xor_sync(0xffffffffu, qn, o));
        }
        const bool ok = __all_sync(0xffffffffu, !bad && (qn * kn <= 3500.f));
        if (lane == 0) s_cnt[4] = ok ? 1u : 0u;
    }
    uint32_t qn2[2][4];
#pragma unroll
    for (int ps = 0; ps < 2; ps++) {
        const uint8_t* qb = g_q + (size_t)head * 65536 + (quarter * 512 + ps * 256 + wg * 64 + warp * 16 + g) * 16 + t * 4;
        qn2[ps][0] = *(const uint32_t*)(qb);
        qn2[ps][1] = *(const uint32_t*)(qb + 128);
        qn2[ps][2] = *(const uint32_t*)(qb + 32768);
        qn2[ps][3] = *(const uint32_t*)(qb + 32768 + 128);
    }

    __syncthreads();
    const bool fast = __all_sync(0xffffffffu, s_cnt[4] != 0u);
    if (tid == 32) {
        for (int c = 1; c < KF_NCH; c++) {
            mbar_expect_tx(kvbar + 8 * c, KF_CH_G);
            bulk_g2s(sb + c * KF_CH_S, kvsrc + c * KF_CH_G, KF_CH_G, kvbar + 8 * c);
        }
    }
    if (tid == 0) TSTAMP0(1, 8);
    const uint64_t dk0 = make_desc(sb, 4096, 128, 0);
    const uint64_t dv0 = make_desc(sb + 8192, 128, 4096, 0);

#pragma unroll 1
    for (int pass = 0; pass < 2; pass++) {
        const int row0 = quarter * 512 + pass * 256 + wg * 64 + warp * 16 + g;
        uint32_t qa[4];
#pragma unroll
        for (int i = 0; i < 4; i++) qa[i] = pass ? qn2[1][i] : qn2[0][i];
        float o[12];
#pragma unroll
        for (int i = 0; i < 12; i++) o[i] = 0.f;
        fence_regs(o);
#define KF_RELEASE_CHUNK(c)                                                                          \
        if (pass == 1 && (c) >= 1 && (c) <= 4) {                                                     \
            named_sync(4 + wg, 128);            \
            if ((tid & 127) == 0 && atomicAdd(&s_cnt[(c) - 1], 1u) == 3u) {                          \
                mbar_expect_tx(wbar + 8 * (3 + (c)), 16384);                                         \
                tma_load_3d(sb + ((c) - 1) * KF_CH_S, &tm_wo, 0, (3 + (c)) * 64, nt * 2, wbar + 8 * (3 + (c))); \
            }                                                                                        \
        }
        if (fast) {
#pragma unroll 1
            for (int c = 0; c < KF_NCH; c++) {
                const uint64_t dk = dk0 + (uint64_t)(c * (KF_CH_S >> 4));
                const uint64_t dv = dv0 + (uint64_t)(c * (KF_CH_S >> 4));
                float s0[32], s1[32], s2[32], s3[32];
                uint32_t p0[16], p1[16], p2[16], p3[16];
                mbar_wait(kvbar + 8 * c, 0);
                wg_wait<1>();
                wg_fence();
                wgmma_qk_n64(s0, qa[0], qa[1], qa[2], qa[3], dk);
                wg_commit();
                wg_wait<1>();
                KF_RELEASE_CHUNK(c);
                wg_fence();
                wgmma_qk_n64(s1, qa[0], qa[1], qa[2], qa[3], dk + 64);
                wg_commit();
                wg_wait<1>();
                fence_regs(s0);
                softmax_part<0, 16>(s0, p0);
                wg_fence();
                KF_PV(p0, 0);
                wg_commit();
                wg_wait<1>();
                fence_regs(s1);
                softmax_part<0, 8>(s1, p1);
                wg_wait<0>();
                wg_fence();
                wgmma_qk_n64(s2, qa[0], qa[1], qa[2], qa[3], dk + 128);
                wg_commit();
                softmax_part<8, 16>(s1, p1);
                wg_fence();
                KF_PV(p1, 64);
                wg_commit();
                wg_wait<1>();
                fence_regs(s2);
                softmax_part<0, 8>(s2, p2);
                wg_wait<0>();
                wg_fence();
                wgmma_qk_n64(s3, qa[0], qa[1], qa[2], qa[3], dk + 192);
                wg_commit();
                softmax_part<8, 16>(s2, p2);
                wg_fence();
                KF_PV(p2, 128);
                wg_commit();
                wg_wait<1>();
                fence_regs(s3);
                softmax_part<0, 16>(s3, p3);
                wg_fence();
                KF_PV(p3, 192);
                wg_commit();
            }
            wg_wait<0>();
            fence_regs(o);
        } else {
            float m0 = -INFINITY, m1 = -INFINITY;
#pragma unroll 1
            for (int b = 0; b < 32; b++) {
                const int c = b >> 2;
                const uint64_t dk = dk0 + (uint64_t)(c * (KF_CH_S >> 4) + (b & 3) * 64);
                const uint64_t dv = dv0 + (uint64_t)(c * (KF_CH_S >> 4) + (b & 3) * 64);
                float s[32];
                uint32_t p[16];
                mbar_wait(kvbar + 8 * c, 0);
                wg_fence();
                wgmma_qk_n64(s, qa[0], qa[1], qa[2], qa[3], dk);
                wg_commit();
                if ((b & 3) == 0) { KF_RELEASE_CHUNK(c); }
                wg_wait<0>();
                fence_regs(s);
                float x0 = s[0], x1 = s[2];
#pragma unroll
                for (int j = 0; j < 8; j++) {
                    x0 = fmaxf(x0, fmaxf(s[4 * j], s[4 * j + 1]));
                    x1 = fmaxf(x1, fmaxf(s[4 * j + 2], s[4 * j + 3]));
                }
                x0 = fmaxf(x0, __shfl_xor_sync(0xffffffffu, x0, 1));
                x0 = fmaxf(x0, __shfl_xor_sync(0xffffffffu, x0, 2));
                x1 = fmaxf(x1, __shfl_xor_sync(0xffffffffu, x1, 1));
                x1 = fmaxf(x1, __shfl_xor_sync(0xffffffffu, x1, 2));
                const float n0 = fmaxf(m0, x0), n1 = fmaxf(m1, x1);
                const float c0 = ex2f(m0 - n0), c1 = ex2f(m1 - n1);
                m0 = n0; m1 = n1;
#pragma unroll
                for (int j = 0; j < 3; j++) {
                    o[4 * j] *= c0; o[4 * j + 1] *= c0; o[4 * j + 2] *= c1; o[4 * j + 3] *= c1;
                }
#pragma unroll
                for (int j = 0; j < 8; j++) {
                    p[2 * j] = pack_bf16(ex2f(s[4 * j] - n0), ex2f(s[4 * j + 1] - n0));
                    p[2 * j + 1] = pack_bf16(ex2f(s[4 * j + 2] - n1), ex2f(s[4 * j + 3] - n1));
                }
                fence_regs(o);
                wg_fence();
                KF_PV(p, 0);
                wg_commit();
                wg_wait<0>();
                fence_regs(o);
            }
        }
        const float inv0 = 1.f / o[8], inv1 = 1.f / o[10];
        {
            uint32_t v0 = pack_bf16(o[0] * inv0, o[1] * inv0), v1 = pack_bf16(o[4] * inv0, o[5] * inv0);
            uint32_t v2 = pack_bf16(o[2] * inv1, o[3] * inv1), v3 = pack_bf16(o[6] * inv1, o[7] * inv1);
            const bool o1 = t & 1, o2 = t & 2;
            uint32_t s0 = o1 ? v0 : v1, s1 = o1 ? v2 : v3;
            s0 = __shfl_xor_sync(0xffffffffu, s0, 1); s1 = __shfl_xor_sync(0xffffffffu, s1, 1);
            uint32_t a0 = o1 ? s0 : v0, a1 = o1 ? v1 : s0, b0 = o1 ? s1 : v2, b1 = o1 ? v3 : s1;
            uint32_t x0 = o2 ? a0 : b0, x1 = o2 ? a1 : b1;
            x0 = __shfl_xor_sync(0xffffffffu, x0, 2); x1 = __shfl_xor_sync(0xffffffffu, x1, 2);
            uint4 r;
            r.x = o2 ? x0 : a0; r.y = o2 ? x1 : a1; r.z = o2 ? b0 : x0; r.w = o2 ? b1 : x1;
            *(uint4*)(g_o + (size_t)(row0 + (t >> 1) * 8) * DM + head * 16 + (t & 1) * 8) = r;
        }
        if (tid == 0) TSTAMP0(1, 4 + pass);
    }
    if (wg >= 2) named_arrive(1, 512);
    named_sync(4 + wg, 128);
    if ((tid & 127) == 0) {
        asm volatile("fence.acq_rel.gpu;" ::: "memory");
        asm volatile("red.relaxed.gpu.global.add.u32 [%0], 1;" ::"l"(&g_oflag[(quarter * 8 + 4 + wg) * 32]) : "memory");
        asm volatile("red.relaxed.gpu.global.add.u32 [%0], 1;" ::"l"(&g_oflag[(quarter * 8 + wg) * 32]) : "memory");
    }
    if (tid == 0) TSTAMP0(1, 3);

    if (wg < 2) {
        const int wi = warp;
        const int r0 = mt * 64 + wi * 16 + g;
        const int cb = nt * 128 + wg * 64;
        uint32_t xr[16], wr[8];
#pragma unroll
        for (int j = 0; j < 8; j++) {
            xr[2 * j] = __ldg((const uint32_t*)(x + (size_t)r0 * DM + cb + 8 * j + 2 * t));
            xr[2 * j + 1] = __ldg((const uint32_t*)(x + (size_t)(r0 + 8) * DM + cb + 8 * j + 2 * t));
            wr[j] = __ldg((const uint32_t*)(w_r + cb + 8 * j + 2 * t));
        }
        if (tid == 0) {
            int spins = 0;
            while (ld_acquire(&g_oflag[mt * 32]) < 32u && ++spins < (1 << 22)) {}
            asm volatile("fence.proxy.async.global;" ::: "memory");
        }
        if (tid == 0) TSTAMP0(2, 7);
        named_sync(1, 512);
        if (tid == 128 && blockIdx.x < FF / 16) {
            mbar_expect_tx(gbar, 32768);
            for (int i = 0; i < 4; i++) {
                tma_load_2d(sb + i * KF_CH_S + 16384, &tm_g, blockIdx.x * 16, i * 128, gbar);
                tma_load_2d(sb + (4 + i) * KF_CH_S + 16384, &tm_u, blockIdx.x * 16, i * 128, gbar);
            }
        }
        if (tid == 0) {
            TSTAMP0(2, 1);
            for (int k2 = 0; k2 < 4; k2++) {
                mbar_expect_tx(obar + 8 * k2, 16384);
                tma_load_3d(sb + (4 + k2) * KF_CH_S, &tm_o, 0, mt * 64, k2 * 2, obar + 8 * k2);
            }
        }
        float wsum = 0.f;
        {
            const uint4 a = __ldg((const uint4*)(w_r + lane * 16)), b = __ldg((const uint4*)(w_r + lane * 16 + 8));
            const uint32_t w[8] = {a.x, a.y, a.z, a.w, b.x, b.y, b.z, b.w};
#pragma unroll
            for (int i = 0; i < 8; i++) wsum += bf_lo(w[i]) + bf_hi(w[i]);
#pragma unroll
            for (int o = 16; o > 0; o >>= 1) wsum += __shfl_xor_sync(0xffffffffu, wsum, o);
        }
        float acc[32];
#pragma unroll
        for (int i = 0; i < 32; i++) acc[i] = 0.f;
        fence_regs(acc);
#pragma unroll 1
        for (int kb = 0; kb < 8; kb++) {
            mbar_wait(wbar + 8 * kb, 0);
            mbar_wait(obar + 8 * (kb >> 1), 0);
            const uint32_t wa = (kb < 4) ? (KF_OFF_WO + kb * 16384) : ((kb - 4) * KF_CH_S);
            const uint64_t da = make_desc(sb + (4 + (kb >> 1)) * KF_CH_S + (kb & 1) * 8192, 16, 1024, 1);
            const uint64_t db = make_desc(sb + wa + wg * 8192, 1024, 1024, 1);
            wg_fence();
#pragma unroll
            for (int k = 0; k < 4; k++) wgmma_k3_n64(acc, da + k * 2, db + k * 128, (kb | k) != 0);
            wg_commit();
        }
        wg_wait<0>();
        fence_regs(acc);
        if (tid == 0) TSTAMP0(2, 2);
        float hv[32];
        uint32_t hp[16];
        float s0 = 0.f, s1 = 0.f, d0 = 0.f, d1 = 0.f;
#pragma unroll
        for (int j = 0; j < 8; j++) {
            const uint32_t a01 = pack_bf16(acc[4 * j], acc[4 * j + 1]), a23 = pack_bf16(acc[4 * j + 2], acc[4 * j + 3]);
            hp[2 * j] = pack_bf16(bf_lo(xr[2 * j]) + bf_lo(a01), bf_hi(xr[2 * j]) + bf_hi(a01));
            hp[2 * j + 1] = pack_bf16(bf_lo(xr[2 * j + 1]) + bf_lo(a23), bf_hi(xr[2 * j + 1]) + bf_hi(a23));
            hv[4 * j] = bf_lo(hp[2 * j]); hv[4 * j + 1] = bf_hi(hp[2 * j]);
            hv[4 * j + 2] = bf_lo(hp[2 * j + 1]); hv[4 * j + 3] = bf_hi(hp[2 * j + 1]);
            const float wl = bf_lo(wr[j]), wh = bf_hi(wr[j]);
            s0 += hv[4 * j] + hv[4 * j + 1];
            s1 += hv[4 * j + 2] + hv[4 * j + 3];
            d0 = fmaf(hv[4 * j], wl, fmaf(hv[4 * j + 1], wh, d0));
            d1 = fmaf(hv[4 * j + 2], wl, fmaf(hv[4 * j + 3], wh, d1));
        }
        float mu0 = s0 * (1.f / 16), mu1 = s1 * (1.f / 16);
        float q0 = 0.f, q1 = 0.f;
#pragma unroll
        for (int j = 0; j < 8; j++) {
            float a = hv[4 * j] - mu0, b = hv[4 * j + 1] - mu0, c = hv[4 * j + 2] - mu1, d = hv[4 * j + 3] - mu1;
            q0 = fmaf(a, a, fmaf(b, b, q0));
            q1 = fmaf(c, c, fmaf(d, d, q1));
        }
#pragma unroll
        for (int o = 1; o < 4; o <<= 1) {
            const float m0 = __shfl_xor_sync(0xffffffffu, mu0, o), m1 = __shfl_xor_sync(0xffffffffu, mu1, o);
            const float e0 = __shfl_xor_sync(0xffffffffu, q0, o), e1 = __shfl_xor_sync(0xffffffffu, q1, o);
            d0 += __shfl_xor_sync(0xffffffffu, d0, o);
            d1 += __shfl_xor_sync(0xffffffffu, d1, o);
            const float f0 = mu0 - m0, f1 = mu1 - m1;
            q0 = q0 + e0 + f0 * f0 * (8.f * o);
            q1 = q1 + e1 + f1 * f1 * (8.f * o);
            mu0 = 0.5f * (mu0 + m0); mu1 = 0.5f * (mu1 + m1);
        }
        float4* part = g_part + (size_t)mt * 512 + wi * 16 + g;
        if (t < 2) {
            float4* dst = part + (nt * 2 + wg) * 64 + t * 8;
            const float a = t ? mu1 : mu0, b = t ? q1 : q0, c = t ? d1 : d0;
            asm volatile("st.relaxed.gpu.global.v4.f32 [%0], {%1, %2, %3, %4};" ::"l"(dst), "f"(a), "f"(b), "f"(c), "f"(1.0f) : "memory");
        }
        if (tid == 0) TSTAMP0(2, 5);
        const uint32_t stg_off = KF_OFF_WO + (wi >> 1) * 16384 + wg * 8192 + (wi & 1) * 4096;
        const uint32_t stg_o = sb + stg_off, stg_h = stg_o + 2048;
        const int srow = (lane & 7) + ((lane >> 3) & 1) * 8;
        const int sj = lane >> 4;
        named_sync(4 + wg, 128);
#pragma unroll
        for (int j = 0; j < 8; j += 2) {
            const uint32_t off = srow * 128 + (((j + sj) ^ (srow & 7)) << 4);
            stmatrix_x4(stg_h + off, hp[2 * j], hp[2 * j + 1], hp[2 * j + 2], hp[2 * j + 3]);
        }
        __syncwarp();
#pragma unroll
        for (int i = 0; i < 4; i++) {
            const int row = i * 4 + (lane >> 3), ch = lane & 7;
            const uint4 vh = *(const uint4*)(sp + stg_off + 2048 + row * 128 + ((ch ^ (row & 7)) << 4));
            *(uint4*)(g_h + (size_t)(mt * 64 + wi * 16 + row) * DM + cb + ch * 8) = vh;
        }
        named_arrive(8, 288);
        if (tid == 0) TSTAMP0(2, 6);
        float mean[2], den[2], rr[2];
        {
            float4 v[4];
            int spins = 0;
            while (true) {
#pragma unroll
                for (int i = 0; i < 4; i++) {
                    const float4* p = part + (t + (i & 1) * 4) * 64 + (i >> 1) * 8;
                    asm volatile("ld.relaxed.gpu.global.v4.f32 {%0, %1, %2, %3}, [%4];" : "=f"(v[i].x), "=f"(v[i].y), "=f"(v[i].z), "=f"(v[i].w) : "l"(p) : "memory");
                }
                const bool ok = (v[0].w != 0.f) && (v[1].w != 0.f) && (v[2].w != 0.f) && (v[3].w != 0.f);
                if (__all_sync(0xffffffffu, ok) || ++spins > (1 << 22)) break;
            }
#pragma unroll
            for (int u = 0; u < 2; u++) {
                float mu = v[2 * u].x + v[2 * u + 1].x, m2 = v[2 * u].y + v[2 * u + 1].y, hw = v[2 * u].z + v[2 * u + 1].z;
#pragma unroll
                for (int o = 1; o < 4; o <<= 1) {
                    mu += __shfl_xor_sync(0xffffffffu, mu, o);
                    m2 += __shfl_xor_sync(0xffffffffu, m2, o);
                    hw += __shfl_xor_sync(0xffffffffu, hw, o);
                }
                mu *= 0.125f;
                const float da = v[2 * u].x - mu, db = v[2 * u + 1].x - mu;
                float dd = 64.f * (da * da + db * db);
#pragma unroll
                for (int o = 1; o < 4; o <<= 1) dd += __shfl_xor_sync(0xffffffffu, dd, o);
                m2 += dd;
                mean[u] = rbf(mu);
                den[u] = rbf(sqrtf(rbf(rbf(m2 * (1.f / DM)) + 1e-5f)));
                rr[u] = rbf((hw - mean[u] * wsum) / den[u]);
            }
        }
        if (tid == 0) TSTAMP0(2, 3);
        named_arrive(3, 512);
        if (nt == 0 && wg == 0) {
            float2* s_st = (float2*)(sp + KF_OFF_WO + 49152);
            if (t == 0) {
                s_key[wi * 16 + g] = make_key(rr[0], r0);
                s_key[wi * 16 + g + 8] = make_key(rr[1], r0 + 8);
                s_st[wi * 16 + g] = make_float2(mean[0], den[0]);
                s_st[wi * 16 + g + 8] = make_float2(mean[1], den[1]);
            }
            named_sync(4, 128);
            if (warp == 0) {
                uint32_t k1, k2;
                warp_top2(s_key[lane], s_key[lane + 32], k1, k2);
                if (lane < 2) {
                    const uint32_t k = lane ? k2 : k1;
                    const float2 st = s_st[key_token(k) & 63];
                    asm volatile("st.relaxed.gpu.global.v4.u32 [%0], {%1, %2, %3, %4};" ::"l"(g_cand + mt * 2 + lane), "r"(k),
                                 "r"(1u), "r"(__float_as_uint(st.x)), "r"(__float_as_uint(st.y)) : "memory");
                }
            }
        }
        const float i0 = 1.f / den[0], i1 = 1.f / den[1];
#pragma unroll
        for (int j = 0; j < 8; j += 2) {
            uint32_t ro[4];
#pragma unroll
            for (int u = 0; u < 2; u++) {
                const int jj = j + u;
                const float a = hv[4 * jj], b = hv[4 * jj + 1], c = hv[4 * jj + 2], d = hv[4 * jj + 3];
                const uint32_t u01 = pack_bf16(a - mean[0], b - mean[0]), u23 = pack_bf16(c - mean[1], d - mean[1]);
                const uint32_t n01 = pack_bf16(bf_lo(u01) * i0, bf_hi(u01) * i0), n23 = pack_bf16(bf_lo(u23) * i1, bf_hi(u23) * i1);
                ro[2 * u] = pack_bf16(a + bf_lo(n01), b + bf_hi(n01));
                ro[2 * u + 1] = pack_bf16(c + bf_lo(n23), d + bf_hi(n23));
            }
            const uint32_t off = srow * 128 + (((j + sj) ^ (srow & 7)) << 4);
            stmatrix_x4(stg_o + off, ro[0], ro[1], ro[2], ro[3]);
        }
        __syncwarp();
#pragma unroll
        for (int i = 0; i < 4; i++) {
            const int row = i * 4 + (lane >> 3), ch = lane & 7;
            const uint4 vo = *(const uint4*)(sp + stg_off + row * 128 + ((ch ^ (row & 7)) << 4));
            *(uint4*)(out + (size_t)(mt * 64 + wi * 16 + row) * DM + cb + ch * 8) = vo;
        }
        named_sync(4 + wg, 128);
        if ((tid & 127) == 0) red_release_add(&g_sflag[mt]);
        if (tid == 0) TSTAMP0(2, 4);
    } else {
        const bool worker = blockIdx.x < FF / 16;
        const bool downer = blockIdx.x >= 64;
        const int mtid = tid - 256, mwarp = mtid >> 5;
        const int c0 = (blockIdx.x - 64) * 8;
        float* s_x = (float*)(sp + KF_OFF_WO + 49152 + 8192);
        float* s_red = (float*)(sp + KF_OFF_WO + 49152 + 8192 + 4096);
        if (mwarp == 1) {
            named_sync(8, 288);
            if (lane == 0) {
                red_release_add(&g_hflag[mt]);
                if (downer) {
                    mbar_expect_tx(dbar, 7 * 4096);
                    for (int i = 0; i < 7; i++) tma_load_2d(sb + (4 + (i >> 2)) * KF_CH_S + (i & 3) * 4096, &tm_d, c0, i * 256, dbar);
                }
            }
            __syncwarp();
        }
        if (mtid == 0) TSTAMP0(3, 0);
        named_sync(3, 512);
        if (mwarp == 0) {
            uint4 ca, cb4;
            int spins = 0;
            while (true) {
                asm volatile("ld.relaxed.gpu.global.v4.u32 {%0, %1, %2, %3}, [%4];" : "=r"(ca.x), "=r"(ca.y), "=r"(ca.z), "=r"(ca.w) : "l"(g_cand + 2 * lane) : "memory");
                asm volatile("ld.relaxed.gpu.global.v4.u32 {%0, %1, %2, %3}, [%4];" : "=r"(cb4.x), "=r"(cb4.y), "=r"(cb4.z), "=r"(cb4.w) : "l"(g_cand + 2 * lane + 1) : "memory");
                const unsigned int hf = ld_acquire(&g_hflag[lane]);
                const bool ok = ca.y != 0 && cb4.y != 0 && hf >= 4u;
                if (__all_sync(0xffffffffu, ok) || ++spins > (1 << 22)) break;
            }
            uint32_t k1, k2;
            warp_top2(ca.x, cb4.x, k1, k2);
            if (ca.x == k1) s_sel[0] = ca;
            if (cb4.x == k1) s_sel[0] = cb4;
            if (ca.x == k2) s_sel[1] = ca;
            if (cb4.x == k2) s_sel[1] = cb4;
        }
        named_sync(2, 256);
        if (mtid == 0) TSTAMP0(3, 1);
        int idx[2];
        float mean[2], inv[2], rv[2];
#pragma unroll
        for (int u = 0; u < 2; u++) {
            const uint4 c = s_sel[u];
            idx[u] = key_token(c.x);
            rv[u] = key_value(c.x);
            mean[u] = __uint_as_float(c.z);
            inv[u] = 1.f / __uint_as_float(c.w);
        }
        float hfin = 0.f;
        if (downer && mtid < 16) hfin = __bfloat162float(__ldcg((const __nv_bfloat16*)(g_h + (size_t)((mtid >> 3) ? idx[1] : idx[0]) * DM + c0 + (mtid & 7))));
        if (worker) {
            {
                const uint32_t h0 = __ldcg((const uint32_t*)(g_h + (size_t)idx[0] * DM + 2 * mtid));
                const uint32_t h1 = __ldcg((const uint32_t*)(g_h + (size_t)idx[1] * DM + 2 * mtid));
                const uint32_t u0 = pack_bf16(bf_lo(h0) - mean[0], bf_hi(h0) - mean[0]), u1 = pack_bf16(bf_lo(h1) - mean[1], bf_hi(h1) - mean[1]);
                const uint32_t n0 = pack_bf16(bf_lo(u0) * inv[0], bf_hi(u0) * inv[0]), n1 = pack_bf16(bf_lo(u1) * inv[1], bf_hi(u1) * inv[1]);
                *(float4*)(s_x + 4 * mtid) = make_float4(bf_lo(n0), bf_lo(n1), bf_hi(n0), bf_hi(n1));
            }
            if (mtid == 0) TSTAMP0(3, 5);
            mbar_wait(gbar, 0);
            named_sync(2, 256);
            if (mtid == 0) TSTAMP0(3, 6);
            float acc[8];
#pragma unroll
            for (int i = 0; i < 8; i++) acc[i] = 0.f;
            const uint8_t* wbase = sp + (mwarp >> 2) * (4 * KF_CH_S) + 16384 + lane * 32 + (mwarp & 3) * 8;
#pragma unroll
            for (int k = 0; k < 16; k++) {
                const uint2 w = *(const uint2*)(wbase + (k >> 2) * KF_CH_S + (k & 3) * 1024);
                const float2 xx = *(const float2*)(s_x + 2 * (lane + 32 * k));
                const float x0 = xx.x, x1 = xx.y;
                const float w0 = bf_lo(w.x), w1 = bf_hi(w.x), w2 = bf_lo(w.y), w3 = bf_hi(w.y);
                acc[0] = fmaf(x0, w0, acc[0]); acc[1] = fmaf(x0, w1, acc[1]); acc[2] = fmaf(x0, w2, acc[2]); acc[3] = fmaf(x0, w3, acc[3]);
                acc[4] = fmaf(x1, w0, acc[4]); acc[5] = fmaf(x1, w1, acc[5]); acc[6] = fmaf(x1, w2, acc[6]); acc[7] = fmaf(x1, w3, acc[7]);
            }
#define KF_STEP(O, N)                                                          \
            {                                                                  \
                const bool up = (lane & (O)) != 0;                             \
                _Pragma("unroll") for (int i = 0; i < (N); i++) {              \
                    const float send = up ? acc[i] : acc[i + (N)];             \
                    const float keep = up ? acc[i + (N)] : acc[i];             \
                    acc[i] = keep + __shfl_xor_sync(0xffffffffu, send, (O));   \
                }                                                              \
            }
            KF_STEP(16, 4) KF_STEP(8, 2) KF_STEP(4, 1)
            acc[0] += __shfl_xor_sync(0xffffffffu, acc[0], 2);
            acc[0] += __shfl_xor_sync(0xffffffffu, acc[0], 1);
            if ((lane & 3) == 0) {
                const int v = ((lane & 16) ? 4 : 0) + ((lane & 8) ? 2 : 0) + ((lane & 4) ? 1 : 0);
                s_gu[(v >> 2) * 32 + mwarp * 4 + (v & 3)] = acc[0];
            }
            named_sync(2, 256);
            if (mtid < 16) {
                uint32_t a2 = 0;
#pragma unroll
                for (int u = 0; u < 2; u++) {
                    const float gb = rbf(s_gu[u * 32 + mtid]);
                    const float sg = rbf(gb / (1.f + __expf(-gb)));
                    float a = sg * rbf(s_gu[u * 32 + 16 + mtid]);
                    uint32_t ab = (uint32_t)__bfloat16_as_ushort(__float2bfloat16_rn(a));
                    if (ab == 0xFFFFu) ab = 0x7FFFu;
                    a2 |= ab << (16 * u);
                }
                asm volatile("st.relaxed.gpu.global.u32 [%0], %1;" ::"l"(g_act + blockIdx.x * 16 + mtid), "r"(a2) : "memory");
            }
            if (mtid == 0) TSTAMP0(3, 2);
        }
        if (downer) {
            uint32_t av[7];
            {
                int spins = 0;
                while (true) {
                    bool ok = true;
#pragma unroll
                    for (int j = 0; j < 7; j++) {
                        asm volatile("ld.relaxed.gpu.global.u32 %0, [%1];" : "=r"(av[j]) : "l"(g_act + mtid + 256 * j) : "memory");
                        ok = ok && ((av[j] & 0xFFFFu) != 0xFFFFu) && ((av[j] >> 16) != 0xFFFFu);
                    }
                    if (mtid < 2) ok = ok && (ld_acquire(&g_sflag[(mtid ? idx[1] : idx[0]) >> 6]) >= 8u);
                    if (__all_sync(0xffffffffu, ok) || ++spins > (1 << 20)) break;
                    __nanosleep(20);
                }
            }
            if (mtid == 0) TSTAMP0(3, 3);
            mbar_wait(dbar, 0);
            float acc[16];
#pragma unroll
            for (int i = 0; i < 16; i++) acc[i] = 0.f;
#pragma unroll
            for (int j = 0; j < 7; j++) {
                const uint4 w = *(const uint4*)(sp + (4 + (j >> 2)) * KF_CH_S + (j & 3) * 4096 + mtid * 16);
                const float a0 = bf_lo(av[j]), a1 = bf_hi(av[j]);
                const uint32_t ww[4] = {w.x, w.y, w.z, w.w};
#pragma unroll
                for (int q = 0; q < 4; q++) {
                    const float wl = bf_lo(ww[q]), wh = bf_hi(ww[q]);
                    acc[2 * q] = fmaf(a0, wl, acc[2 * q]); acc[2 * q + 1] = fmaf(a0, wh, acc[2 * q + 1]);
                    acc[8 + 2 * q] = fmaf(a1, wl, acc[8 + 2 * q]); acc[8 + 2 * q + 1] = fmaf(a1, wh, acc[8 + 2 * q + 1]);
                }
            }
            KF_STEP(16, 8) KF_STEP(8, 4) KF_STEP(4, 2) KF_STEP(2, 1)
            acc[0] += __shfl_xor_sync(0xffffffffu, acc[0], 1);
            if ((lane & 1) == 0) {
                const int v = ((lane & 16) ? 8 : 0) + ((lane & 8) ? 4 : 0) + ((lane & 4) ? 2 : 0) + ((lane & 2) ? 1 : 0);
                s_red[mwarp * 16 + v] = acc[0];
            }
            named_sync(2, 256);
            if (mtid < 16) {
                const int u = mtid >> 3;
                float y = 0.f;
#pragma unroll
                for (int w = 0; w < 8; w++) y += s_red[w * 16 + mtid];
                const float sig = rbf(1.f / (1.f + __expf(-(u ? rv[1] : rv[0]))));
                const float xn = rbf(rbf(hfin - (u ? mean[1] : mean[0])) * (u ? inv[1] : inv[0]));
                const float ov = hfin + rbf(xn + rbf(rbf(y) * sig));
                out[(size_t)(u ? idx[1] : idx[0]) * DM + c0 + (mtid & 7)] = __float2bfloat16_rn(ov);
            }
            if (blockIdx.x == gridDim.x - 1 && mtid == 0) g_epoch = g_epoch + 1u;
            if (mtid == 0) TSTAMP0(3, 4);
        }
    }
}

typedef CUresult (*PFN_encodeTiled)(CUtensorMap*, CUtensorMapDataType, cuuint32_t, void*, const cuuint64_t*, const cuuint64_t*,
                                    const cuuint32_t*, const cuuint32_t*, CUtensorMapInterleave, CUtensorMapSwizzle,
                                    CUtensorMapL2promotion, CUtensorMapFloatOOBfill);

void make_map(PFN_encodeTiled enc, CUtensorMap* m, const void* ptr, uint64_t cols, uint64_t rows, uint32_t bcols, uint32_t brows) {
    cuuint64_t dims[2] = {cols, rows};
    cuuint64_t strides[1] = {cols * 2};
    cuuint32_t box[2] = {bcols, brows};
    cuuint32_t es[2] = {1, 1};
    enc(m, CU_TENSOR_MAP_DATA_TYPE_BFLOAT16, 2, const_cast<void*>(ptr), dims, strides, box, es, CU_TENSOR_MAP_INTERLEAVE_NONE,
        CU_TENSOR_MAP_SWIZZLE_128B, CU_TENSOR_MAP_L2_PROMOTION_L2_256B, CU_TENSOR_MAP_FLOAT_OOB_FILL_NONE);
}

void make_map3(PFN_encodeTiled enc, CUtensorMap* m, const void* ptr, uint64_t d0, uint64_t rows, uint64_t d2, uint64_t row_stride_bytes,
               uint64_t d2_stride_bytes, uint32_t b0, uint32_t b1, uint32_t b2) {
    cuuint64_t dims[3] = {d0, rows, d2};
    cuuint64_t strides[2] = {row_stride_bytes, d2_stride_bytes};
    cuuint32_t box[3] = {b0, b1, b2};
    cuuint32_t es[3] = {1, 1, 1};
    enc(m, CU_TENSOR_MAP_DATA_TYPE_BFLOAT16, 3, const_cast<void*>(ptr), dims, strides, box, es, CU_TENSOR_MAP_INTERLEAVE_NONE,
        CU_TENSOR_MAP_SWIZZLE_128B, CU_TENSOR_MAP_L2_PROMOTION_L2_256B, CU_TENSOR_MAP_FLOAT_OOB_FILL_NONE);
}

void make_map_plain(PFN_encodeTiled enc, CUtensorMap* m, const void* ptr, uint64_t cols, uint64_t rows, uint32_t bcols, uint32_t brows) {
    cuuint64_t dims[2] = {cols, rows};
    cuuint64_t strides[1] = {cols * 2};
    cuuint32_t box[2] = {bcols, brows};
    cuuint32_t es[2] = {1, 1};
    enc(m, CU_TENSOR_MAP_DATA_TYPE_BFLOAT16, 2, const_cast<void*>(ptr), dims, strides, box, es, CU_TENSOR_MAP_INTERLEAVE_NONE,
        CU_TENSOR_MAP_SWIZZLE_NONE, CU_TENSOR_MAP_L2_PROMOTION_NONE, CU_TENSOR_MAP_FLOAT_OOB_FILL_NONE);
}

template <typename... KArgs, typename... Args>
void launch(void (*kern)(KArgs...), int grid, int block, int smem, bool pdl, Args... args) {
    cudaLaunchConfig_t cfg = {};
    cfg.gridDim = dim3(grid);
    cfg.blockDim = dim3(block);
    cfg.dynamicSmemBytes = smem;
    cfg.stream = cudaStreamPerThread;
    cudaLaunchAttribute at[1];
    at[0].id = cudaLaunchAttributeProgrammaticStreamSerialization;
    at[0].val.programmaticStreamSerializationAllowed = 1;
    cfg.attrs = at;
    cfg.numAttrs = pdl ? 1 : 0;
    cudaLaunchKernelEx(&cfg, kern, KArgs(args)...);
}

}

extern "C" void kernel_launch(void* const* d_in, const int* in_sizes, int n_in, void* d_out, int out_size) {
    const __nv_bfloat16* x = (const __nv_bfloat16*)d_in[0];
    const __nv_bfloat16* wqkv = (const __nv_bfloat16*)d_in[1];
    const __nv_bfloat16* wo = (const __nv_bfloat16*)d_in[2];
    const __nv_bfloat16* w_r = (const __nv_bfloat16*)d_in[4];
    const __nv_bfloat16* w_gate = (const __nv_bfloat16*)d_in[5];
    const __nv_bfloat16* w_up = (const __nv_bfloat16*)d_in[6];
    const __nv_bfloat16* w_down = (const __nv_bfloat16*)d_in[7];
    __nv_bfloat16* out = (__nv_bfloat16*)d_out;

    static PFN_encodeTiled enc = nullptr;
    static void* g_o_ptr = nullptr;
    if (!enc) {
        cudaDriverEntryPointQueryResult qres;
        void* fn = nullptr;
        cudaGetDriverEntryPoint("cuTensorMapEncodeTiled", &fn, cudaEnableDefault, &qres);
        enc = (PFN_encodeTiled)fn;
        cudaGetSymbolAddress(&g_o_ptr, g_o);
        cudaFuncSetAttribute(k1_qkv, cudaFuncAttributeMaxDynamicSharedMemorySize, K1_SMEM);
        cudaFuncSetAttribute(kf_main, cudaFuncAttributeMaxDynamicSharedMemorySize, KF_SMEM);
    }
    CUtensorMap tm_x, tm_w, tm_o, tm_wo, tm_g, tm_u, tm_d;
    make_map_plain(enc, &tm_d, w_down, DM, FF, 8, 256);
    make_map_plain(enc, &tm_g, w_gate, FF, DM, 16, 128);
    make_map_plain(enc, &tm_u, w_up, FF, DM, 16, 128);
    make_map(enc, &tm_x, x, DM, SEQ, 64, 128);
    make_map3(enc, &tm_w, wqkv, DM, DM, 3, 3 * DM * 2, DM * 2, 64, 64, 3);
    make_map3(enc, &tm_o, g_o_ptr, 64, SEQ, 8, DM * 2, 128, 64, 64, 2);
    make_map3(enc, &tm_wo, wo, 64, DM, 8, DM * 2, 128, 64, 64, 2);

    const bool pdl = true;
    launch(k1_qkv, 128, 544, K1_SMEM, false, tm_x, tm_w, x);
    launch(kf_main, 128, 512, KF_SMEM, pdl, tm_o, tm_wo, tm_g, tm_u, tm_d, x, wo, w_r, w_gate, w_up, w_down, out);
}
```

```cpp
#include <cuda_runtime.h>
#include <cuda_bf16.h>
#include <cuda.h>
#include <stdint.h>

namespace {

constexpr int SEQ = 2048, DM = 512, NH = 32, FF = 1792;

__device__ __align__(1024) uint8_t g_q[NH * 2 * SEQ * 16];
__device__ __align__(1024) uint8_t g_kv[NH * 8 * 16384];
__device__ float g_norm[16 * NH * 3];
__device__ __align__(1024) __nv_bfloat16 g_o[SEQ * DM];
__device__ __align__(1024) __nv_bfloat16 g_h[SEQ * DM];
__device__ __align__(16) uint4 g_cand[64];
__device__ unsigned int g_oflag[32 * 32];
__device__ unsigned int g_hflag[32];
__device__ unsigned int g_sflag[32];
__device__ unsigned int g_act[FF];
__device__ unsigned int g_epoch;
__device__ __align__(16) float4 g_ln1[SEQ];
__device__ __align__(16) float4 g_part[32 * 8 * 64];

#define TSTAMP(K, I)
#define TSTAMP0(K, I)
__device__ __forceinline__ uint32_t smem_u32(const void* p) { return (uint32_t)__cvta_generic_to_shared(p); }
__device__ __forceinline__ void wg_fence() { asm volatile("wgmma.fence.sync.aligned;" ::: "memory"); }
__device__ __forceinline__ void wg_commit() { asm volatile("wgmma.commit_group.sync.aligned;" ::: "memory"); }
template <int N> __device__ __forceinline__ void wg_wait() { asm volatile("wgmma.wait_group.sync.aligned %0;" ::"n"(N) : "memory"); }
template <int N> __device__ __forceinline__ void fence_regs(float (&r)[N]) {
#pragma unroll
    for (int i = 0; i < N; i++) asm volatile("" : "+f"(r[i])::"memory");
}
__device__ __forceinline__ uint64_t make_desc(uint32_t addr, uint32_t lbo, uint32_t sbo, uint32_t swz) {
    uint64_t d = 0;
    d |= (uint64_t)((addr & 0x3FFFF) >> 4);
    d |= (uint64_t)((lbo & 0x3FFFF) >> 4) << 16;
    d |= (uint64_t)((sbo & 0x3FFFF) >> 4) << 32;
    d |= (uint64_t)swz << 62;
    return d;
}
__device__ __forceinline__ void mbar_init(uint32_t bar, uint32_t cnt) {
    asm volatile("mbarrier.init.shared::cta.b64 [%0], %1;" ::"r"(bar), "r"(cnt) : "memory");
}
__device__ __forceinline__ void mbar_expect_tx(uint32_t bar, uint32_t bytes) {
    asm volatile("mbarrier.arrive.expect_tx.shared::cta.b64 _, [%0], %1;" ::"r"(bar), "r"(bytes) : "memory");
}
__device__ __forceinline__ void mbar_arrive(uint32_t bar) {
    asm volatile("mbarrier.arrive.shared::cta.b64 _, [%0];" ::"r"(bar) : "memory");
}
__device__ __forceinline__ void mbar_wait(uint32_t bar, uint32_t parity) {
    asm volatile(
        "{\n.reg .pred p;\nWAIT_%=:\n"
        "mbarrier.try_wait.parity.shared::cta.b64 p, [%0], %1;\n"
        "@p bra DONE_%=;\nbra WAIT_%=;\nDONE_%=:\n}\n" ::"r"(bar), "r"(parity) : "memory");
}
__device__ __forceinline__ void bulk_g2s(uint32_t dst, const void* src, uint32_t bytes, uint32_t bar) {
    asm volatile("cp.async.bulk.shared::cluster.global.mbarrier::complete_tx::bytes [%0], [%1], %2, [%3];" ::"r"(dst),
                 "l"(src), "r"(bytes), "r"(bar) : "memory");
}
__device__ __forceinline__ void bulk_s2g(void* dst, uint32_t src, uint32_t bytes) {
    asm volatile("cp.async.bulk.global.shared::cta.bulk_group [%0], [%1], %2;" ::"l"(dst), "r"(src), "r"(bytes) : "memory");
}
__device__ __forceinline__ void tma_load_2d(uint32_t dst, const CUtensorMap* tm, int c0, int c1, uint32_t bar) {
    asm volatile("cp.async.bulk.tensor.2d.shared::cluster.global.mbarrier::complete_tx::bytes [%0], [%1, {%3, %4}], [%2];" ::"r"(dst),
                 "l"(tm), "r"(bar), "r"(c0), "r"(c1) : "memory");
}
__device__ __forceinline__ void tma_load_3d(uint32_t dst, const CUtensorMap* tm, int c0, int c1, int c2, uint32_t bar) {
    asm volatile("cp.async.bulk.tensor.3d.shared::cluster.global.mbarrier::complete_tx::bytes [%0], [%1, {%3, %4, %5}], [%2];" ::"r"(dst),
                 "l"(tm), "r"(bar), "r"(c0), "r"(c1), "r"(c2) : "memory");
}
__device__ __forceinline__ void tma_load_2d_mc(uint32_t dst, const CUtensorMap* tm, int c0, int c1, uint32_t bar, uint16_t mask) {
    asm volatile("cp.async.bulk.tensor.2d.shared::cluster.global.mbarrier::complete_tx::bytes.multicast::cluster [%0], [%1, {%3, %4}], [%2], %5;" ::"r"(dst),
                 "l"(tm), "r"(bar), "r"(c0), "r"(c1), "h"(mask) : "memory");
}
__device__ __forceinline__ void mbar_arrive_cluster(uint32_t bar, uint32_t cta) {
    asm volatile("{\n.reg .b32 ra;\nmapa.shared::cluster.u32 ra, %0, %1;\nmbarrier.arrive.release.cluster.shared::cluster.b64 _, [ra];\n}" ::"r"(bar), "r"(cta) : "memory");
}
__device__ __forceinline__ void cluster_sync() {
    asm volatile("barrier.cluster.arrive.release.aligned;\nbarrier.cluster.wait.acquire.aligned;" ::: "memory");
}
__device__ __forceinline__ void prefetch_l2(const void* p, uint32_t bytes) {
    asm volatile("cp.async.bulk.prefetch.L2.global [%0], %1;" ::"l"(p), "r"(bytes) : "memory");
}
__device__ __forceinline__ void fence_proxy_async() { asm volatile("fence.proxy.async.shared::cta;" ::: "memory"); }
__device__ __forceinline__ void fence_barrier_init() { asm volatile("fence.mbarrier_init.release.cluster;" ::: "memory"); }
__device__ __forceinline__ void pdl_launch() { asm volatile("griddepcontrol.launch_dependents;" ::: "memory"); }
__device__ __forceinline__ void pdl_wait() { asm volatile("griddepcontrol.wait;" ::: "memory"); }
__device__ __forceinline__ void named_sync(int id, int n) { asm volatile("bar.sync %0, %1;" ::"r"(id), "r"(n) : "memory"); }
__device__ __forceinline__ void named_arrive(int id, int n) { asm volatile("bar.arrive %0, %1;" ::"r"(id), "r"(n) : "memory"); }

__device__ __forceinline__ float ex2f(float x) { float y; asm("ex2.approx.ftz.f32 %0, %1;" : "=f"(y) : "f"(x)); return y; }
__device__ __forceinline__ uint32_t pack_bf16(float lo, float hi) {
    uint32_t r; asm("cvt.rn.bf16x2.f32 %0, %1, %2;" : "=r"(r) : "f"(hi), "f"(lo)); return r;
}
__device__ __forceinline__ float bf_lo(uint32_t v) { return __uint_as_float(v << 16); }
__device__ __forceinline__ float bf_hi(uint32_t v) { return __uint_as_float(v & 0xFFFF0000u); }
__device__ __forceinline__ float rbf(float x) { return __bfloat162float(__float2bfloat16_rn(x)); }
__device__ __forceinline__ uint32_t fma_bf16x2(uint32_t a, uint32_t b, uint32_t c) {
    uint32_t r; asm("fma.rn.bf16x2 %0, %1, %2, %3;" : "=r"(r) : "r"(a), "r"(b), "r"(c)); return r;
}
__device__ __forceinline__ void stmatrix_x4(uint32_t addr, uint32_t r0, uint32_t r1, uint32_t r2, uint32_t r3) {
    asm volatile("stmatrix.sync.aligned.m8n8.x4.shared.b16 [%0], {%1, %2, %3, %4};" ::"r"(addr), "r"(r0), "r"(r1), "r"(r2), "r"(r3) : "memory");
}
__device__ __forceinline__ void stmatrix_x4_trans(uint32_t addr, uint32_t r0, uint32_t r1, uint32_t r2, uint32_t r3) {
    asm volatile("stmatrix.sync.aligned.m8n8.x4.trans.shared.b16 [%0], {%1, %2, %3, %4};" ::"r"(addr), "r"(r0), "r"(r1), "r"(r2), "r"(r3) : "memory");
}

__device__ __forceinline__ void wgmma_k1_n136(float (&d)[68], uint64_t desca, uint64_t descb, int scale_d) {
  asm volatile("{\n.reg .pred p;\nsetp.ne.b32 p, %70, 0;\n"
    "wgmma.mma_async.sync.aligned.m64n136k16.f32.bf16.bf16 "
    "{%0, %1, %2, %3, %4, %5, %6, %7, %8, %9, %10, %11, %12, %13, %14, %15, %16, %17, %18, %19, %20, %21, %22, %23, %24, %25, %26, %27, %28, %29, %30, %31, %32, %33, %34, %35, %36, %37, %38, %39, %40, %41, %42, %43, %44, %45, %46, %47, %48, %49, %50, %51, %52, %53, %54, %55, %56, %57, %58, %59, %60, %61, %62, %63, %64, %65, %66, %67}, "
    "%68, %69, p, 1, 1, 1, 0;\n}\n"
    : "+f"(d[0]), "+f"(d[1]), "+f"(d[2]), "+f"(d[3]), "+f"(d[4]), "+f"(d[5]), "+f"(d[6]), "+f"(d[7]), "+f"(d[8]), "+f"(d[9]), "+f"(d[10]), "+f"(d[11]), "+f"(d[12]), "+f"(d[13]), "+f"(d[14]), "+f"(d[15]), "+f"(d[16]), "+f"(d[17]), "+f"(d[18]), "+f"(d[19]), "+f"(d[20]), "+f"(d[21]), "+f"(d[22]), "+f"(d[23]), "+f"(d[24]), "+f"(d[25]), "+f"(d[26]), "+f"(d[27]), "+f"(d[28]), "+f"(d[29]), "+f"(d[30]), "+f"(d[31]), "+f"(d[32]), "+f"(d[33]), "+f"(d[34]), "+f"(d[35]), "+f"(d[36]), "+f"(d[37]), "+f"(d[38]), "+f"(d[39]), "+f"(d[40]), "+f"(d[41]), "+f"(d[42]), "+f"(d[43]), "+f"(d[44]), "+f"(d[45]), "+f"(d[46]), "+f"(d[47]), "+f"(d[48]), "+f"(d[49]), "+f"(d[50]), "+f"(d[51]), "+f"(d[52]), "+f"(d[53]), "+f"(d[54]), "+f"(d[55]), "+f"(d[56]), "+f"(d[57]), "+f"(d[58]), "+f"(d[59]), "+f"(d[60]), "+f"(d[61]), "+f"(d[62]), "+f"(d[63]), "+f"(d[64]), "+f"(d[65]), "+f"(d[66]), "+f"(d[67])
    : "l"(desca), "l"(descb), "r"(scale_d));
}
__device__ __forceinline__ void wgmma_qk_n64(float (&d)[32], uint32_t a0, uint32_t a1, uint32_t a2, uint32_t a3, uint64_t descb) {
  asm volatile("{\n.reg .pred p;\nsetp.ne.b32 p, 0, 0;\n"
    "wgmma.mma_async.sync.aligned.m64n64k16.f32.bf16.bf16 "
    "{%0, %1, %2, %3, %4, %5, %6, %7, %8, %9, %10, %11, %12, %13, %14, %15, %16, %17, %18, %19, %20, %21, %22, %23, %24, %25, %26, %27, %28, %29, %30, %31}, "
    "{%32, %33, %34, %35}, %36, p, 1, 1, 0;\n}\n"
    : "=f"(d[0]), "=f"(d[1]), "=f"(d[2]), "=f"(d[3]), "=f"(d[4]), "=f"(d[5]), "=f"(d[6]), "=f"(d[7]), "=f"(d[8]), "=f"(d[9]), "=f"(d[10]), "=f"(d[11]), "=f"(d[12]), "=f"(d[13]), "=f"(d[14]), "=f"(d[15]), "=f"(d[16]), "=f"(d[17]), "=f"(d[18]), "=f"(d[19]), "=f"(d[20]), "=f"(d[21]), "=f"(d[22]), "=f"(d[23]), "=f"(d[24]), "=f"(d[25]), "=f"(d[26]), "=f"(d[27]), "=f"(d[28]), "=f"(d[29]), "=f"(d[30]), "=f"(d[31])
    : "r"(a0), "r"(a1), "r"(a2), "r"(a3), "l"(descb));
}
__device__ __forceinline__ void wgmma_pv_n24(float (&d)[12], uint32_t a0, uint32_t a1, uint32_t a2, uint32_t a3, uint64_t descb) {
  asm volatile("{\n.reg .pred p;\nsetp.eq.b32 p, 0, 0;\n"
    "wgmma.mma_async.sync.aligned.m64n24k16.f32.bf16.bf16 "
    "{%0, %1, %2, %3, %4, %5, %6, %7, %8, %9, %10, %11}, "
    "{%12, %13, %14, %15}, %16, p, 1, 1, 1;\n}\n"
    : "+f"(d[0]), "+f"(d[1]), "+f"(d[2]), "+f"(d[3]), "+f"(d[4]), "+f"(d[5]), "+f"(d[6]), "+f"(d[7]), "+f"(d[8]), "+f"(d[9]), "+f"(d[10]), "+f"(d[11])
    : "r"(a0), "r"(a1), "r"(a2), "r"(a3), "l"(descb));
}
__device__ __forceinline__ void wgmma_k3_n64(float (&d)[32], uint64_t desca, uint64_t descb, int scale_d) {
  asm volatile("{\n.reg .pred p;\nsetp.ne.b32 p, %34, 0;\n"
    "wgmma.mma_async.sync.aligned.m64n64k16.f32.bf16.bf16 "
    "{%0, %1, %2, %3, %4, %5, %6, %7, %8, %9, %10, %11, %12, %13, %14, %15, %16, %17, %18, %19, %20, %21, %22, %23, %24, %25, %26, %27, %28, %29, %30, %31}, "
    "%32, %33, p, 1, 1, 0, 1;\n}\n"
    : "+f"(d[0]), "+f"(d[1]), "+f"(d[2]), "+f"(d[3]), "+f"(d[4]), "+f"(d[5]), "+f"(d[6]), "+f"(d[7]), "+f"(d[8]), "+f"(d[9]), "+f"(d[10]), "+f"(d[11]), "+f"(d[12]), "+f"(d[13]), "+f"(d[14]), "+f"(d[15]), "+f"(d[16]), "+f"(d[17]), "+f"(d[18]), "+f"(d[19]), "+f"(d[20]), "+f"(d[21]), "+f"(d[22]), "+f"(d[23]), "+f"(d[24]), "+f"(d[25]), "+f"(d[26]), "+f"(d[27]), "+f"(d[28]), "+f"(d[29]), "+f"(d[30]), "+f"(d[31])
    : "l"(desca), "l"(descb), "r"(scale_d));
}

constexpr int K1_XS = 17408;
constexpr int K1_WS = 24576;
constexpr int K1_ST = K1_XS + K1_WS;
constexpr int K1_NST = 5;
constexpr int K1_OFF_MISC = K1_NST * K1_ST;
constexpr int K1_SMEM = K1_OFF_MISC + 2048 + 1024;
constexpr float QSCALE = 0.25f * 1.4426950408889634f;

__global__ void __launch_bounds__(544, 1)
k1_qkv(const __grid_constant__ CUtensorMap tm_x, const __grid_constant__ CUtensorMap tm_w, const __nv_bfloat16* __restrict__ x) {
    extern __shared__ uint8_t smem_raw[];
    const uint32_t sraw = smem_u32(smem_raw);
    const uint32_t sb = (sraw + 1023) & ~1023u;
    uint8_t* sp = smem_raw + (sb - sraw);
    const uint32_t full = sb + K1_OFF_MISC;
    const uint32_t empty = full + 64;
    float* s_m = (float*)(sp + K1_OFF_MISC + 256);
    float* s_r = s_m + 128;

    const int tid = threadIdx.x, warp = tid >> 5, lane = tid & 31;
    const int mt = blockIdx.x >> 3, nt = blockIdx.x & 7;
    if (tid == 0) TSTAMP0(0, 0);
    pdl_launch();
    if (tid == 512) {
        for (int i = 0; i < K1_NST; i++) { mbar_init(full + 8 * i, 1); mbar_init(empty + 8 * i, 3); }
        fence_barrier_init();
        for (int kb = 0; kb < K1_NST; kb++) {
            mbar_expect_tx(full + 8 * kb, 16384 + K1_WS);
            tma_load_2d(sb + kb * K1_ST, &tm_x, kb * 64, mt * 128, full + 8 * kb);
            tma_load_3d(sb + kb * K1_ST + K1_XS, &tm_w, nt * 64, kb * 64, 0, full + 8 * kb);
        }
    }
    if (tid < K1_NST * 64) {
        *(uint4*)(sp + (tid >> 6) * K1_ST + 16384 + (tid & 63) * 16) =
            make_uint4(0x3F803F80u, 0x3F803F80u, 0x3F803F80u, 0x3F803F80u);
    }
    fence_proxy_async();
    __syncthreads();

    if (warp == 16) {
        if (lane == 0) {
            for (int kb = K1_NST; kb < 8; kb++) {
                const int s = kb % K1_NST;
                mbar_wait(empty + 8 * s, 0);
                mbar_expect_tx(full + 8 * s, 16384 + K1_WS);
                tma_load_2d(sb + s * K1_ST, &tm_x, kb * 64, mt * 128, full + 8 * s);
                tma_load_3d(sb + s * K1_ST + K1_XS, &tm_w, nt * 64, kb * 64, 0, full + 8 * s);
            }
        }
        __syncwarp();
        if (lane < FF / 128) g_act[blockIdx.x * (FF / 128) + lane] = 0xFFFFFFFFu;
        for (int i = lane; i < 128; i += 32) g_part[blockIdx.x * 128 + i] = make_float4(0.f, 0.f, 0.f, 0.f);
        if (blockIdx.x == 1) { g_cand[lane] = make_uint4(0, 0, 0, 0); g_cand[lane + 32] = make_uint4(0, 0, 0, 0); g_hflag[lane] = 0; g_sflag[lane] = 0; }
        if (blockIdx.x == 2) for (int i = lane; i < 1024; i += 32) g_oflag[i] = 0;
    } else if (warp >= 12) {
        const int r = tid - 384;
        const unsigned int tag = *(volatile unsigned int*)&g_epoch + 1u;
        {
            const int row = mt * 128 + nt * 16 + (r >> 3);
            const uint4* xp = (const uint4*)(x + (size_t)row * DM) + (r & 7);
            uint4 v[8];
#pragma unroll
            for (int i = 0; i < 8; i++) v[i] = __ldg(xp + i * 8);
            float s1 = 0.f;
#pragma unroll
            for (int i = 0; i < 8; i++)
                s1 += ((bf_lo(v[i].x) + bf_hi(v[i].x)) + (bf_lo(v[i].y) + bf_hi(v[i].y))) + ((bf_lo(v[i].z) + bf_hi(v[i].z)) + (bf_lo(v[i].w) + bf_hi(v[i].w)));
#pragma unroll
            for (int o = 1; o < 8; o <<= 1) s1 += __shfl_xor_sync(0xffffffffu, s1, o);
            const float mean = s1 * (1.f / DM);
            float q0 = 0.f, q1 = 0.f;
#pragma unroll
            for (int i = 0; i < 8; i++) {
                const uint32_t w[4] = {v[i].x, v[i].y, v[i].z, v[i].w};
#pragma unroll
                for (int j = 0; j < 4; j++) {
                    const float a = bf_lo(w[j]) - mean, b = bf_hi(w[j]) - mean;
                    q0 = fmaf(a, a, q0); q1 = fmaf(b, b, q1);
                }
            }
            float q = q0 + q1;
#pragma unroll
            for (int o = 1; o < 8; o <<= 1) q += __shfl_xor_sync(0xffffffffu, q, o);
            const float den = rbf(sqrtf(rbf(rbf(q * (1.f / DM)) + 1e-5f)));
            if ((r & 7) == 0)
                asm volatile("st.relaxed.gpu.global.v4.f32 [%0], {%1, %2, %3, %4};" ::"l"(g_ln1 + row), "f"(rbf(mean)), "f"(1.f / den),
                             "f"(__uint_as_float(tag)), "f"(0.f) : "memory");
        }
        if (r == 0) TSTAMP0(0, 6);
        {
            float4 v;
            int spins = 0;
            do {
                asm volatile("ld.relaxed.gpu.global.v4.f32 {%0, %1, %2, %3}, [%4];" : "=f"(v.x), "=f"(v.y), "=f"(v.z), "=f"(v.w) : "l"(g_ln1 + mt * 128 + r) : "memory");
            } while (__float_as_uint(v.z) != tag && ++spins < (1 << 22));
            s_m[r] = v.x;
            s_r[r] = v.y;
        }
        if (r == 0) TSTAMP0(0, 7);
        named_arrive(1, 512);
    } else {
        const int part = warp >> 2, hw = warp & 3;
        float acc[68];
#pragma unroll
        for (int i = 0; i < 68; i++) acc[i] = 0.f;
        fence_regs(acc);
#pragma unroll 1
        for (int kb = 0; kb < 8; kb++) {
            const int s = kb % K1_NST;
            mbar_wait(full + 8 * s, (kb / K1_NST) & 1);
            const uint64_t da = make_desc(sb + s * K1_ST + K1_XS + part * 8192, 1024, 1024, 1);
            const uint64_t db = make_desc(sb + s * K1_ST, 16, 1024, 1);
            wg_fence();
#pragma unroll
            for (int k = 0; k < 4; k++) wgmma_k1_n136(acc, da + k * 128, db + k * 2, (kb | k) != 0);
            wg_commit();
            if (kb > 0 && kb <= 8 - K1_NST) {
                wg_wait<1>();
                if ((tid & 127) == 0) mbar_arrive(empty + 8 * (kb - 1));
            }
        }
        wg_wait<0>();
        fence_regs(acc);
        if (tid == 0) TSTAMP0(0, 1);
        named_sync(1, 512);
        if (tid == 0) TSTAMP0(0, 2);

        const int t = lane & 3;
        const float cs0 = acc[64], cs1 = acc[66];
        const float sc = (part == 0) ? QSCALE : 1.f;
        const uint32_t stg = sb + (hw >> 1) * K1_ST + K1_XS + part * 8192 + (hw & 1) * 4096;
        const uint32_t st_addr = stg + ((lane >> 3) & 1) * 2048 + ((lane >> 4) * 8 + (lane & 7)) * 16;
#pragma unroll
        for (int j = 0; j < 16; j += 2) {
            uint32_t rr[4];
#pragma unroll
            for (int u = 0; u < 2; u++) {
                const int jj = j + u;
                const float2 m2 = *(const float2*)(s_m + 8 * jj + 2 * t);
                const float2 r2 = *(const float2*)(s_r + 8 * jj + 2 * t);
                const float ra = r2.x * sc, rb = r2.y * sc;
                rr[2 * u] = pack_bf16((acc[4 * jj] - m2.x * cs0) * ra, (acc[4 * jj + 1] - m2.y * cs0) * rb);
                rr[2 * u + 1] = pack_bf16((acc[4 * jj + 2] - m2.x * cs1) * ra, (acc[4 * jj + 3] - m2.y * cs1) * rb);
            }
            stmatrix_x4_trans(st_addr + j * 128, rr[0], rr[1], rr[2], rr[3]);
        }
        fence_proxy_async();
        __syncwarp();
        if (tid == 0) TSTAMP0(0, 4);
        const int head = nt * 4 + hw;
        if (lane == 0) {
            uint8_t* dst;
            uint32_t hstride;
            if (part == 0) { dst = g_q + (size_t)head * 65536 + mt * 2048; hstride = 32768; }
            else { dst = g_kv + (size_t)head * 131072 + (mt >> 1) * 16384 + (part - 1) * 8192 + (mt & 1) * 2048; hstride = 4096; }
            bulk_s2g(dst, stg, 2048);
            bulk_s2g(dst + hstride, stg + 2048, 2048);
            asm volatile("cp.async.bulk.commit_group;" ::: "memory");
        }
        float nmax = 0.f;
#pragma unroll
        for (int i = 0; i < 4; i++) {
            const int tok = lane + 32 * i;
            const uint4 a = *(const uint4*)(sp + (stg - sb) + tok * 16);
            const uint4 b = *(const uint4*)(sp + (stg - sb) + 2048 + tok * 16);
            const uint32_t w[8] = {a.x, a.y, a.z, a.w, b.x, b.y, b.z, b.w};
            float n2 = 0.f, n3 = 0.f;
#pragma unroll
            for (int q = 0; q < 8; q++) {
                const float lo = bf_lo(w[q]), hi = bf_hi(w[q]);
                n2 = fmaf(lo, lo, n2); n3 = fmaf(hi, hi, n3);
            }
            n2 += n3;
            nmax = (n2 > nmax || n2 != n2) ? n2 : nmax;
        }
#pragma unroll
        for (int o = 16; o > 0; o >>= 1) {
            const float v = __shfl_xor_sync(0xffffffffu, nmax, o);
            nmax = (v > nmax || v != v) ? v : nmax;
        }
        if (tid == 0) TSTAMP0(0, 5);
        if (lane == 0) {
            g_norm[(head * 16 + mt) * 3 + part] = nmax;
            asm volatile("cp.async.bulk.wait_group.read 0;" ::: "memory");
            if (tid == 0) TSTAMP0(0, 3);
        }
    }
}

constexpr int KF_CH_G = 16384, KF_CH_S = 20480, KF_NCH = 8;
constexpr int KF_OFF_WO = KF_NCH * KF_CH_S;
constexpr int KF_OFF_MISC = KF_OFF_WO + 65536;
constexpr int KF_SMEM = KF_OFF_MISC + 1280 + 1024;

__device__ __forceinline__ uint32_t exp2_pair_poly(float s0, float s1) {
    const float KB = 65536.0f + 127.0f;
    const float t0 = s0 + KB, t1 = s1 + KB;
    const uint32_t w = __byte_perm(__float_as_uint(t0), __float_as_uint(t1), 0x5410);
    uint32_t z;
    asm("lop3.b32 %0, %1, %2, %3, 0xEA;" : "=r"(z) : "r"(w), "r"(0x007F007Fu), "r"(0x3F803F80u));
    uint32_t p = fma_bf16x2(0x3eab3eabu, z, 0xbc73bc73u);
    p = fma_bf16x2(p, z, 0x3f2f3f2fu);
    return p + w - z;
}
#define EMASK 0x5757u
constexpr uint32_t KF_EMASK = EMASK;
template <int LO, int HI>
__device__ __forceinline__ void softmax_part(const float (&s)[32], uint32_t (&p)[16]) {
#pragma unroll
    for (int i = LO; i < HI; i++) {
        if ((KF_EMASK >> i) & 1) p[i] = exp2_pair_poly(s[2 * i], s[2 * i + 1]);
        else p[i] = pack_bf16(ex2f(s[2 * i]), ex2f(s[2 * i + 1]));
    }
}
#define KF_PV(P, OFF)                                                                              \
    _Pragma("unroll") for (int kk = 0; kk < 4; kk++)                                               \
        wgmma_pv_n24(o, P[4 * kk], P[4 * kk + 1], P[4 * kk + 2], P[4 * kk + 3], dv + ((OFF) + kk * 16));

__device__ __forceinline__ uint32_t make_key(float r_bf16, int token) {
    const uint32_t u = __float_as_uint(r_bf16) >> 16;
    const uint32_t o = (u & 0x8000u) ? (~u & 0xFFFFu) : (u | 0x8000u);
    return (o << 16) | (uint32_t)(0xFFFF - token);
}
__device__ __forceinline__ float key_value(uint32_t k) {
    const uint32_t o = k >> 16;
    const uint32_t u = (o & 0x8000u) ? (o & 0x7FFFu) : (~o & 0xFFFFu);
    return __uint_as_float(u << 16);
}
__device__ __forceinline__ int key_token(uint32_t k) { return 0xFFFF - (int)(k & 0xFFFFu); }
__device__ __forceinline__ void warp_top2(uint32_t a, uint32_t b, uint32_t& k1, uint32_t& k2) {
    k1 = __reduce_max_sync(0xffffffffu, a > b ? a : b);
    const uint32_t a2 = (a == k1) ? 0u : a, b2 = (b == k1) ? 0u : b;
    k2 = __reduce_max_sync(0xffffffffu, a2 > b2 ? a2 : b2);
}
__device__ __forceinline__ unsigned int ld_acquire(const unsigned int* p) {
    unsigned int v; asm volatile("ld.acquire.gpu.global.u32 %0, [%1];" : "=r"(v) : "l"(p) : "memory"); return v;
}
__device__ __forceinline__ void red_release_add(unsigned int* p) {
    asm volatile("red.release.gpu.global.add.u32 [%0], 1;" ::"l"(p) : "memory");
}

__global__ void __launch_bounds__(512, 1)
kf_main(const __grid_constant__ CUtensorMap tm_o, const __grid_constant__ CUtensorMap tm_wo,
        const __grid_constant__ CUtensorMap tm_g, const __grid_constant__ CUtensorMap tm_u, const __grid_constant__ CUtensorMap tm_d,
        const __nv_bfloat16* __restrict__ x, const __nv_bfloat16* __restrict__ wo, const __nv_bfloat16* __restrict__ w_r,
        const __nv_bfloat16* __restrict__ w_gate, const __nv_bfloat16* __restrict__ w_up, const __nv_bfloat16* __restrict__ w_down,
        __nv_bfloat16* __restrict__ out) {
    extern __shared__ uint8_t smem_raw[];
    const uint32_t sraw = smem_u32(smem_raw);
    const uint32_t sb = (sraw + 1023) & ~1023u;
    uint8_t* sp = smem_raw + (sb - sraw);
    const uint32_t kvbar = sb + KF_OFF_MISC;
    const uint32_t wbar = kvbar + 64;
    const uint32_t obar = wbar + 64;
    const uint32_t gbar = obar + 64;
    const uint32_t dbar = gbar + 8;
    unsigned int* s_cnt = (unsigned int*)(sp + KF_OFF_MISC + 208);
    volatile unsigned int* s_order = (volatile unsigned int*)(sp + KF_OFF_MISC + 1056);
    uint32_t* s_key = (uint32_t*)(sp + KF_OFF_MISC + 256);
    float* s_gu = (float*)(sp + KF_OFF_MISC + 768);
    uint4* s_sel = (uint4*)(sp + KF_OFF_MISC + 1024);
    const int tid = threadIdx.x;
    const int head = blockIdx.x >> 2, quarter = blockIdx.x & 3;
    const int mt = blockIdx.x >> 2, nt = blockIdx.x & 3;
    if (tid == 0) TSTAMP0(1, 0);
    if (tid == 0) {
        for (int c = 0; c < 26; c++) mbar_init(kvbar + 8 * c, 1);
        for (int c = 0; c < 4; c++) s_cnt[c] = 0;
        fence_barrier_init();
        for (int kb = 0; kb < 4; kb++) {
            mbar_expect_tx(wbar + 8 * kb, 16384);
            tma_load_3d(sb + KF_OFF_WO + kb * 16384, &tm_wo, 0, kb * 64, nt * 2, wbar + 8 * kb);
        }
    }
    if (tid == 32) {
        prefetch_l2((const uint8_t*)wo + blockIdx.x * 4096, 4096);
        prefetch_l2((const uint8_t*)w_gate + blockIdx.x * 14336, 14336);
        prefetch_l2((const uint8_t*)w_up + blockIdx.x * 14336, 14336);
        prefetch_l2((const uint8_t*)w_down + blockIdx.x * 14336, 14336);
    }
    for (int i = tid; i < KF_NCH * 256; i += 512)
        *(uint4*)(sp + (i >> 8) * KF_CH_S + 16384 + (i & 255) * 16) =
            make_uint4(0x3F803F80u, 0x3F803F80u, 0x3F803F80u, 0x3F803F80u);
    fence_proxy_async();
    __syncthreads();
    pdl_wait();
    if (tid == 0) TSTAMP0(1, 1);
    const uint8_t* kvsrc = g_kv + (size_t)head * (KF_NCH * KF_CH_G);
    if (tid == 32) {
        mbar_expect_tx(kvbar, KF_CH_G);
        bulk_g2s(sb, kvsrc, KF_CH_G, kvbar);
    }
    const int wg = tid >> 7, warp = (tid >> 5) & 3, lane = tid & 31, g = lane >> 2, t = lane & 3;
    if (tid < 32) {
        const int m16 = lane & 15;
        float kn = g_norm[(head * 16 + m16) * 3 + 1];
        float vn = g_norm[(head * 16 + m16) * 3 + 2];
        float qn = g_norm[(head * 16 + quarter * 4 + (lane & 3)) * 3 + 0];
        const bool bad = !(kn < 1e30f) || !(vn < 1e30f) || !(qn < 1e30f);
#pragma unroll
        for (int o = 8; o > 0; o >>= 1) {
            kn = fmaxf(kn, __shfl_xor_sync(0xffffffffu, kn, o));
            qn = fmaxf(qn, __shfl_xor_sync(0xffffffffu, qn, o));
        }
        const bool ok = __all_sync(0xffffffffu, !bad && (qn * kn <= 3500.f));
        if (lane == 0) s_cnt[4] = ok ? 1u : 0u;
    }
    uint32_t qn2[2][4];
#pragma unroll
    for (int ps = 0; ps < 2; ps++) {
        const uint8_t* qb = g_q + (size_t)head * 65536 + (quarter * 512 + ps * 256 + wg * 64 + warp * 16 + g) * 16 + t * 4;
        qn2[ps][0] = *(const uint32_t*)(qb);
        qn2[ps][1] = *(const uint32_t*)(qb + 128);
        qn2[ps][2] = *(const uint32_t*)(qb + 32768);
        qn2[ps][3] = *(const uint32_t*)(qb + 32768 + 128);
    }

    __syncthreads();
    const bool fast = __all_sync(0xffffffffu, s_cnt[4] != 0u);
    if (tid == 32) {
        for (int c = 1; c < KF_NCH; c++) {
            mbar_expect_tx(kvbar + 8 * c, KF_CH_G);
            bulk_g2s(sb + c * KF_CH_S, kvsrc + c * KF_CH_G, KF_CH_G, kvbar + 8 * c);
        }
    }
    if (tid == 0) TSTAMP0(1, 8);
    const uint64_t dk0 = make_desc(sb, 4096, 128, 0);
    const uint64_t dv0 = make_desc(sb + 8192, 128, 4096, 0);

#pragma unroll 1
    for (int pass = 0; pass < 2; pass++) {
        const int row0 = quarter * 512 + pass * 256 + wg * 64 + warp * 16 + g;
        uint32_t qa[4];
#pragma unroll
        for (int i = 0; i < 4; i++) qa[i] = pass ? qn2[1][i] : qn2[0][i];
        float o[12];
#pragma unroll
        for (int i = 0; i < 12; i++) o[i] = 0.f;
        fence_regs(o);
#define KF_RELEASE_CHUNK(c)                                                                          \
        if (pass == 1 && (c) >= 1 && (c) <= 4) {                                                     \
            named_sync(4 + wg, 128);            \
            if ((tid & 127) == 0 && atomicAdd(&s_cnt[(c) - 1], 1u) == 3u) {                          \
                mbar_expect_tx(wbar + 8 * (3 + (c)), 16384);                                         \
                tma_load_3d(sb + ((c) - 1) * KF_CH_S, &tm_wo, 0, (3 + (c)) * 64, nt * 2, wbar + 8 * (3 + (c))); \
            }                                                                                        \
        }
        if (fast) {
#pragma unroll 1
            for (int c = 0; c < KF_NCH; c++) {
                const uint64_t dk = dk0 + (uint64_t)(c * (KF_CH_S >> 4));
                const uint64_t dv = dv0 + (uint64_t)(c * (KF_CH_S >> 4));
                float s0[32], s1[32], s2[32], s3[32];
                uint32_t p0[16], p1[16], p2[16], p3[16];
                mbar_wait(kvbar + 8 * c, 0);
                wg_wait<1>();
                wg_fence();
                wgmma_qk_n64(s0, qa[0], qa[1], qa[2], qa[3], dk);
                wg_commit();
                wg_wait<1>();
                KF_RELEASE_CHUNK(c);
                wg_fence();
                wgmma_qk_n64(s1, qa[0], qa[1], qa[2], qa[3], dk + 64);
                wg_commit();
                wg_wait<1>();
                fence_regs(s0);
                softmax_part<0, 16>(s0, p0);
                wg_fence();
                KF_PV(p0, 0);
                wg_commit();
                wg_wait<1>();
                fence_regs(s1);
                softmax_part<0, 8>(s1, p1);
                wg_wait<0>();
                wg_fence();
                wgmma_qk_n64(s2, qa[0], qa[1], qa[2], qa[3], dk + 128);
                wg_commit();
                softmax_part<8, 16>(s1, p1);
                wg_fence();
                KF_PV(p1, 64);
                wg_commit();
                wg_wait<1>();
                fence_regs(s2);
                softmax_part<0, 8>(s2, p2);
                wg_wait<0>();
                wg_fence();
                wgmma_qk_n64(s3, qa[0], qa[1], qa[2], qa[3], dk + 192);
                wg_commit();
                softmax_part<8, 16>(s2, p2);
                wg_fence();
                KF_PV(p2, 128);
                wg_commit();
                wg_wait<1>();
                fence_regs(s3);
                softmax_part<0, 16>(s3, p3);
                wg_fence();
                KF_PV(p3, 192);
                wg_commit();
            }
            wg_wait<0>();
            fence_regs(o);
        } else {
            float m0 = -INFINITY, m1 = -INFINITY;
#pragma unroll 1
            for (int b = 0; b < 32; b++) {
                const int c = b >> 2;
                const uint64_t dk = dk0 + (uint64_t)(c * (KF_CH_S >> 4) + (b & 3) * 64);
                const uint64_t dv = dv0 + (uint64_t)(c * (KF_CH_S >> 4) + (b & 3) * 64);
                float s[32];
                uint32_t p[16];
                mbar_wait(kvbar + 8 * c, 0);
                wg_fence();
                wgmma_qk_n64(s, qa[0], qa[1], qa[2], qa[3], dk);
                wg_commit();
                if ((b & 3) == 0) { KF_RELEASE_CHUNK(c); }
                wg_wait<0>();
                fence_regs(s);
                float x0 = s[0], x1 = s[2];
#pragma unroll
                for (int j = 0; j < 8; j++) {
                    x0 = fmaxf(x0, fmaxf(s[4 * j], s[4 * j + 1]));
                    x1 = fmaxf(x1, fmaxf(s[4 * j + 2], s[4 * j + 3]));
                }
                x0 = fmaxf(x0, __shfl_xor_sync(0xffffffffu, x0, 1));
                x0 = fmaxf(x0, __shfl_xor_sync(0xffffffffu, x0, 2));
                x1 = fmaxf(x1, __shfl_xor_sync(0xffffffffu, x1, 1));
                x1 = fmaxf(x1, __shfl_xor_sync(0xffffffffu, x1, 2));
                const float n0 = fmaxf(m0, x0), n1 = fmaxf(m1, x1);
                const float c0 = ex2f(m0 - n0), c1 = ex2f(m1 - n1);
                m0 = n0; m1 = n1;
#pragma unroll
                for (int j = 0; j < 3; j++) {
                    o[4 * j] *= c0; o[4 * j + 1] *= c0; o[4 * j + 2] *= c1; o[4 * j + 3] *= c1;
                }
#pragma unroll
                for (int j = 0; j < 8; j++) {
                    p[2 * j] = pack_bf16(ex2f(s[4 * j] - n0), ex2f(s[4 * j + 1] - n0));
                    p[2 * j + 1] = pack_bf16(ex2f(s[4 * j + 2] - n1), ex2f(s[4 * j + 3] - n1));
                }
                fence_regs(o);
                wg_fence();
                KF_PV(p, 0);
                wg_commit();
                wg_wait<0>();
                fence_regs(o);
            }
        }
        const float inv0 = 1.f / o[8], inv1 = 1.f / o[10];
        {
            uint32_t v0 = pack_bf16(o[0] * inv0, o[1] * inv0), v1 = pack_bf16(o[4] * inv0, o[5] * inv0);
            uint32_t v2 = pack_bf16(o[2] * inv1, o[3] * inv1), v3 = pack_bf16(o[6] * inv1, o[7] * inv1);
            const bool o1 = t & 1, o2 = t & 2;
            uint32_t s0 = o1 ? v0 : v1, s1 = o1 ? v2 : v3;
            s0 = __shfl_xor_sync(0xffffffffu, s0, 1); s1 = __shfl_xor_sync(0xffffffffu, s1, 1);
            uint32_t a0 = o1 ? s0 : v0, a1 = o1 ? v1 : s0, b0 = o1 ? s1 : v2, b1 = o1 ? v3 : s1;
            uint32_t x0 = o2 ? a0 : b0, x1 = o2 ? a1 : b1;
            x0 = __shfl_xor_sync(0xffffffffu, x0, 2); x1 = __shfl_xor_sync(0xffffffffu, x1, 2);
            uint4 r;
            r.x = o2 ? x0 : a0; r.y = o2 ? x1 : a1; r.z = o2 ? b0 : x0; r.w = o2 ? b1 : x1;
            *(uint4*)(g_o + (size_t)(row0 + (t >> 1) * 8) * DM + head * 16 + (t & 1) * 8) = r;
        }
        if (tid == 0) TSTAMP0(1, 4 + pass);
    }
    if ((tid >> 5) != 10) named_arrive(1, 512);
    named_sync(4 + wg, 128);
    if ((tid & 127) == 0) {
        asm volatile("fence.acq_rel.gpu;" ::: "memory");
        asm volatile("red.relaxed.gpu.global.add.u32 [%0], 1;" ::"l"(&g_oflag[(quarter * 8 + 4 + wg) * 32 + (head >> 2) * 4]) : "memory");
        asm volatile("red.relaxed.gpu.global.add.u32 [%0], 1;" ::"l"(&g_oflag[(quarter * 8 + wg) * 32 + (head >> 2) * 4]) : "memory");
    }
    if (tid == 0) TSTAMP0(1, 3);

    if (wg < 2) {
        const int wi = warp;
        const int r0 = mt * 64 + wi * 16 + g;
        const int cb = nt * 128 + wg * 64;
        uint32_t xr[16], wr[8];
#pragma unroll
        for (int j = 0; j < 8; j++) {
            xr[2 * j] = __ldg((const uint32_t*)(x + (size_t)r0 * DM + cb + 8 * j + 2 * t));
            xr[2 * j + 1] = __ldg((const uint32_t*)(x + (size_t)(r0 + 8) * DM + cb + 8 * j + 2 * t));
            wr[j] = __ldg((const uint32_t*)(w_r + cb + 8 * j + 2 * t));
        }
        float wsum = 0.f;
        {
            const uint4 a = __ldg((const uint4*)(w_r + lane * 16)), b = __ldg((const uint4*)(w_r + lane * 16 + 8));
            const uint32_t w[8] = {a.x, a.y, a.z, a.w, b.x, b.y, b.z, b.w};
#pragma unroll
            for (int i = 0; i < 8; i++) wsum += bf_lo(w[i]) + bf_hi(w[i]);
#pragma unroll
            for (int o = 16; o > 0; o >>= 1) wsum += __shfl_xor_sync(0xffffffffu, wsum, o);
        }
        float acc[32];
#pragma unroll
        for (int i = 0; i < 32; i++) acc[i] = 0.f;
        fence_regs(acc);
#pragma unroll 1
        for (int i = 0; i < 8; i++) {
            mbar_wait(obar + 8 * i, 0);
            const int kb = __shfl_sync(0xffffffffu, (int)s_order[i], 0);
            mbar_wait(wbar + 8 * kb, 0);
            const uint32_t wa = (kb < 4) ? (KF_OFF_WO + kb * 16384) : ((kb - 4) * KF_CH_S);
            const uint64_t da = make_desc(sb + (4 + (kb >> 1)) * KF_CH_S + (kb & 1) * 8192, 16, 1024, 1);
            const uint64_t db = make_desc(sb + wa + wg * 8192, 1024, 1024, 1);
            wg_fence();
#pragma unroll
            for (int k = 0; k < 4; k++) wgmma_k3_n64(acc, da + k * 2, db + k * 128, (i | k) != 0);
            wg_commit();
        }
        wg_wait<0>();
        fence_regs(acc);
        if (tid == 0) TSTAMP0(2, 2);
        float hv[32];
        uint32_t hp[16];
        float s0 = 0.f, s1 = 0.f, d0 = 0.f, d1 = 0.f;
#pragma unroll
        for (int j = 0; j < 8; j++) {
            const uint32_t a01 = pack_bf16(acc[4 * j], acc[4 * j + 1]), a23 = pack_bf16(acc[4 * j + 2], acc[4 * j + 3]);
            hp[2 * j] = pack_bf16(bf_lo(xr[2 * j]) + bf_lo(a01), bf_hi(xr[2 * j]) + bf_hi(a01));
            hp[2 * j + 1] = pack_bf16(bf_lo(xr[2 * j + 1]) + bf_lo(a23), bf_hi(xr[2 * j + 1]) + bf_hi(a23));
            hv[4 * j] = bf_lo(hp[2 * j]); hv[4 * j + 1] = bf_hi(hp[2 * j]);
            hv[4 * j + 2] = bf_lo(hp[2 * j + 1]); hv[4 * j + 3] = bf_hi(hp[2 * j + 1]);
            const float wl = bf_lo(wr[j]), wh = bf_hi(wr[j]);
            s0 += hv[4 * j] + hv[4 * j + 1];
            s1 += hv[4 * j + 2] + hv[4 * j + 3];
            d0 = fmaf(hv[4 * j], wl, fmaf(hv[4 * j + 1], wh, d0));
            d1 = fmaf(hv[4 * j + 2], wl, fmaf(hv[4 * j + 3], wh, d1));
        }
        float mu0 = s0 * (1.f / 16), mu1 = s1 * (1.f / 16);
        float q0 = 0.f, q1 = 0.f;
#pragma unroll
        for (int j = 0; j < 8; j++) {
            float a = hv[4 * j] - mu0, b = hv[4 * j + 1] - mu0, c = hv[4 * j + 2] - mu1, d = hv[4 * j + 3] - mu1;
            q0 = fmaf(a, a, fmaf(b, b, q0));
            q1 = fmaf(c, c, fmaf(d, d, q1));
        }
#pragma unroll
        for (int o = 1; o < 4; o <<= 1) {
            const float m0 = __shfl_xor_sync(0xffffffffu, mu0, o), m1 = __shfl_xor_sync(0xffffffffu, mu1, o);
            const float e0 = __shfl_xor_sync(0xffffffffu, q0, o), e1 = __shfl_xor_sync(0xffffffffu, q1, o);
            d0 += __shfl_xor_sync(0xffffffffu, d0, o);
            d1 += __shfl_xor_sync(0xffffffffu, d1, o);
            const float f0 = mu0 - m0, f1 = mu1 - m1;
            q0 = q0 + e0 + f0 * f0 * (8.f * o);
            q1 = q1 + e1 + f1 * f1 * (8.f * o);
            mu0 = 0.5f * (mu0 + m0); mu1 = 0.5f * (mu1 + m1);
        }
        float4* part = g_part + (size_t)mt * 512 + wi * 16 + g;
        if (t < 2) {
            float4* dst = part + (nt * 2 + wg) * 64 + t * 8;
            const float a = t ? mu1 : mu0, b = t ? q1 : q0, c = t ? d1 : d0;
            asm volatile("st.relaxed.gpu.global.v4.f32 [%0], {%1, %2, %3, %4};" ::"l"(dst), "f"(a), "f"(b), "f"(c), "f"(1.0f) : "memory");
        }
        if (tid == 0) TSTAMP0(2, 5);
        const uint32_t stg_off = KF_OFF_WO + (wi >> 1) * 16384 + wg * 8192 + (wi & 1) * 4096;
        const uint32_t stg_o = sb + stg_off, stg_h = stg_o + 2048;
        const int srow = (lane & 7) + ((lane >> 3) & 1) * 8;
        const int sj = lane >> 4;
        named_sync(4 + wg, 128);
#pragma unroll
        for (int j = 0; j < 8; j += 2) {
            const uint32_t off = srow * 128 + (((j + sj) ^ (srow & 7)) << 4);
            stmatrix_x4(stg_h + off, hp[2 * j], hp[2 * j + 1], hp[2 * j + 2], hp[2 * j + 3]);
        }
        __syncwarp();
#pragma unroll
        for (int i = 0; i < 4; i++) {
            const int row = i * 4 + (lane >> 3), ch = lane & 7;
            const uint4 vh = *(const uint4*)(sp + stg_off + 2048 + row * 128 + ((ch ^ (row & 7)) << 4));
            *(uint4*)(g_h + (size_t)(mt * 64 + wi * 16 + row) * DM + cb + ch * 8) = vh;
        }
        named_arrive(8, 288);
        if (tid == 0) TSTAMP0(2, 6);
        float mean[2], den[2], rr[2];
        {
            float4 v[4];
            int spins = 0;
            while (true) {
#pragma unroll
                for (int i = 0; i < 4; i++) {
                    const float4* p = part + (t + (i & 1) * 4) * 64 + (i >> 1) * 8;
                    asm volatile("ld.relaxed.gpu.global.v4.f32 {%0, %1, %2, %3}, [%4];" : "=f"(v[i].x), "=f"(v[i].y), "=f"(v[i].z), "=f"(v[i].w) : "l"(p) : "memory");
                }
                const bool ok = (v[0].w != 0.f) && (v[1].w != 0.f) && (v[2].w != 0.f) && (v[3].w != 0.f);
                if (__all_sync(0xffffffffu, ok) || ++spins > (1 << 22)) break;
            }
#pragma unroll
            for (int u = 0; u < 2; u++) {
                float mu = v[2 * u].x + v[2 * u + 1].x, m2 = v[2 * u].y + v[2 * u + 1].y, hw = v[2 * u].z + v[2 * u + 1].z;
#pragma unroll
                for (int o = 1; o < 4; o <<= 1) {
                    mu += __shfl_xor_sync(0xffffffffu, mu, o);
                    m2 += __shfl_xor_sync(0xffffffffu, m2, o);
                    hw += __shfl_xor_sync(0xffffffffu, hw, o);
                }
                mu *= 0.125f;
                const float da = v[2 * u].x - mu, db = v[2 * u + 1].x - mu;
                float dd = 64.f * (da * da + db * db);
#pragma unroll
                for (int o = 1; o < 4; o <<= 1) dd += __shfl_xor_sync(0xffffffffu, dd, o);
                m2 += dd;
                mean[u] = rbf(mu);
                den[u] = rbf(sqrtf(rbf(rbf(m2 * (1.f / DM)) + 1e-5f)));
                rr[u] = rbf((hw - mean[u] * wsum) / den[u]);
            }
        }
        if (tid == 0) TSTAMP0(2, 3);
        named_arrive(3, 512);
        if (nt == 0 && wg == 0) {
            float2* s_st = (float2*)(sp + KF_OFF_WO + 49152);
            if (t == 0) {
                s_key[wi * 16 + g] = make_key(rr[0], r0);
                s_key[wi * 16 + g + 8] = make_key(rr[1], r0 + 8);
                s_st[wi * 16 + g] = make_float2(mean[0], den[0]);
                s_st[wi * 16 + g + 8] = make_float2(mean[1], den[1]);
            }
            named_sync(4, 128);
            if (warp == 0) {
                uint32_t k1, k2;
                warp_top2(s_key[lane], s_key[lane + 32], k1, k2);
                if (lane < 2) {
                    const uint32_t k = lane ? k2 : k1;
                    const float2 st = s_st[key_token(k) & 63];
                    asm volatile("st.relaxed.gpu.global.v4.u32 [%0], {%1, %2, %3, %4};" ::"l"(g_cand + mt * 2 + lane), "r"(k),
                                 "r"(1u), "r"(__float_as_uint(st.x)), "r"(__float_as_uint(st.y)) : "memory");
                }
            }
        }
        const float i0 = 1.f / den[0], i1 = 1.f / den[1];
#pragma unroll
        for (int j = 0; j < 8; j += 2) {
            uint32_t ro[4];
#pragma unroll
            for (int u = 0; u < 2; u++) {
                const int jj = j + u;
                const float a = hv[4 * jj], b = hv[4 * jj + 1], c = hv[4 * jj + 2], d = hv[4 * jj + 3];
                const uint32_t u01 = pack_bf16(a - mean[0], b - mean[0]), u23 = pack_bf16(c - mean[1], d - mean[1]);
                const uint32_t n01 = pack_bf16(bf_lo(u01) * i0, bf_hi(u01) * i0), n23 = pack_bf16(bf_lo(u23) * i1, bf_hi(u23) * i1);
                ro[2 * u] = pack_bf16(a + bf_lo(n01), b + bf_hi(n01));
                ro[2 * u + 1] = pack_bf16(c + bf_lo(n23), d + bf_hi(n23));
            }
            const uint32_t off = srow * 128 + (((j + sj) ^ (srow & 7)) << 4);
            stmatrix_x4(stg_o + off, ro[0], ro[1], ro[2], ro[3]);
        }
        __syncwarp();
#pragma unroll
        for (int i = 0; i < 4; i++) {
            const int row = i * 4 + (lane >> 3), ch = lane & 7;
            const uint4 vo = *(const uint4*)(sp + stg_off + row * 128 + ((ch ^ (row & 7)) << 4));
            *(uint4*)(out + (size_t)(mt * 64 + wi * 16 + row) * DM + cb + ch * 8) = vo;
        }
        named_sync(4 + wg, 128);
        if ((tid & 127) == 0) red_release_add(&g_sflag[mt]);
        if (tid == 0) TSTAMP0(2, 4);
    } else {
        const bool worker = blockIdx.x < FF / 16;
        const bool downer = blockIdx.x >= 64;
        const int mtid = tid - 256, mwarp = mtid >> 5;
        const int c0 = (blockIdx.x - 64) * 8;
        float* s_x = (float*)(sp + KF_OFF_WO + 49152 + 8192);
        float* s_red = (float*)(sp + KF_OFF_WO + 49152 + 8192 + 4096);
        if (mwarp == 2) {
            named_sync(1, 512);
            if (lane == 0 && worker) {
                mbar_expect_tx(gbar, 32768);
                for (int i = 0; i < 4; i++) {
                    tma_load_2d(sb + i * KF_CH_S + 16384, &tm_g, blockIdx.x * 16, i * 128, gbar);
                    tma_load_2d(sb + (4 + i) * KF_CH_S + 16384, &tm_u, blockIdx.x * 16, i * 128, gbar);
                }
            }
            uint32_t done = 0;
            int n = 0, spins = 0;
            while (done != 0xFFu && ++spins < (1 << 22)) {
                const bool rdy = lane < 8 && ld_acquire(&g_oflag[mt * 32 + lane * 4]) >= 4u;
                uint32_t todo = __ballot_sync(0xffffffffu, rdy) & ~done;
                done |= todo;
                if (todo && lane == 0) {
                    asm volatile("fence.proxy.async.global;" ::: "memory");
                    while (todo) {
                        const int kb = __ffs(todo) - 1;
                        todo &= todo - 1;
                        s_order[n] = kb;
                        mbar_expect_tx(obar + 8 * n, 8192);
                        tma_load_3d(sb + (4 + (kb >> 1)) * KF_CH_S + (kb & 1) * 8192, &tm_o, 0, mt * 64, kb, obar + 8 * n);
                        n++;
                    }
                }
                n = __shfl_sync(0xffffffffu, n, 0);
            }
            if (lane == 0) TSTAMP0(2, 1);
        }
        if (mwarp == 1) {
            named_sync(8, 288);
            if (lane == 0) {
                red_release_add(&g_hflag[mt]);
                if (downer) {
                    mbar_expect_tx(dbar, 7 * 4096);
                    for (int i = 0; i < 7; i++) tma_load_2d(sb + (4 + (i >> 2)) * KF_CH_S + (i & 3) * 4096, &tm_d, c0, i * 256, dbar);
                }
            }
            __syncwarp();
        }
        if (mtid == 0) TSTAMP0(3, 0);
        named_sync(3, 512);
        if (mwarp == 0) {
            uint4 ca, cb4;
            int spins = 0;
            while (true) {
                asm volatile("ld.relaxed.gpu.global.v4.u32 {%0, %1, %2, %3}, [%4];" : "=r"(ca.x), "=r"(ca.y), "=r"(ca.z), "=r"(ca.w) : "l"(g_cand + 2 * lane) : "memory");
                asm volatile("ld.relaxed.gpu.global.v4.u32 {%0, %1, %2, %3}, [%4];" : "=r"(cb4.x), "=r"(cb4.y), "=r"(cb4.z), "=r"(cb4.w) : "l"(g_cand + 2 * lane + 1) : "memory");
                const unsigned int hf = ld_acquire(&g_hflag[lane]);
                const bool ok = ca.y != 0 && cb4.y != 0 && hf >= 4u;
                if (__all_sync(0xffffffffu, ok) || ++spins > (1 << 22)) break;
            }
            uint32_t k1, k2;
            warp_top2(ca.x, cb4.x, k1, k2);
            if (ca.x == k1) s_sel[0] = ca;
            if (cb4.x == k1) s_sel[0] = cb4;
            if (ca.x == k2) s_sel[1] = ca;
            if (cb4.x == k2) s_sel[1] = cb4;
        }
        named_sync(2, 256);
        if (mtid == 0) TSTAMP0(3, 1);
        int idx[2];
        float mean[2], inv[2], rv[2];
#pragma unroll
        for (int u = 0; u < 2; u++) {
            const uint4 c = s_sel[u];
            idx[u] = key_token(c.x);
            rv[u] = key_value(c.x);
            mean[u] = __uint_as_float(c.z);
            inv[u] = 1.f / __uint_as_float(c.w);
        }
        float hfin = 0.f;
        if (downer && mtid < 16) hfin = __bfloat162float(__ldcg((const __nv_bfloat16*)(g_h + (size_t)((mtid >> 3) ? idx[1] : idx[0]) * DM + c0 + (mtid & 7))));
        if (worker) {
            {
                const uint32_t h0 = __ldcg((const uint32_t*)(g_h + (size_t)idx[0] * DM + 2 * mtid));
                const uint32_t h1 = __ldcg((const uint32_t*)(g_h + (size_t)idx[1] * DM + 2 * mtid));
                const uint32_t u0 = pack_bf16(bf_lo(h0) - mean[0], bf_hi(h0) - mean[0]), u1 = pack_bf16(bf_lo(h1) - mean[1], bf_hi(h1) - mean[1]);
                const uint32_t n0 = pack_bf16(bf_lo(u0) * inv[0], bf_hi(u0) * inv[0]), n1 = pack_bf16(bf_lo(u1) * inv[1], bf_hi(u1) * inv[1]);
                *(float4*)(s_x + 4 * mtid) = make_float4(bf_lo(n0), bf_lo(n1), bf_hi(n0), bf_hi(n1));
            }
            if (mtid == 0) TSTAMP0(3, 5);
            mbar_wait(gbar, 0);
            named_sync(2, 256);
            if (mtid == 0) TSTAMP0(3, 6);
            float acc[8];
#pragma unroll
            for (int i = 0; i < 8; i++) acc[i] = 0.f;
            const uint8_t* wbase = sp + (mwarp >> 2) * (4 * KF_CH_S) + 16384 + lane * 32 + (mwarp & 3) * 8;
#pragma unroll
            for (int k = 0; k < 16; k++) {
                const uint2 w = *(const uint2*)(wbase + (k >> 2) * KF_CH_S + (k & 3) * 1024);
                const float2 xx = *(const float2*)(s_x + 2 * (lane + 32 * k));
                const float x0 = xx.x, x1 = xx.y;
                const float w0 = bf_lo(w.x), w1 = bf_hi(w.x), w2 = bf_lo(w.y), w3 = bf_hi(w.y);
                acc[0] = fmaf(x0, w0, acc[0]); acc[1] = fmaf(x0, w1, acc[1]); acc[2] = fmaf(x0, w2, acc[2]); acc[3] = fmaf(x0, w3, acc[3]);
                acc[4] = fmaf(x1, w0, acc[4]); acc[5] = fmaf(x1, w1, acc[5]); acc[6] = fmaf(x1, w2, acc[6]); acc[7] = fmaf(x1, w3, acc[7]);
            }
#define KF_STEP(O, N)                                                          \
            {                                                                  \
                const bool up = (lane & (O)) != 0;                             \
                _Pragma("unroll") for (int i = 0; i < (N); i++) {              \
                    const float send = up ? acc[i] : acc[i + (N)];             \
                    const float keep = up ? acc[i + (N)] : acc[i];             \
                    acc[i] = keep + __shfl_xor_sync(0xffffffffu, send, (O));   \
                }                                                              \
            }
            KF_STEP(16, 4) KF_STEP(8, 2) KF_STEP(4, 1)
            acc[0] += __shfl_xor_sync(0xffffffffu, acc[0], 2);
            acc[0] += __shfl_xor_sync(0xffffffffu, acc[0], 1);
            if ((lane & 3) == 0) {
                const int v = ((lane & 16) ? 4 : 0) + ((lane & 8) ? 2 : 0) + ((lane & 4) ? 1 : 0);
                s_gu[(v >> 2) * 32 + mwarp * 4 + (v & 3)] = acc[0];
            }
            named_sync(2, 256);
            if (mtid < 16) {
                uint32_t a2 = 0;
#pragma unroll
                for (int u = 0; u < 2; u++) {
                    const float gb = rbf(s_gu[u * 32 + mtid]);
                    const float sg = rbf(gb / (1.f + __expf(-gb)));
                    float a = sg * rbf(s_gu[u * 32 + 16 + mtid]);
                    uint32_t ab = (uint32_t)__bfloat16_as_ushort(__float2bfloat16_rn(a));
                    if (ab == 0xFFFFu) ab = 0x7FFFu;
                    a2 |= ab << (16 * u);
                }
                asm volatile("st.relaxed.gpu.global.u32 [%0], %1;" ::"l"(g_act + blockIdx.x * 16 + mtid), "r"(a2) : "memory");
            }
            if (mtid == 0) TSTAMP0(3, 2);
        }
        if (downer) {
            uint32_t av[7];
            {
                int spins = 0;
                while (true) {
                    bool ok = true;
#pragma unroll
                    for (int j = 0; j < 7; j++) {
                        asm volatile("ld.relaxed.gpu.global.u32 %0, [%1];" : "=r"(av[j]) : "l"(g_act + mtid + 256 * j) : "memory");
                        ok = ok && ((av[j] & 0xFFFFu) != 0xFFFFu) && ((av[j] >> 16) != 0xFFFFu);
                    }
                    if (mtid < 2) ok = ok && (ld_acquire(&g_sflag[(mtid ? idx[1] : idx[0]) >> 6]) >= 8u);
                    if (__all_sync(0xffffffffu, ok) || ++spins > (1 << 20)) break;
                    __nanosleep(20);
                }
            }
            if (mtid == 0) TSTAMP0(3, 3);
            mbar_wait(dbar, 0);
            float acc[16];
#pragma unroll
            for (int i = 0; i < 16; i++) acc[i] = 0.f;
#pragma unroll
            for (int j = 0; j < 7; j++) {
                const uint4 w = *(const uint4*)(sp + (4 + (j >> 2)) * KF_CH_S + (j & 3) * 4096 + mtid * 16);
                const float a0 = bf_lo(av[j]), a1 = bf_hi(av[j]);
                const uint32_t ww[4] = {w.x, w.y, w.z, w.w};
#pragma unroll
                for (int q = 0; q < 4; q++) {
                    const float wl = bf_lo(ww[q]), wh = bf_hi(ww[q]);
                    acc[2 * q] = fmaf(a0, wl, acc[2 * q]); acc[2 * q + 1] = fmaf(a0, wh, acc[2 * q + 1]);
                    acc[8 + 2 * q] = fmaf(a1, wl, acc[8 + 2 * q]); acc[8 + 2 * q + 1] = fmaf(a1, wh, acc[8 + 2 * q + 1]);
                }
            }
            KF_STEP(16, 8) KF_STEP(8, 4) KF_STEP(4, 2) KF_STEP(2, 1)
            acc[0] += __shfl_xor_sync(0xffffffffu, acc[0], 1);
            if ((lane & 1) == 0) {
                const int v = ((lane & 16) ? 8 : 0) + ((lane & 8) ? 4 : 0) + ((lane & 4) ? 2 : 0) + ((lane & 2) ? 1 : 0);
                s_red[mwarp * 16 + v] = acc[0];
            }
            named_sync(2, 256);
            if (mtid < 16) {
                const int u = mtid >> 3;
                float y = 0.f;
#pragma unroll
                for (int w = 0; w < 8; w++) y += s_red[w * 16 + mtid];
                const float sig = rbf(1.f / (1.f + __expf(-(u ? rv[1] : rv[0]))));
                const float xn = rbf(rbf(hfin - (u ? mean[1] : mean[0])) * (u ? inv[1] : inv[0]));
                const float ov = hfin + rbf(xn + rbf(rbf(y) * sig));
                out[(size_t)(u ? idx[1] : idx[0]) * DM + c0 + (mtid & 7)] = __float2bfloat16_rn(ov);
            }
            if (blockIdx.x == gridDim.x - 1 && mtid == 0) g_epoch = g_epoch + 1u;
            if (mtid == 0) TSTAMP0(3, 4);
        }
    }
}

typedef CUresult (*PFN_encodeTiled)(CUtensorMap*, CUtensorMapDataType, cuuint32_t, void*, const cuuint64_t*, const cuuint64_t*,
                                    const cuuint32_t*, const cuuint32_t*, CUtensorMapInterleave, CUtensorMapSwizzle,
                                    CUtensorMapL2promotion, CUtensorMapFloatOOBfill);

void make_map(PFN_encodeTiled enc, CUtensorMap* m, const void* ptr, uint64_t cols, uint64_t rows, uint32_t bcols, uint32_t brows) {
    cuuint64_t dims[2] = {cols, rows};
    cuuint64_t strides[1] = {cols * 2};
    cuuint32_t box[2] = {bcols, brows};
    cuuint32_t es[2] = {1, 1};
    enc(m, CU_TENSOR_MAP_DATA_TYPE_BFLOAT16, 2, const_cast<void*>(ptr), dims, strides, box, es, CU_TENSOR_MAP_INTERLEAVE_NONE,
        CU_TENSOR_MAP_SWIZZLE_128B, CU_TENSOR_MAP_L2_PROMOTION_L2_256B, CU_TENSOR_MAP_FLOAT_OOB_FILL_NONE);
}

void make_map3(PFN_encodeTiled enc, CUtensorMap* m, const void* ptr, uint64_t d0, uint64_t rows, uint64_t d2, uint64_t row_stride_bytes,
               uint64_t d2_stride_bytes, uint32_t b0, uint32_t b1, uint32_t b2) {
    cuuint64_t dims[3] = {d0, rows, d2};
    cuuint64_t strides[2] = {row_stride_bytes, d2_stride_bytes};
    cuuint32_t box[3] = {b0, b1, b2};
    cuuint32_t es[3] = {1, 1, 1};
    enc(m, CU_TENSOR_MAP_DATA_TYPE_BFLOAT16, 3, const_cast<void*>(ptr), dims, strides, box, es, CU_TENSOR_MAP_INTERLEAVE_NONE,
        CU_TENSOR_MAP_SWIZZLE_128B, CU_TENSOR_MAP_L2_PROMOTION_L2_256B, CU_TENSOR_MAP_FLOAT_OOB_FILL_NONE);
}

void make_map_plain(PFN_encodeTiled enc, CUtensorMap* m, const void* ptr, uint64_t cols, uint64_t rows, uint32_t bcols, uint32_t brows) {
    cuuint64_t dims[2] = {cols, rows};
    cuuint64_t strides[1] = {cols * 2};
    cuuint32_t box[2] = {bcols, brows};
    cuuint32_t es[2] = {1, 1};
    enc(m, CU_TENSOR_MAP_DATA_TYPE_BFLOAT16, 2, const_cast<void*>(ptr), dims, strides, box, es, CU_TENSOR_MAP_INTERLEAVE_NONE,
        CU_TENSOR_MAP_SWIZZLE_NONE, CU_TENSOR_MAP_L2_PROMOTION_NONE, CU_TENSOR_MAP_FLOAT_OOB_FILL_NONE);
}

template <typename... KArgs, typename... Args>
void launch(void (*kern)(KArgs...), int grid, int block, int smem, bool pdl, Args... args) {
    cudaLaunchConfig_t cfg = {};
    cfg.gridDim = dim3(grid);
    cfg.blockDim = dim3(block);
    cfg.dynamicSmemBytes = smem;
    cfg.stream = cudaStreamPerThread;
    cudaLaunchAttribute at[1];
    at[0].id = cudaLaunchAttributeProgrammaticStreamSerialization;
    at[0].val.programmaticStreamSerializationAllowed = 1;
    cfg.attrs = at;
    cfg.numAttrs = pdl ? 1 : 0;
    cudaLaunchKernelEx(&cfg, kern, KArgs(args)...);
}

}

extern "C" void kernel_launch(void* const* d_in, const int* in_sizes, int n_in, void* d_out, int out_size) {
    const __nv_bfloat16* x = (const __nv_bfloat16*)d_in[0];
    const __nv_bfloat16* wqkv = (const __nv_bfloat16*)d_in[1];
    const __nv_bfloat16* wo = (const __nv_bfloat16*)d_in[2];
    const __nv_bfloat16* w_r = (const __nv_bfloat16*)d_in[4];
    const __nv_bfloat16* w_gate = (const __nv_bfloat16*)d_in[5];
    const __nv_bfloat16* w_up = (const __nv_bfloat16*)d_in[6];
    const __nv_bfloat16* w_down = (const __nv_bfloat16*)d_in[7];
    __nv_bfloat16* out = (__nv_bfloat16*)d_out;

    static PFN_encodeTiled enc = nullptr;
    static void* g_o_ptr = nullptr;
    if (!enc) {
        cudaDriverEntryPointQueryResult qres;
        void* fn = nullptr;
        cudaGetDriverEntryPoint("cuTensorMapEncodeTiled", &fn, cudaEnableDefault, &qres);
        enc = (PFN_encodeTiled)fn;
        cudaGetSymbolAddress(&g_o_ptr, g_o);
        cudaFuncSetAttribute(k1_qkv, cudaFuncAttributeMaxDynamicSharedMemorySize, K1_SMEM);
        cudaFuncSetAttribute(kf_main, cudaFuncAttributeMaxDynamicSharedMemorySize, KF_SMEM);
    }
    CUtensorMap tm_x, tm_w, tm_o, tm_wo, tm_g, tm_u, tm_d;
    make_map_plain(enc, &tm_d, w_down, DM, FF, 8, 256);
    make_map_plain(enc, &tm_g, w_gate, FF, DM, 16, 128);
    make_map_plain(enc, &tm_u, w_up, FF, DM, 16, 128);
    make_map(enc, &tm_x, x, DM, SEQ, 64, 128);
    make_map3(enc, &tm_w, wqkv, DM, DM, 3, 3 * DM * 2, DM * 2, 64, 64, 3);
    make_map3(enc, &tm_o, g_o_ptr, 64, SEQ, 8, DM * 2, 128, 64, 64, 1);
    make_map3(enc, &tm_wo, wo, 64, DM, 8, DM * 2, 128, 64, 64, 2);

    const bool pdl = true;
    launch(k1_qkv, 128, 544, K1_SMEM, false, tm_x, tm_w, x);
    launch(kf_main, 128, 512, KF_SMEM, pdl, tm_o, tm_wo, tm_g, tm_u, tm_d, x, wo, w_r, w_gate, w_up, w_down, out);
}
```

```cpp
#include <cuda_runtime.h>
#include <cuda_bf16.h>
#include <cuda.h>
#include <stdint.h>

namespace {

constexpr int SEQ = 2048, DM = 512, NH = 32, FF = 1792;

__device__ __align__(1024) uint8_t g_q[NH * 2 * SEQ * 16];
__device__ __align__(1024) uint8_t g_kv[NH * 8 * 16384];
__device__ float g_norm[16 * NH * 3];
__device__ __align__(1024) __nv_bfloat16 g_o[SEQ * DM];
__device__ __align__(1024) __nv_bfloat16 g_h[SEQ * DM];
__device__ __align__(16) uint4 g_cand[64];
__device__ unsigned int g_oflag[32 * 32];
__device__ unsigned int g_hflag[32];
__device__ unsigned int g_sflag[32];
__device__ unsigned int g_act[FF];
__device__ unsigned int g_epoch;
__device__ __align__(16) float4 g_ln1[SEQ];
__device__ __align__(16) float4 g_part[32 * 8 * 64];

#define TSTAMP(K, I)
#define TSTAMP0(K, I)
__device__ __forceinline__ uint32_t smem_u32(const void* p) { return (uint32_t)__cvta_generic_to_shared(p); }
__device__ __forceinline__ void wg_fence() { asm volatile("wgmma.fence.sync.aligned;" ::: "memory"); }
__device__ __forceinline__ void wg_commit() { asm volatile("wgmma.commit_group.sync.aligned;" ::: "memory"); }
template <int N> __device__ __forceinline__ void wg_wait() { asm volatile("wgmma.wait_group.sync.aligned %0;" ::"n"(N) : "memory"); }
template <int N> __device__ __forceinline__ void fence_regs(float (&r)[N]) {
#pragma unroll
    for (int i = 0; i < N; i++) asm volatile("" : "+f"(r[i])::"memory");
}
__device__ __forceinline__ uint64_t make_desc(uint32_t addr, uint32_t lbo, uint32_t sbo, uint32_t swz) {
    uint64_t d = 0;
    d |= (uint64_t)((addr & 0x3FFFF) >> 4);
    d |= (uint64_t)((lbo & 0x3FFFF) >> 4) << 16;
    d |= (uint64_t)((sbo & 0x3FFFF) >> 4) << 32;
    d |= (uint64_t)swz << 62;
    return d;
}
__device__ __forceinline__ void mbar_init(uint32_t bar, uint32_t cnt) {
    asm volatile("mbarrier.init.shared::cta.b64 [%0], %1;" ::"r"(bar), "r"(cnt) : "memory");
}
__device__ __forceinline__ void mbar_expect_tx(uint32_t bar, uint32_t bytes) {
    asm volatile("mbarrier.arrive.expect_tx.shared::cta.b64 _, [%0], %1;" ::"r"(bar), "r"(bytes) : "memory");
}
__device__ __forceinline__ void mbar_arrive(uint32_t bar) {
    asm volatile("mbarrier.arrive.shared::cta.b64 _, [%0];" ::"r"(bar) : "memory");
}
__device__ __forceinline__ void mbar_wait(uint32_t bar, uint32_t parity) {
    asm volatile(
        "{\n.reg .pred p;\nWAIT_%=:\n"
        "mbarrier.try_wait.parity.shared::cta.b64 p, [%0], %1;\n"
        "@p bra DONE_%=;\nbra WAIT_%=;\nDONE_%=:\n}\n" ::"r"(bar), "r"(parity) : "memory");
}
__device__ __forceinline__ void bulk_g2s(uint32_t dst, const void* src, uint32_t bytes, uint32_t bar) {
    asm volatile("cp.async.bulk.shared::cluster.global.mbarrier::complete_tx::bytes [%0], [%1], %2, [%3];" ::"r"(dst),
                 "l"(src), "r"(bytes), "r"(bar) : "memory");
}
__device__ __forceinline__ void bulk_s2g(void* dst, uint32_t src, uint32_t bytes) {
    asm volatile("cp.async.bulk.global.shared::cta.bulk_group [%0], [%1], %2;" ::"l"(dst), "r"(src), "r"(bytes) : "memory");
}
__device__ __forceinline__ void tma_load_2d(uint32_t dst, const CUtensorMap* tm, int c0, int c1, uint32_t bar) {
    asm volatile("cp.async.bulk.tensor.2d.shared::cluster.global.mbarrier::complete_tx::bytes [%0], [%1, {%3, %4}], [%2];" ::"r"(dst),
                 "l"(tm), "r"(bar), "r"(c0), "r"(c1) : "memory");
}
__device__ __forceinline__ void tma_load_3d(uint32_t dst, const CUtensorMap* tm, int c0, int c1, int c2, uint32_t bar) {
    asm volatile("cp.async.bulk.tensor.3d.shared::cluster.global.mbarrier::complete_tx::bytes [%0], [%1, {%3, %4, %5}], [%2];" ::"r"(dst),
                 "l"(tm), "r"(bar), "r"(c0), "r"(c1), "r"(c2) : "memory");
}
__device__ __forceinline__ void tma_load_2d_mc(uint32_t dst, const CUtensorMap* tm, int c0, int c1, uint32_t bar, uint16_t mask) {
    asm volatile("cp.async.bulk.tensor.2d.shared::cluster.global.mbarrier::complete_tx::bytes.multicast::cluster [%0], [%1, {%3, %4}], [%2], %5;" ::"r"(dst),
                 "l"(tm), "r"(bar), "r"(c0), "r"(c1), "h"(mask) : "memory");
}
__device__ __forceinline__ void mbar_arrive_cluster(uint32_t bar, uint32_t cta) {
    asm volatile("{\n.reg .b32 ra;\nmapa.shared::cluster.u32 ra, %0, %1;\nmbarrier.arrive.release.cluster.shared::cluster.b64 _, [ra];\n}" ::"r"(bar), "r"(cta) : "memory");
}
__device__ __forceinline__ void cluster_sync() {
    asm volatile("barrier.cluster.arrive.release.aligned;\nbarrier.cluster.wait.acquire.aligned;" ::: "memory");
}
__device__ __forceinline__ void prefetch_l2(const void* p, uint32_t bytes) {
    asm volatile("cp.async.bulk.prefetch.L2.global [%0], %1;" ::"l"(p), "r"(bytes) : "memory");
}
__device__ __forceinline__ void fence_proxy_async() { asm volatile("fence.proxy.async.shared::cta;" ::: "memory"); }
__device__ __forceinline__ void fence_barrier_init() { asm volatile("fence.mbarrier_init.release.cluster;" ::: "memory"); }
__device__ __forceinline__ void pdl_launch() { asm volatile("griddepcontrol.launch_dependents;" ::: "memory"); }
__device__ __forceinline__ void pdl_wait() { asm volatile("griddepcontrol.wait;" ::: "memory"); }
__device__ __forceinline__ void named_sync(int id, int n) { asm volatile("bar.sync %0, %1;" ::"r"(id), "r"(n) : "memory"); }
__device__ __forceinline__ void named_arrive(int id, int n) { asm volatile("bar.arrive %0, %1;" ::"r"(id), "r"(n) : "memory"); }

__device__ __forceinline__ float ex2f(float x) { float y; asm("ex2.approx.ftz.f32 %0, %1;" : "=f"(y) : "f"(x)); return y; }
__device__ __forceinline__ uint32_t pack_bf16(float lo, float hi) {
    uint32_t r; asm("cvt.rn.bf16x2.f32 %0, %1, %2;" : "=r"(r) : "f"(hi), "f"(lo)); return r;
}
__device__ __forceinline__ float bf_lo(uint32_t v) { return __uint_as_float(v << 16); }
__device__ __forceinline__ float bf_hi(uint32_t v) { return __uint_as_float(v & 0xFFFF0000u); }
__device__ __forceinline__ float rbf(float x) { return __bfloat162float(__float2bfloat16_rn(x)); }
__device__ __forceinline__ uint32_t fma_bf16x2(uint32_t a, uint32_t b, uint32_t c) {
    uint32_t r; asm("fma.rn.bf16x2 %0, %1, %2, %3;" : "=r"(r) : "r"(a), "r"(b), "r"(c)); return r;
}
__device__ __forceinline__ void stmatrix_x4(uint32_t addr, uint32_t r0, uint32_t r1, uint32_t r2, uint32_t r3) {
    asm volatile("stmatrix.sync.aligned.m8n8.x4.shared.b16 [%0], {%1, %2, %3, %4};" ::"r"(addr), "r"(r0), "r"(r1), "r"(r2), "r"(r3) : "memory");
}
__device__ __forceinline__ void stmatrix_x4_trans(uint32_t addr, uint32_t r0, uint32_t r1, uint32_t r2, uint32_t r3) {
    asm volatile("stmatrix.sync.aligned.m8n8.x4.trans.shared.b16 [%0], {%1, %2, %3, %4};" ::"r"(addr), "r"(r0), "r"(r1), "r"(r2), "r"(r3) : "memory");
}

__device__ __forceinline__ void wgmma_k1_n136(float (&d)[68], uint64_t desca, uint64_t descb, int scale_d) {
  asm volatile("{\n.reg .pred p;\nsetp.ne.b32 p, %70, 0;\n"
    "wgmma.mma_async.sync.aligned.m64n136k16.f32.bf16.bf16 "
    "{%0, %1, %2, %3, %4, %5, %6, %7, %8, %9, %10, %11, %12, %13, %14, %15, %16, %17, %18, %19, %20, %21, %22, %23, %24, %25, %26, %27, %28, %29, %30, %31, %32, %33, %34, %35, %36, %37, %38, %39, %40, %41, %42, %43, %44, %45, %46, %47, %48, %49, %50, %51, %52, %53, %54, %55, %56, %57, %58, %59, %60, %61, %62, %63, %64, %65, %66, %67}, "
    "%68, %69, p, 1, 1, 1, 0;\n}\n"
    : "+f"(d[0]), "+f"(d[1]), "+f"(d[2]), "+f"(d[3]), "+f"(d[4]), "+f"(d[5]), "+f"(d[6]), "+f"(d[7]), "+f"(d[8]), "+f"(d[9]), "+f"(d[10]), "+f"(d[11]), "+f"(d[12]), "+f"(d[13]), "+f"(d[14]), "+f"(d[15]), "+f"(d[16]), "+f"(d[17]), "+f"(d[18]), "+f"(d[19]), "+f"(d[20]), "+f"(d[21]), "+f"(d[22]), "+f"(d[23]), "+f"(d[24]), "+f"(d[25]), "+f"(d[26]), "+f"(d[27]), "+f"(d[28]), "+f"(d[29]), "+f"(d[30]), "+f"(d[31]), "+f"(d[32]), "+f"(d[33]), "+f"(d[34]), "+f"(d[35]), "+f"(d[36]), "+f"(d[37]), "+f"(d[38]), "+f"(d[39]), "+f"(d[40]), "+f"(d[41]), "+f"(d[42]), "+f"(d[43]), "+f"(d[44]), "+f"(d[45]), "+f"(d[46]), "+f"(d[47]), "+f"(d[48]), "+f"(d[49]), "+f"(d[50]), "+f"(d[51]), "+f"(d[52]), "+f"(d[53]), "+f"(d[54]), "+f"(d[55]), "+f"(d[56]), "+f"(d[57]), "+f"(d[58]), "+f"(d[59]), "+f"(d[60]), "+f"(d[61]), "+f"(d[62]), "+f"(d[63]), "+f"(d[64]), "+f"(d[65]), "+f"(d[66]), "+f"(d[67])
    : "l"(desca), "l"(descb), "r"(scale_d));
}
__device__ __forceinline__ void wgmma_qk_n64(float (&d)[32], uint32_t a0, uint32_t a1, uint32_t a2, uint32_t a3, uint64_t descb) {
  asm volatile("{\n.reg .pred p;\nsetp.ne.b32 p, 0, 0;\n"
    "wgmma.mma_async.sync.aligned.m64n64k16.f32.bf16.bf16 "
    "{%0, %1, %2, %3, %4, %5, %6, %7, %8, %9, %10, %11, %12, %13, %14, %15, %16, %17, %18, %19, %20, %21, %22, %23, %24, %25, %26, %27, %28, %29, %30, %31}, "
    "{%32, %33, %34, %35}, %36, p, 1, 1, 0;\n}\n"
    : "=f"(d[0]), "=f"(d[1]), "=f"(d[2]), "=f"(d[3]), "=f"(d[4]), "=f"(d[5]), "=f"(d[6]), "=f"(d[7]), "=f"(d[8]), "=f"(d[9]), "=f"(d[10]), "=f"(d[11]), "=f"(d[12]), "=f"(d[13]), "=f"(d[14]), "=f"(d[15]), "=f"(d[16]), "=f"(d[17]), "=f"(d[18]), "=f"(d[19]), "=f"(d[20]), "=f"(d[21]), "=f"(d[22]), "=f"(d[23]), "=f"(d[24]), "=f"(d[25]), "=f"(d[26]), "=f"(d[27]), "=f"(d[28]), "=f"(d[29]), "=f"(d[30]), "=f"(d[31])
    : "r"(a0), "r"(a1), "r"(a2), "r"(a3), "l"(descb));
}
__device__ __forceinline__ void wgmma_pv_n24(float (&d)[12], uint32_t a0, uint32_t a1, uint32_t a2, uint32_t a3, uint64_t descb) {
  asm volatile("{\n.reg .pred p;\nsetp.eq.b32 p, 0, 0;\n"
    "wgmma.mma_async.sync.aligned.m64n24k16.f32.bf16.bf16 "
    "{%0, %1, %2, %3, %4, %5, %6, %7, %8, %9, %10, %11}, "
    "{%12, %13, %14, %15}, %16, p, 1, 1, 1;\n}\n"
    : "+f"(d[0]), "+f"(d[1]), "+f"(d[2]), "+f"(d[3]), "+f"(d[4]), "+f"(d[5]), "+f"(d[6]), "+f"(d[7]), "+f"(d[8]), "+f"(d[9]), "+f"(d[10]), "+f"(d[11])
    : "r"(a0), "r"(a1), "r"(a2), "r"(a3), "l"(descb));
}
__device__ __forceinline__ void wgmma_k3_n64(float (&d)[32], uint64_t desca, uint64_t descb, int scale_d) {
  asm volatile("{\n.reg .pred p;\nsetp.ne.b32 p, %34, 0;\n"
    "wgmma.mma_async.sync.aligned.m64n64k16.f32.bf16.bf16 "
    "{%0, %1, %2, %3, %4, %5, %6, %7, %8, %9, %10, %11, %12, %13, %14, %15, %16, %17, %18, %19, %20, %21, %22, %23, %24, %25, %26, %27, %28, %29, %30, %31}, "
    "%32, %33, p, 1, 1, 0, 1;\n}\n"
    : "+f"(d[0]), "+f"(d[1]), "+f"(d[2]), "+f"(d[3]), "+f"(d[4]), "+f"(d[5]), "+f"(d[6]), "+f"(d[7]), "+f"(d[8]), "+f"(d[9]), "+f"(d[10]), "+f"(d[11]), "+f"(d[12]), "+f"(d[13]), "+f"(d[14]), "+f"(d[15]), "+f"(d[16]), "+f"(d[17]), "+f"(d[18]), "+f"(d[19]), "+f"(d[20]), "+f"(d[21]), "+f"(d[22]), "+f"(d[23]), "+f"(d[24]), "+f"(d[25]), "+f"(d[26]), "+f"(d[27]), "+f"(d[28]), "+f"(d[29]), "+f"(d[30]), "+f"(d[31])
    : "l"(desca), "l"(descb), "r"(scale_d));
}

constexpr int K1_XS = 17408;
constexpr int K1_WS = 24576;
constexpr int K1_ST = K1_XS + K1_WS;
constexpr int K1_NST = 5;
constexpr int K1_OFF_MISC = K1_NST * K1_ST;
constexpr int K1_SMEM = K1_OFF_MISC + 2048 + 1024;
constexpr float QSCALE = 0.25f * 1.4426950408889634f;

__global__ void __launch_bounds__(544, 1)
k1_qkv(const __grid_constant__ CUtensorMap tm_x, const __grid_constant__ CUtensorMap tm_w, const __nv_bfloat16* __restrict__ x) {
    extern __shared__ uint8_t smem_raw[];
    const uint32_t sraw = smem_u32(smem_raw);
    const uint32_t sb = (sraw + 1023) & ~1023u;
    uint8_t* sp = smem_raw + (sb - sraw);
    const uint32_t full = sb + K1_OFF_MISC;
    const uint32_t empty = full + 64;
    float* s_mr = (float*)(sp + K1_OFF_MISC + 256);

    const int tid = threadIdx.x, warp = tid >> 5, lane = tid & 31;
    const int mt = blockIdx.x >> 3, nt = blockIdx.x & 7;
    if (tid == 0) TSTAMP0(0, 0);
    pdl_launch();
    if (tid == 512) {
        for (int i = 0; i < K1_NST; i++) { mbar_init(full + 8 * i, 1); mbar_init(empty + 8 * i, 3); }
        fence_barrier_init();
        for (int kb = 0; kb < K1_NST; kb++) {
            mbar_expect_tx(full + 8 * kb, 16384 + K1_WS);
            tma_load_2d(sb + kb * K1_ST, &tm_x, kb * 64, mt * 128, full + 8 * kb);
            tma_load_3d(sb + kb * K1_ST + K1_XS, &tm_w, nt * 64, kb * 64, 0, full + 8 * kb);
        }
    }
    if (tid < K1_NST * 64) {
        *(uint4*)(sp + (tid >> 6) * K1_ST + 16384 + (tid & 63) * 16) =
            make_uint4(0x3F803F80u, 0x3F803F80u, 0x3F803F80u, 0x3F803F80u);
    }
    fence_proxy_async();
    __syncthreads();

    if (warp == 16) {
        if (lane == 0) {
            for (int kb = K1_NST; kb < 8; kb++) {
                const int s = kb % K1_NST;
                mbar_wait(empty + 8 * s, 0);
                mbar_expect_tx(full + 8 * s, 16384 + K1_WS);
                tma_load_2d(sb + s * K1_ST, &tm_x, kb * 64, mt * 128, full + 8 * s);
                tma_load_3d(sb + s * K1_ST + K1_XS, &tm_w, nt * 64, kb * 64, 0, full + 8 * s);
            }
        }
        __syncwarp();
        if (lane < FF / 128) g_act[blockIdx.x * (FF / 128) + lane] = 0xFFFFFFFFu;
        for (int i = lane; i < 128; i += 32) g_part[blockIdx.x * 128 + i] = make_float4(0.f, 0.f, 0.f, 0.f);
        if (blockIdx.x == 1) { g_cand[lane] = make_uint4(0, 0, 0, 0); g_cand[lane + 32] = make_uint4(0, 0, 0, 0); g_hflag[lane] = 0; g_sflag[lane] = 0; }
        if (blockIdx.x == 2) for (int i = lane; i < 1024; i += 32) g_oflag[i] = 0;
    } else if (warp >= 12) {
        const int r = tid - 384;
        const unsigned int tag = *(volatile unsigned int*)&g_epoch + 1u;
        {
            const int row = mt * 128 + nt * 16 + (r >> 3);
            const uint4* xp = (const uint4*)(x + (size_t)row * DM) + (r & 7);
            uint4 v[8];
#pragma unroll
            for (int i = 0; i < 8; i++) v[i] = __ldg(xp + i * 8);
            float s1 = 0.f;
#pragma unroll
            for (int i = 0; i < 8; i++)
                s1 += ((bf_lo(v[i].x) + bf_hi(v[i].x)) + (bf_lo(v[i].y) + bf_hi(v[i].y))) + ((bf_lo(v[i].z) + bf_hi(v[i].z)) + (bf_lo(v[i].w) + bf_hi(v[i].w)));
#pragma unroll
            for (int o = 1; o < 8; o <<= 1) s1 += __shfl_xor_sync(0xffffffffu, s1, o);
            const float mean = s1 * (1.f / DM);
            float q0 = 0.f, q1 = 0.f;
#pragma unroll
            for (int i = 0; i < 8; i++) {
                const uint32_t w[4] = {v[i].x, v[i].y, v[i].z, v[i].w};
#pragma unroll
                for (int j = 0; j < 4; j++) {
                    const float a = bf_lo(w[j]) - mean, b = bf_hi(w[j]) - mean;
                    q0 = fmaf(a, a, q0); q1 = fmaf(b, b, q1);
                }
            }
            float q = q0 + q1;
#pragma unroll
            for (int o = 1; o < 8; o <<= 1) q += __shfl_xor_sync(0xffffffffu, q, o);
            const float den = rbf(sqrtf(rbf(rbf(q * (1.f / DM)) + 1e-5f)));
            if ((r & 7) == 0)
                asm volatile("st.relaxed.gpu.global.v4.f32 [%0], {%1, %2, %3, %4};" ::"l"(g_ln1 + row), "f"(rbf(mean)), "f"(1.f / den),
                             "f"(__uint_as_float(tag)), "f"(0.f) : "memory");
        }
        if (r == 0) TSTAMP0(0, 6);
        {
            float4 v;
            int spins = 0;
            do {
                asm volatile("ld.relaxed.gpu.global.v4.f32 {%0, %1, %2, %3}, [%4];" : "=f"(v.x), "=f"(v.y), "=f"(v.z), "=f"(v.w) : "l"(g_ln1 + mt * 128 + r) : "memory");
            } while (__float_as_uint(v.z) != tag && ++spins < (1 << 22));
            s_mr[(r >> 1) * 4 + (r & 1)] = v.x;
            s_mr[(r >> 1) * 4 + 2 + (r & 1)] = v.y;
        }
        if (r == 0) TSTAMP0(0, 7);
        named_arrive(1, 512);
    } else {
        const int part = warp >> 2, hw = warp & 3;
        float acc[68];
#pragma unroll
        for (int i = 0; i < 68; i++) acc[i] = 0.f;
        fence_regs(acc);
#pragma unroll 1
        for (int kb = 0; kb < 8; kb++) {
            const int s = kb % K1_NST;
            mbar_wait(full + 8 * s, (kb / K1_NST) & 1);
            const uint64_t da = make_desc(sb + s * K1_ST + K1_XS + part * 8192, 1024, 1024, 1);
            const uint64_t db = make_desc(sb + s * K1_ST, 16, 1024, 1);
            wg_fence();
#pragma unroll
            for (int k = 0; k < 4; k++) wgmma_k1_n136(acc, da + k * 128, db + k * 2, (kb | k) != 0);
            wg_commit();
            if (kb > 0 && kb <= 8 - K1_NST) {
                wg_wait<1>();
                if ((tid & 127) == 0) mbar_arrive(empty + 8 * (kb - 1));
            }
        }
        wg_wait<0>();
        fence_regs(acc);
        if (tid == 0) TSTAMP0(0, 1);
        named_sync(1, 512);
        if (tid == 0) TSTAMP0(0, 2);

        const int t = lane & 3;
        const float cs0 = acc[64], cs1 = acc[66];
        const float sc = (part == 0) ? QSCALE : 1.f;
        const uint32_t stg = sb + (hw >> 1) * K1_ST + K1_XS + part * 8192 + (hw & 1) * 4096;
        const uint32_t st_addr = stg + ((lane >> 3) & 1) * 2048 + ((lane >> 4) * 8 + (lane & 7)) * 16;
#pragma unroll
        for (int j = 0; j < 16; j += 2) {
            uint32_t rr[4];
#pragma unroll
            for (int u = 0; u < 2; u++) {
                const int jj = j + u;
                const float4 mr = *(const float4*)(s_mr + (4 * jj + t) * 4);
                const float2 m2 = make_float2(mr.x, mr.y);
                const float ra = mr.z * sc, rb = mr.w * sc;
                rr[2 * u] = pack_bf16((acc[4 * jj] - m2.x * cs0) * ra, (acc[4 * jj + 1] - m2.y * cs0) * rb);
                rr[2 * u + 1] = pack_bf16((acc[4 * jj + 2] - m2.x * cs1) * ra, (acc[4 * jj + 3] - m2.y * cs1) * rb);
            }
            stmatrix_x4_trans(st_addr + j * 128, rr[0], rr[1], rr[2], rr[3]);
        }
        fence_proxy_async();
        __syncwarp();
        if (tid == 0) TSTAMP0(0, 4);
        const int head = nt * 4 + hw;
        if (lane == 0) {
            uint8_t* dst;
            uint32_t hstride;
            if (part == 0) { dst = g_q + (size_t)head * 65536 + mt * 2048; hstride = 32768; }
            else { dst = g_kv + (size_t)head * 131072 + (mt >> 1) * 16384 + (part - 1) * 8192 + (mt & 1) * 2048; hstride = 4096; }
            bulk_s2g(dst, stg, 2048);
            bulk_s2g(dst + hstride, stg + 2048, 2048);
            asm volatile("cp.async.bulk.commit_group;" ::: "memory");
        }
        float nmax = 0.f;
#pragma unroll
        for (int i = 0; i < 4; i++) {
            const int tok = lane + 32 * i;
            const uint4 a = *(const uint4*)(sp + (stg - sb) + tok * 16);
            const uint4 b = *(const uint4*)(sp + (stg - sb) + 2048 + tok * 16);
            uint32_t n0 = fma_bf16x2(a.x, a.x, 0u), n1 = fma_bf16x2(b.x, b.x, 0u);
            n0 = fma_bf16x2(a.y, a.y, n0); n1 = fma_bf16x2(b.y, b.y, n1);
            n0 = fma_bf16x2(a.z, a.z, n0); n1 = fma_bf16x2(b.z, b.z, n1);
            n0 = fma_bf16x2(a.w, a.w, n0); n1 = fma_bf16x2(b.w, b.w, n1);
            const float n2 = ((bf_lo(n0) + bf_hi(n0)) + (bf_lo(n1) + bf_hi(n1))) * 1.125f;
            nmax = (n2 > nmax || n2 != n2) ? n2 : nmax;
        }
#pragma unroll
        for (int o = 16; o > 0; o >>= 1) {
            const float v = __shfl_xor_sync(0xffffffffu, nmax, o);
            nmax = (v > nmax || v != v) ? v : nmax;
        }
        if (tid == 0) TSTAMP0(0, 5);
        if (lane == 0) {
            g_norm[(head * 16 + mt) * 3 + part] = nmax;
            asm volatile("cp.async.bulk.wait_group.read 0;" ::: "memory");
            if (tid == 0) TSTAMP0(0, 3);
        }
    }
}

#define POLL_NS 50
constexpr int KF_CH_G = 16384, KF_CH_S = 20480, KF_NCH = 8;
constexpr int KF_OFF_WO = KF_NCH * KF_CH_S;
constexpr int KF_OFF_MISC = KF_OFF_WO + 65536;
constexpr int KF_SMEM = KF_OFF_MISC + 1280 + 1024;

__device__ __forceinline__ uint32_t exp2_pair_poly(float s0, float s1) {
    const float KB = 65536.0f + 127.0f;
    const float t0 = s0 + KB, t1 = s1 + KB;
    const uint32_t w = __byte_perm(__float_as_uint(t0), __float_as_uint(t1), 0x5410);
    uint32_t z;
    asm("lop3.b32 %0, %1, %2, %3, 0xEA;" : "=r"(z) : "r"(w), "r"(0x007F007Fu), "r"(0x3F803F80u));
    uint32_t p = fma_bf16x2(0x3eab3eabu, z, 0xbc73bc73u);
    p = fma_bf16x2(p, z, 0x3f2f3f2fu);
    return p + w - z;
}
#define EMASK 0x5757u
constexpr uint32_t KF_EMASK = EMASK;
template <int LO, int HI>
__device__ __forceinline__ void softmax_part(const float (&s)[32], uint32_t (&p)[16]) {
#pragma unroll
    for (int i = LO; i < HI; i++) {
        if ((KF_EMASK >> i) & 1) p[i] = exp2_pair_poly(s[2 * i], s[2 * i + 1]);
        else p[i] = pack_bf16(ex2f(s[2 * i]), ex2f(s[2 * i + 1]));
    }
}
#define KF_PV(P, OFF)                                                                              \
    _Pragma("unroll") for (int kk = 0; kk < 4; kk++)                                               \
        wgmma_pv_n24(o, P[4 * kk], P[4 * kk + 1], P[4 * kk + 2], P[4 * kk + 3], dv + ((OFF) + kk * 16));

__device__ __forceinline__ uint32_t make_key(float r_bf16, int token) {
    const uint32_t u = __float_as_uint(r_bf16) >> 16;
    const uint32_t o = (u & 0x8000u) ? (~u & 0xFFFFu) : (u | 0x8000u);
    return (o << 16) | (uint32_t)(0xFFFF - token);
}
__device__ __forceinline__ float key_value(uint32_t k) {
    const uint32_t o = k >> 16;
    const uint32_t u = (o & 0x8000u) ? (o & 0x7FFFu) : (~o & 0xFFFFu);
    return __uint_as_float(u << 16);
}
__device__ __forceinline__ int key_token(uint32_t k) { return 0xFFFF - (int)(k & 0xFFFFu); }
__device__ __forceinline__ void warp_top2(uint32_t a, uint32_t b, uint32_t& k1, uint32_t& k2) {
    k1 = __reduce_max_sync(0xffffffffu, a > b ? a : b);
    const uint32_t a2 = (a == k1) ? 0u : a, b2 = (b == k1) ? 0u : b;
    k2 = __reduce_max_sync(0xffffffffu, a2 > b2 ? a2 : b2);
}
__device__ __forceinline__ unsigned int ld_acquire(const unsigned int* p) {
    unsigned int v; asm volatile("ld.acquire.gpu.global.u32 %0, [%1];" : "=r"(v) : "l"(p) : "memory"); return v;
}
__device__ __forceinline__ void red_release_add(unsigned int* p) {
    asm volatile("red.release.gpu.global.add.u32 [%0], 1;" ::"l"(p) : "memory");
}

__global__ void __launch_bounds__(512, 1)
kf_main(const __grid_constant__ CUtensorMap tm_o, const __grid_constant__ CUtensorMap tm_wo,
        const __grid_constant__ CUtensorMap tm_g, const __grid_constant__ CUtensorMap tm_u, const __grid_constant__ CUtensorMap tm_d,
        const __nv_bfloat16* __restrict__ x, const __nv_bfloat16* __restrict__ wo, const __nv_bfloat16* __restrict__ w_r,
        const __nv_bfloat16* __restrict__ w_gate, const __nv_bfloat16* __restrict__ w_up, const __nv_bfloat16* __restrict__ w_down,
        __nv_bfloat16* __restrict__ out) {
    extern __shared__ uint8_t smem_raw[];
    const uint32_t sraw = smem_u32(smem_raw);
    const uint32_t sb = (sraw + 1023) & ~1023u;
    uint8_t* sp = smem_raw + (sb - sraw);
    const uint32_t kvbar = sb + KF_OFF_MISC;
    const uint32_t wbar = kvbar + 64;
    const uint32_t obar = wbar + 64;
    const uint32_t gbar = obar + 64;
    const uint32_t dbar = gbar + 8;
    unsigned int* s_cnt = (unsigned int*)(sp + KF_OFF_MISC + 208);
    volatile unsigned int* s_order = (volatile unsigned int*)(sp + KF_OFF_MISC + 1056);
    uint32_t* s_key = (uint32_t*)(sp + KF_OFF_MISC + 256);
    float* s_gu = (float*)(sp + KF_OFF_MISC + 768);
    uint4* s_sel = (uint4*)(sp + KF_OFF_MISC + 1024);
    const int tid = threadIdx.x;
    const int head = blockIdx.x >> 2, quarter = blockIdx.x & 3;
    const int mt = blockIdx.x >> 2, nt = blockIdx.x & 3;
    if (tid == 0) TSTAMP0(1, 0);
    if (tid == 0) {
        for (int c = 0; c < 26; c++) mbar_init(kvbar + 8 * c, 1);
        for (int c = 0; c < 4; c++) s_cnt[c] = 0;
        fence_barrier_init();
        for (int kb = 0; kb < 4; kb++) {
            mbar_expect_tx(wbar + 8 * kb, 16384);
            tma_load_3d(sb + KF_OFF_WO + kb * 16384, &tm_wo, 0, kb * 64, nt * 2, wbar + 8 * kb);
        }
    }
    if (tid == 32) {
        prefetch_l2((const uint8_t*)wo + blockIdx.x * 4096, 4096);
        prefetch_l2((const uint8_t*)w_gate + blockIdx.x * 14336, 14336);
        prefetch_l2((const uint8_t*)w_up + blockIdx.x * 14336, 14336);
        prefetch_l2((const uint8_t*)w_down + blockIdx.x * 14336, 14336);
    }
    for (int i = tid; i < KF_NCH * 256; i += 512)
        *(uint4*)(sp + (i >> 8) * KF_CH_S + 16384 + (i & 255) * 16) =
            make_uint4(0x3F803F80u, 0x3F803F80u, 0x3F803F80u, 0x3F803F80u);
    fence_proxy_async();
    __syncthreads();
    pdl_wait();
    if (tid == 0) TSTAMP0(1, 1);
    const uint8_t* kvsrc = g_kv + (size_t)head * (KF_NCH * KF_CH_G);
    if (tid == 32) {
        mbar_expect_tx(kvbar, KF_CH_G);
        bulk_g2s(sb, kvsrc, KF_CH_G, kvbar);
    }
    const int wg = tid >> 7, warp = (tid >> 5) & 3, lane = tid & 31, g = lane >> 2, t = lane & 3;
    if (tid < 32) {
        const int m16 = lane & 15;
        float kn = g_norm[(head * 16 + m16) * 3 + 1];
        float vn = g_norm[(head * 16 + m16) * 3 + 2];
        float qn = g_norm[(head * 16 + quarter * 4 + (lane & 3)) * 3 + 0];
        const bool bad = !(kn < 1e30f) || !(vn < 1e30f) || !(qn < 1e30f);
#pragma unroll
        for (int o = 8; o > 0; o >>= 1) {
            kn = fmaxf(kn, __shfl_xor_sync(0xffffffffu, kn, o));
            qn = fmaxf(qn, __shfl_xor_sync(0xffffffffu, qn, o));
        }
        const bool ok = __all_sync(0xffffffffu, !bad && (qn * kn <= 3500.f));
        if (lane == 0) s_cnt[4] = ok ? 1u : 0u;
    }
    uint32_t qn2[2][4];
#pragma unroll
    for (int ps = 0; ps < 2; ps++) {
        const uint8_t* qb = g_q + (size_t)head * 65536 + (quarter * 512 + ps * 256 + wg * 64 + warp * 16 + g) * 16 + t * 4;
        qn2[ps][0] = *(const uint32_t*)(qb);
        qn2[ps][1] = *(const uint32_t*)(qb + 128);
        qn2[ps][2] = *(const uint32_t*)(qb + 32768);
        qn2[ps][3] = *(const uint32_t*)(qb + 32768 + 128);
    }

    __syncthreads();
    const bool fast = __all_sync(0xffffffffu, s_cnt[4] != 0u);
    if (tid == 32) {
        for (int c = 1; c < KF_NCH; c++) {
            mbar_expect_tx(kvbar + 8 * c, KF_CH_G);
            bulk_g2s(sb + c * KF_CH_S, kvsrc + c * KF_CH_G, KF_CH_G, kvbar + 8 * c);
        }
    }
    if (tid == 0) TSTAMP0(1, 8);
    const uint64_t dk0 = make_desc(sb, 4096, 128, 0);
    const uint64_t dv0 = make_desc(sb + 8192, 128, 4096, 0);

#pragma unroll 1
    for (int pass = 0; pass < 2; pass++) {
        const int row0 = quarter * 512 + pass * 256 + wg * 64 + warp * 16 + g;
        uint32_t qa[4];
#pragma unroll
        for (int i = 0; i < 4; i++) qa[i] = pass ? qn2[1][i] : qn2[0][i];
        float o[12];
#pragma unroll
        for (int i = 0; i < 12; i++) o[i] = 0.f;
        fence_regs(o);
#define KF_RELEASE_CHUNK(c)                                                                          \
        if (pass == 1 && (c) >= 1 && (c) <= 4) {                                                     \
            named_sync(4 + wg, 128);            \
            if ((tid & 127) == 0 && atomicAdd(&s_cnt[(c) - 1], 1u) == 3u) {                          \
                mbar_expect_tx(wbar + 8 * (3 + (c)), 16384);                                         \
                tma_load_3d(sb + ((c) - 1) * KF_CH_S, &tm_wo, 0, (3 + (c)) * 64, nt * 2, wbar + 8 * (3 + (c))); \
            }                                                                                        \
        }
        if (fast) {
#pragma unroll 1
            for (int c = 0; c < KF_NCH; c++) {
                const uint64_t dk = dk0 + (uint64_t)(c * (KF_CH_S >> 4));
                const uint64_t dv = dv0 + (uint64_t)(c * (KF_CH_S >> 4));
                float s0[32], s1[32], s2[32], s3[32];
                uint32_t p0[16], p1[16], p2[16], p3[16];
                mbar_wait(kvbar + 8 * c, 0);
                wg_wait<1>();
                wg_fence();
                wgmma_qk_n64(s0, qa[0], qa[1], qa[2], qa[3], dk);
                wg_commit();
                wg_wait<1>();
                KF_RELEASE_CHUNK(c);
                wg_fence();
                wgmma_qk_n64(s1, qa[0], qa[1], qa[2], qa[3], dk + 64);
                wg_commit();
                wg_wait<1>();
                fence_regs(s0);
                softmax_part<0, 16>(s0, p0);
                wg_fence();
                KF_PV(p0, 0);
                wg_commit();
                wg_wait<1>();
                fence_regs(s1);
                softmax_part<0, 8>(s1, p1);
                wg_wait<0>();
                wg_fence();
                wgmma_qk_n64(s2, qa[0], qa[1], qa[2], qa[3], dk + 128);
                wg_commit();
                softmax_part<8, 16>(s1, p1);
                wg_fence();
                KF_PV(p1, 64);
                wg_commit();
                wg_wait<1>();
                fence_regs(s2);
                softmax_part<0, 8>(s2, p2);
                wg_wait<0>();
                wg_fence();
                wgmma_qk_n64(s3, qa[0], qa[1], qa[2], qa[3], dk + 192);
                wg_commit();
                softmax_part<8, 16>(s2, p2);
                wg_fence();
                KF_PV(p2, 128);
                wg_commit();
                wg_wait<1>();
                fence_regs(s3);
                softmax_part<0, 16>(s3, p3);
                wg_fence();
                KF_PV(p3, 192);
                wg_commit();
            }
            wg_wait<0>();
            fence_regs(o);
        } else {
            float m0 = -INFINITY, m1 = -INFINITY;
#pragma unroll 1
            for (int b = 0; b < 32; b++) {
                const int c = b >> 2;
                const uint64_t dk = dk0 + (uint64_t)(c * (KF_CH_S >> 4) + (b & 3) * 64);
                const uint64_t dv = dv0 + (uint64_t)(c * (KF_CH_S >> 4) + (b & 3) * 64);
                float s[32];
                uint32_t p[16];
                mbar_wait(kvbar + 8 * c, 0);
                wg_fence();
                wgmma_qk_n64(s, qa[0], qa[1], qa[2], qa[3], dk);
                wg_commit();
                if ((b & 3) == 0) { KF_RELEASE_CHUNK(c); }
                wg_wait<0>();
                fence_regs(s);
                float x0 = s[0], x1 = s[2];
#pragma unroll
                for (int j = 0; j < 8; j++) {
                    x0 = fmaxf(x0, fmaxf(s[4 * j], s[4 * j + 1]));
                    x1 = fmaxf(x1, fmaxf(s[4 * j + 2], s[4 * j + 3]));
                }
                x0 = fmaxf(x0, __shfl_xor_sync(0xffffffffu, x0, 1));
                x0 = fmaxf(x0, __shfl_xor_sync(0xffffffffu, x0, 2));
                x1 = fmaxf(x1, __shfl_xor_sync(0xffffffffu, x1, 1));
                x1 = fmaxf(x1, __shfl_xor_sync(0xffffffffu, x1, 2));
                const float n0 = fmaxf(m0, x0), n1 = fmaxf(m1, x1);
                const float c0 = ex2f(m0 - n0), c1 = ex2f(m1 - n1);
                m0 = n0; m1 = n1;
#pragma unroll
                for (int j = 0; j < 3; j++) {
                    o[4 * j] *= c0; o[4 * j + 1] *= c0; o[4 * j + 2] *= c1; o[4 * j + 3] *= c1;
                }
#pragma unroll
                for (int j = 0; j < 8; j++) {
                    p[2 * j] = pack_bf16(ex2f(s[4 * j] - n0), ex2f(s[4 * j + 1] - n0));
                    p[2 * j + 1] = pack_bf16(ex2f(s[4 * j + 2] - n1), ex2f(s[4 * j + 3] - n1));
                }
                fence_regs(o);
                wg_fence();
                KF_PV(p, 0);
                wg_commit();
                wg_wait<0>();
                fence_regs(o);
            }
        }
        const float inv0 = 1.f / o[8], inv1 = 1.f / o[10];
        {
            uint32_t v0 = pack_bf16(o[0] * inv0, o[1] * inv0), v1 = pack_bf16(o[4] * inv0, o[5] * inv0);
            uint32_t v2 = pack_bf16(o[2] * inv1, o[3] * inv1), v3 = pack_bf16(o[6] * inv1, o[7] * inv1);
            const bool o1 = t & 1, o2 = t & 2;
            uint32_t s0 = o1 ? v0 : v1, s1 = o1 ? v2 : v3;
            s0 = __shfl_xor_sync(0xffffffffu, s0, 1); s1 = __shfl_xor_sync(0xffffffffu, s1, 1);
            uint32_t a0 = o1 ? s0 : v0, a1 = o1 ? v1 : s0, b0 = o1 ? s1 : v2, b1 = o1 ? v3 : s1;
            uint32_t x0 = o2 ? a0 : b0, x1 = o2 ? a1 : b1;
            x0 = __shfl_xor_sync(0xffffffffu, x0, 2); x1 = __shfl_xor_sync(0xffffffffu, x1, 2);
            uint4 r;
            r.x = o2 ? x0 : a0; r.y = o2 ? x1 : a1; r.z = o2 ? b0 : x0; r.w = o2 ? b1 : x1;
            *(uint4*)(g_o + (size_t)(row0 + (t >> 1) * 8) * DM + head * 16 + (t & 1) * 8) = r;
        }
        if (tid == 0) TSTAMP0(1, 4 + pass);
    }
    if ((tid >> 5) != 10) named_arrive(1, 512);
    named_sync(4 + wg, 128);
    if ((tid & 127) == 0) {
        asm volatile("fence.acq_rel.gpu;" ::: "memory");
        asm volatile("red.relaxed.gpu.global.add.u32 [%0], 1;" ::"l"(&g_oflag[(quarter * 8 + 4 + wg) * 32 + (head >> 2) * 4]) : "memory");
        asm volatile("red.relaxed.gpu.global.add.u32 [%0], 1;" ::"l"(&g_oflag[(quarter * 8 + wg) * 32 + (head >> 2) * 4]) : "memory");
    }
    if (tid == 0) TSTAMP0(1, 3);

    if (wg < 2) {
        const int wi = warp;
        const int r0 = mt * 64 + wi * 16 + g;
        const int cb = nt * 128 + wg * 64;
        uint32_t xr[16], wr[8];
#pragma unroll
        for (int j = 0; j < 8; j++) {
            xr[2 * j] = __ldg((const uint32_t*)(x + (size_t)r0 * DM + cb + 8 * j + 2 * t));
            xr[2 * j + 1] = __ldg((const uint32_t*)(x + (size_t)(r0 + 8) * DM + cb + 8 * j + 2 * t));
            wr[j] = __ldg((const uint32_t*)(w_r + cb + 8 * j + 2 * t));
        }
        float wsum = 0.f;
        {
            const uint4 a = __ldg((const uint4*)(w_r + lane * 16)), b = __ldg((const uint4*)(w_r + lane * 16 + 8));
            const uint32_t w[8] = {a.x, a.y, a.z, a.w, b.x, b.y, b.z, b.w};
#pragma unroll
            for (int i = 0; i < 8; i++) wsum += bf_lo(w[i]) + bf_hi(w[i]);
#pragma unroll
            for (int o = 16; o > 0; o >>= 1) wsum += __shfl_xor_sync(0xffffffffu, wsum, o);
        }
        float acc[32];
#pragma unroll
        for (int i = 0; i < 32; i++) acc[i] = 0.f;
        fence_regs(acc);
#pragma unroll 1
        for (int i = 0; i < 8; i++) {
            mbar_wait(obar + 8 * i, 0);
            const int kb = __shfl_sync(0xffffffffu, (int)s_order[i], 0);
            mbar_wait(wbar + 8 * kb, 0);
            const uint32_t wa = (kb < 4) ? (KF_OFF_WO + kb * 16384) : ((kb - 4) * KF_CH_S);
            const uint64_t da = make_desc(sb + (4 + (kb >> 1)) * KF_CH_S + (kb & 1) * 8192, 16, 1024, 1);
            const uint64_t db = make_desc(sb + wa + wg * 8192, 1024, 1024, 1);
            wg_fence();
#pragma unroll
            for (int k = 0; k < 4; k++) wgmma_k3_n64(acc, da + k * 2, db + k * 128, (i | k) != 0);
            wg_commit();
        }
        wg_wait<0>();
        fence_regs(acc);
        if (tid == 0) TSTAMP0(2, 2);
        float hv[32];
        uint32_t hp[16];
        float s0 = 0.f, s1 = 0.f, d0 = 0.f, d1 = 0.f;
#pragma unroll
        for (int j = 0; j < 8; j++) {
            const uint32_t a01 = pack_bf16(acc[4 * j], acc[4 * j + 1]), a23 = pack_bf16(acc[4 * j + 2], acc[4 * j + 3]);
            hp[2 * j] = pack_bf16(bf_lo(xr[2 * j]) + bf_lo(a01), bf_hi(xr[2 * j]) + bf_hi(a01));
            hp[2 * j + 1] = pack_bf16(bf_lo(xr[2 * j + 1]) + bf_lo(a23), bf_hi(xr[2 * j + 1]) + bf_hi(a23));
            hv[4 * j] = bf_lo(hp[2 * j]); hv[4 * j + 1] = bf_hi(hp[2 * j]);
            hv[4 * j + 2] = bf_lo(hp[2 * j + 1]); hv[4 * j + 3] = bf_hi(hp[2 * j + 1]);
            const float wl = bf_lo(wr[j]), wh = bf_hi(wr[j]);
            s0 += hv[4 * j] + hv[4 * j + 1];
            s1 += hv[4 * j + 2] + hv[4 * j + 3];
            d0 = fmaf(hv[4 * j], wl, fmaf(hv[4 * j + 1], wh, d0));
            d1 = fmaf(hv[4 * j + 2], wl, fmaf(hv[4 * j + 3], wh, d1));
        }
        float mu0 = s0 * (1.f / 16), mu1 = s1 * (1.f / 16);
        float q0 = 0.f, q1 = 0.f;
#pragma unroll
        for (int j = 0; j < 8; j++) {
            float a = hv[4 * j] - mu0, b = hv[4 * j + 1] - mu0, c = hv[4 * j + 2] - mu1, d = hv[4 * j + 3] - mu1;
            q0 = fmaf(a, a, fmaf(b, b, q0));
            q1 = fmaf(c, c, fmaf(d, d, q1));
        }
#pragma unroll
        for (int o = 1; o < 4; o <<= 1) {
            const float m0 = __shfl_xor_sync(0xffffffffu, mu0, o), m1 = __shfl_xor_sync(0xffffffffu, mu1, o);
            const float e0 = __shfl_xor_sync(0xffffffffu, q0, o), e1 = __shfl_xor_sync(0xffffffffu, q1, o);
            d0 += __shfl_xor_sync(0xffffffffu, d0, o);
            d1 += __shfl_xor_sync(0xffffffffu, d1, o);
            const float f0 = mu0 - m0, f1 = mu1 - m1;
            q0 = q0 + e0 + f0 * f0 * (8.f * o);
            q1 = q1 + e1 + f1 * f1 * (8.f * o);
            mu0 = 0.5f * (mu0 + m0); mu1 = 0.5f * (mu1 + m1);
        }
        float4* part = g_part + (size_t)mt * 512 + wi * 16 + g;
        if (t < 2) {
            float4* dst = part + (nt * 2 + wg) * 64 + t * 8;
            const float a = t ? mu1 : mu0, b = t ? q1 : q0, c = t ? d1 : d0;
            asm volatile("st.relaxed.gpu.global.v4.f32 [%0], {%1, %2, %3, %4};" ::"l"(dst), "f"(a), "f"(b), "f"(c), "f"(1.0f) : "memory");
        }
        if (tid == 0) TSTAMP0(2, 5);
        const uint32_t stg_off = KF_OFF_WO + (wi >> 1) * 16384 + wg * 8192 + (wi & 1) * 4096;
        const uint32_t stg_o = sb + stg_off, stg_h = stg_o + 2048;
        const int srow = (lane & 7) + ((lane >> 3) & 1) * 8;
        const int sj = lane >> 4;
        named_sync(4 + wg, 128);
#pragma unroll
        for (int j = 0; j < 8; j += 2) {
            const uint32_t off = srow * 128 + (((j + sj) ^ (srow & 7)) << 4);
            stmatrix_x4(stg_h + off, hp[2 * j], hp[2 * j + 1], hp[2 * j + 2], hp[2 * j + 3]);
        }
        __syncwarp();
#pragma unroll
        for (int i = 0; i < 4; i++) {
            const int row = i * 4 + (lane >> 3), ch = lane & 7;
            const uint4 vh = *(const uint4*)(sp + stg_off + 2048 + row * 128 + ((ch ^ (row & 7)) << 4));
            *(uint4*)(g_h + (size_t)(mt * 64 + wi * 16 + row) * DM + cb + ch * 8) = vh;
        }
        named_arrive(8, 288);
        if (tid == 0) TSTAMP0(2, 6);
        float mean[2], den[2], rr[2];
        {
            float4 v[4];
            int spins = 0;
            while (true) {
#pragma unroll
                for (int i = 0; i < 4; i++) {
                    const float4* p = part + (t + (i & 1) * 4) * 64 + (i >> 1) * 8;
                    asm volatile("ld.relaxed.gpu.global.v4.f32 {%0, %1, %2, %3}, [%4];" : "=f"(v[i].x), "=f"(v[i].y), "=f"(v[i].z), "=f"(v[i].w) : "l"(p) : "memory");
                }
                const bool ok = (v[0].w != 0.f) && (v[1].w != 0.f) && (v[2].w != 0.f) && (v[3].w != 0.f);
                if (__all_sync(0xffffffffu, ok) || ++spins > (1 << 22)) break;
            }
#pragma unroll
            for (int u = 0; u < 2; u++) {
                float mu = v[2 * u].x + v[2 * u + 1].x, m2 = v[2 * u].y + v[2 * u + 1].y, hw = v[2 * u].z + v[2 * u + 1].z;
#pragma unroll
                for (int o = 1; o < 4; o <<= 1) {
                    mu += __shfl_xor_sync(0xffffffffu, mu, o);
                    m2 += __shfl_xor_sync(0xffffffffu, m2, o);
                    hw += __shfl_xor_sync(0xffffffffu, hw, o);
                }
                mu *= 0.125f;
                const float da = v[2 * u].x - mu, db = v[2 * u + 1].x - mu;
                float dd = 64.f * (da * da + db * db);
#pragma unroll
                for (int o = 1; o < 4; o <<= 1) dd += __shfl_xor_sync(0xffffffffu, dd, o);
                m2 += dd;
                mean[u] = rbf(mu);
                den[u] = rbf(sqrtf(rbf(rbf(m2 * (1.f / DM)) + 1e-5f)));
                rr[u] = rbf((hw - mean[u] * wsum) / den[u]);
            }
        }
        if (tid == 0) TSTAMP0(2, 3);
        named_arrive(3, 512);
        if (nt == 0 && wg == 0) {
            float2* s_st = (float2*)(sp + KF_OFF_WO + 49152);
            if (t == 0) {
                s_key[wi * 16 + g] = make_key(rr[0], r0);
                s_key[wi * 16 + g + 8] = make_key(rr[1], r0 + 8);
                s_st[wi * 16 + g] = make_float2(mean[0], den[0]);
                s_st[wi * 16 + g + 8] = make_float2(mean[1], den[1]);
            }
            named_sync(4, 128);
            if (warp == 0) {
                uint32_t k1, k2;
                warp_top2(s_key[lane], s_key[lane + 32], k1, k2);
                if (lane < 2) {
                    const uint32_t k = lane ? k2 : k1;
                    const float2 st = s_st[key_token(k) & 63];
                    asm volatile("st.relaxed.gpu.global.v4.u32 [%0], {%1, %2, %3, %4};" ::"l"(g_cand + mt * 2 + lane), "r"(k),
                                 "r"(1u), "r"(__float_as_uint(st.x)), "r"(__float_as_uint(st.y)) : "memory");
                }
            }
        }
        const float i0 = 1.f / den[0], i1 = 1.f / den[1];
#pragma unroll
        for (int j = 0; j < 8; j += 2) {
            uint32_t ro[4];
#pragma unroll
            for (int u = 0; u < 2; u++) {
                const int jj = j + u;
                const float a = hv[4 * jj], b = hv[4 * jj + 1], c = hv[4 * jj + 2], d = hv[4 * jj + 3];
                const uint32_t u01 = pack_bf16(a - mean[0], b - mean[0]), u23 = pack_bf16(c - mean[1], d - mean[1]);
                const uint32_t n01 = pack_bf16(bf_lo(u01) * i0, bf_hi(u01) * i0), n23 = pack_bf16(bf_lo(u23) * i1, bf_hi(u23) * i1);
                ro[2 * u] = pack_bf16(a + bf_lo(n01), b + bf_hi(n01));
                ro[2 * u + 1] = pack_bf16(c + bf_lo(n23), d + bf_hi(n23));
            }
            const uint32_t off = srow * 128 + (((j + sj) ^ (srow & 7)) << 4);
            stmatrix_x4(stg_o + off, ro[0], ro[1], ro[2], ro[3]);
        }
        __syncwarp();
#pragma unroll
        for (int i = 0; i < 4; i++) {
            const int row = i * 4 + (lane >> 3), ch = lane & 7;
            const uint4 vo = *(const uint4*)(sp + stg_off + row * 128 + ((ch ^ (row & 7)) << 4));
            *(uint4*)(out + (size_t)(mt * 64 + wi * 16 + row) * DM + cb + ch * 8) = vo;
        }
        named_sync(4 + wg, 128);
        if ((tid & 127) == 0) red_release_add(&g_sflag[mt]);
        if (tid == 0) TSTAMP0(2, 4);
    } else {
        const bool worker = blockIdx.x < FF / 16;
        const bool downer = blockIdx.x >= 64;
        const int mtid = tid - 256, mwarp = mtid >> 5;
        const int c0 = (blockIdx.x - 64) * 8;
        float* s_x = (float*)(sp + KF_OFF_WO + 49152 + 8192);
        float* s_red = (float*)(sp + KF_OFF_WO + 49152 + 8192 + 4096);
        if (mwarp == 2) {
            named_sync(1, 512);
            uint32_t done = 0;
            int n = 0, spins = 0;
            while (done != 0xFFu && ++spins < (1 << 22)) {
                const bool rdy = lane < 8 && ld_acquire(&g_oflag[mt * 32 + lane * 4]) >= 4u;
                uint32_t todo = __ballot_sync(0xffffffffu, rdy) & ~done;
                done |= todo;
                if (todo && lane == 0) {
                    asm volatile("fence.proxy.async.global;" ::: "memory");
                    while (todo) {
                        const int kb = __ffs(todo) - 1;
                        todo &= todo - 1;
                        s_order[n] = kb;
                        mbar_expect_tx(obar + 8 * n, 8192);
                        tma_load_3d(sb + (4 + (kb >> 1)) * KF_CH_S + (kb & 1) * 8192, &tm_o, 0, mt * 64, kb, obar + 8 * n);
                        n++;
                    }
                }
                n = __shfl_sync(0xffffffffu, n, 0);
                if (done != 0xFFu) __nanosleep(POLL_NS);
            }
            if (lane == 0) TSTAMP0(2, 1);
            if (lane == 0 && worker) {
                mbar_expect_tx(gbar, 32768);
                for (int i = 0; i < 4; i++) {
                    tma_load_2d(sb + i * KF_CH_S + 16384, &tm_g, blockIdx.x * 16, i * 128, gbar);
                    tma_load_2d(sb + (4 + i) * KF_CH_S + 16384, &tm_u, blockIdx.x * 16, i * 128, gbar);
                }
            }
        }
        if (mwarp == 1) {
            named_sync(8, 288);
            if (lane == 0) {
                red_release_add(&g_hflag[mt]);
                if (downer) {
                    mbar_expect_tx(dbar, 7 * 4096);
                    for (int i = 0; i < 7; i++) tma_load_2d(sb + (4 + (i >> 2)) * KF_CH_S + (i & 3) * 4096, &tm_d, c0, i * 256, dbar);
                }
            }
            __syncwarp();
        }
        if (mtid == 0) TSTAMP0(3, 0);
        named_sync(3, 512);
        if (mwarp == 0) {
            uint4 ca, cb4;
            int spins = 0;
            while (true) {
                asm volatile("ld.relaxed.gpu.global.v4.u32 {%0, %1, %2, %3}, [%4];" : "=r"(ca.x), "=r"(ca.y), "=r"(ca.z), "=r"(ca.w) : "l"(g_cand + 2 * lane) : "memory");
                asm volatile("ld.relaxed.gpu.global.v4.u32 {%0, %1, %2, %3}, [%4];" : "=r"(cb4.x), "=r"(cb4.y), "=r"(cb4.z), "=r"(cb4.w) : "l"(g_cand + 2 * lane + 1) : "memory");
                const unsigned int hf = ld_acquire(&g_hflag[lane]);
                const bool ok = ca.y != 0 && cb4.y != 0 && hf >= 4u;
                if (__all_sync(0xffffffffu, ok) || ++spins > (1 << 22)) break;
            }
            uint32_t k1, k2;
            warp_top2(ca.x, cb4.x, k1, k2);
            if (ca.x == k1) s_sel[0] = ca;
            if (cb4.x == k1) s_sel[0] = cb4;
            if (ca.x == k2) s_sel[1] = ca;
            if (cb4.x == k2) s_sel[1] = cb4;
        }
        named_sync(2, 256);
        if (mtid == 0) TSTAMP0(3, 1);
        int idx[2];
        float mean[2], inv[2], rv[2];
#pragma unroll
        for (int u = 0; u < 2; u++) {
            const uint4 c = s_sel[u];
            idx[u] = key_token(c.x);
            rv[u] = key_value(c.x);
            mean[u] = __uint_as_float(c.z);
            inv[u] = 1.f / __uint_as_float(c.w);
        }
        float hfin = 0.f;
        if (downer && mtid < 16) hfin = __bfloat162float(__ldcg((const __nv_bfloat16*)(g_h + (size_t)((mtid >> 3) ? idx[1] : idx[0]) * DM + c0 + (mtid & 7))));
        if (worker) {
            {
                const uint32_t h0 = __ldcg((const uint32_t*)(g_h + (size_t)idx[0] * DM + 2 * mtid));
                const uint32_t h1 = __ldcg((const uint32_t*)(g_h + (size_t)idx[1] * DM + 2 * mtid));
                const uint32_t u0 = pack_bf16(bf_lo(h0) - mean[0], bf_hi(h0) - mean[0]), u1 = pack_bf16(bf_lo(h1) - mean[1], bf_hi(h1) - mean[1]);
                const uint32_t n0 = pack_bf16(bf_lo(u0) * inv[0], bf_hi(u0) * inv[0]), n1 = pack_bf16(bf_lo(u1) * inv[1], bf_hi(u1) * inv[1]);
                *(float4*)(s_x + 4 * mtid) = make_float4(bf_lo(n0), bf_lo(n1), bf_hi(n0), bf_hi(n1));
            }
            if (mtid == 0) TSTAMP0(3, 5);
            mbar_wait(gbar, 0);
            named_sync(2, 256);
            if (mtid == 0) TSTAMP0(3, 6);
            float acc[8];
#pragma unroll
            for (int i = 0; i < 8; i++) acc[i] = 0.f;
            const uint8_t* wbase = sp + (mwarp >> 2) * (4 * KF_CH_S) + 16384 + lane * 32 + (mwarp & 3) * 8;
#pragma unroll
            for (int k = 0; k < 16; k++) {
                const uint2 w = *(const uint2*)(wbase + (k >> 2) * KF_CH_S + (k & 3) * 1024);
                const float2 xx = *(const float2*)(s_x + 2 * (lane + 32 * k));
                const float x0 = xx.x, x1 = xx.y;
                const float w0 = bf_lo(w.x), w1 = bf_hi(w.x), w2 = bf_lo(w.y), w3 = bf_hi(w.y);
                acc[0] = fmaf(x0, w0, acc[0]); acc[1] = fmaf(x0, w1, acc[1]); acc[2] = fmaf(x0, w2, acc[2]); acc[3] = fmaf(x0, w3, acc[3]);
                acc[4] = fmaf(x1, w0, acc[4]); acc[5] = fmaf(x1, w1, acc[5]); acc[6] = fmaf(x1, w2, acc[6]); acc[7] = fmaf(x1, w3, acc[7]);
            }
#define KF_STEP(O, N)                                                          \
            {                                                                  \
                const bool up = (lane & (O)) != 0;                             \
                _Pragma("unroll") for (int i = 0; i < (N); i++) {              \
                    const float send = up ? acc[i] : acc[i + (N)];             \
                    const float keep = up ? acc[i + (N)] : acc[i];             \
                    acc[i] = keep + __shfl_xor_sync(0xffffffffu, send, (O));   \
                }                                                              \
            }
            KF_STEP(16, 4) KF_STEP(8, 2) KF_STEP(4, 1)
            acc[0] += __shfl_xor_sync(0xffffffffu, acc[0], 2);
            acc[0] += __shfl_xor_sync(0xffffffffu, acc[0], 1);
            if ((lane & 3) == 0) {
                const int v = ((lane & 16) ? 4 : 0) + ((lane & 8) ? 2 : 0) + ((lane & 4) ? 1 : 0);
                s_gu[(v >> 2) * 32 + mwarp * 4 + (v & 3)] = acc[0];
            }
            named_sync(2, 256);
            if (mtid < 16) {
                uint32_t a2 = 0;
#pragma unroll
                for (int u = 0; u < 2; u++) {
                    const float gb = rbf(s_gu[u * 32 + mtid]);
                    const float sg = rbf(gb / (1.f + __expf(-gb)));
                    float a = sg * rbf(s_gu[u * 32 + 16 + mtid]);
                    uint32_t ab = (uint32_t)__bfloat16_as_ushort(__float2bfloat16_rn(a));
                    if (ab == 0xFFFFu) ab = 0x7FFFu;
                    a2 |= ab << (16 * u);
                }
                asm volatile("st.relaxed.gpu.global.u32 [%0], %1;" ::"l"(g_act + blockIdx.x * 16 + mtid), "r"(a2) : "memory");
            }
            if (mtid == 0) TSTAMP0(3, 2);
        }
        if (downer) {
            uint32_t av[7];
            {
                int spins = 0;
                while (true) {
                    bool ok = true;
#pragma unroll
                    for (int j = 0; j < 7; j++) {
                        asm volatile("ld.relaxed.gpu.global.u32 %0, [%1];" : "=r"(av[j]) : "l"(g_act + mtid + 256 * j) : "memory");
                        ok = ok && ((av[j] & 0xFFFFu) != 0xFFFFu) && ((av[j] >> 16) != 0xFFFFu);
                    }
                    if (mtid < 2) ok = ok && (ld_acquire(&g_sflag[(mtid ? idx[1] : idx[0]) >> 6]) >= 8u);
                    if (__all_sync(0xffffffffu, ok) || ++spins > (1 << 20)) break;
                    __nanosleep(20);
                }
            }
            if (mtid == 0) TSTAMP0(3, 3);
            mbar_wait(dbar, 0);
            float acc[16];
#pragma unroll
            for (int i = 0; i < 16; i++) acc[i] = 0.f;
#pragma unroll
            for (int j = 0; j < 7; j++) {
                const uint4 w = *(const uint4*)(sp + (4 + (j >> 2)) * KF_CH_S + (j & 3) * 4096 + mtid * 16);
                const float a0 = bf_lo(av[j]), a1 = bf_hi(av[j]);
                const uint32_t ww[4] = {w.x, w.y, w.z, w.w};
#pragma unroll
                for (int q = 0; q < 4; q++) {
                    const float wl = bf_lo(ww[q]), wh = bf_hi(ww[q]);
                    acc[2 * q] = fmaf(a0, wl, acc[2 * q]); acc[2 * q + 1] = fmaf(a0, wh, acc[2 * q + 1]);
                    acc[8 + 2 * q] = fmaf(a1, wl, acc[8 + 2 * q]); acc[8 + 2 * q + 1] = fmaf(a1, wh, acc[8 + 2 * q + 1]);
                }
            }
            KF_STEP(16, 8) KF_STEP(8, 4) KF_STEP(4, 2) KF_STEP(2, 1)
            acc[0] += __shfl_xor_sync(0xffffffffu, acc[0], 1);
            if ((lane & 1) == 0) {
                const int v = ((lane & 16) ? 8 : 0) + ((lane & 8) ? 4 : 0) + ((lane & 4) ? 2 : 0) + ((lane & 2) ? 1 : 0);
                s_red[mwarp * 16 + v] = acc[0];
            }
            named_sync(2, 256);
            if (mtid < 16) {
                const int u = mtid >> 3;
                float y = 0.f;
#pragma unroll
                for (int w = 0; w < 8; w++) y += s_red[w * 16 + mtid];
                const float sig = rbf(1.f / (1.f + __expf(-(u ? rv[1] : rv[0]))));
                const float xn = rbf(rbf(hfin - (u ? mean[1] : mean[0])) * (u ? inv[1] : inv[0]));
                const float ov = hfin + rbf(xn + rbf(rbf(y) * sig));
                out[(size_t)(u ? idx[1] : idx[0]) * DM + c0 + (mtid & 7)] = __float2bfloat16_rn(ov);
            }
            if (blockIdx.x == gridDim.x - 1 && mtid == 0) g_epoch = g_epoch + 1u;
            if (mtid == 0) TSTAMP0(3, 4);
        }
    }
}

typedef CUresult (*PFN_encodeTiled)(CUtensorMap*, CUtensorMapDataType, cuuint32_t, void*, const cuuint64_t*, const cuuint64_t*,
                                    const cuuint32_t*, const cuuint32_t*, CUtensorMapInterleave, CUtensorMapSwizzle,
                                    CUtensorMapL2promotion, CUtensorMapFloatOOBfill);

void make_map(PFN_encodeTiled enc, CUtensorMap* m, const void* ptr, uint64_t cols, uint64_t rows, uint32_t bcols, uint32_t brows) {
    cuuint64_t dims[2] = {cols, rows};
    cuuint64_t strides[1] = {cols * 2};
    cuuint32_t box[2] = {bcols, brows};
    cuuint32_t es[2] = {1, 1};
    enc(m, CU_TENSOR_MAP_DATA_TYPE_BFLOAT16, 2, const_cast<void*>(ptr), dims, strides, box, es, CU_TENSOR_MAP_INTERLEAVE_NONE,
        CU_TENSOR_MAP_SWIZZLE_128B, CU_TENSOR_MAP_L2_PROMOTION_L2_256B, CU_TENSOR_MAP_FLOAT_OOB_FILL_NONE);
}

void make_map3(PFN_encodeTiled enc, CUtensorMap* m, const void* ptr, uint64_t d0, uint64_t rows, uint64_t d2, uint64_t row_stride_bytes,
               uint64_t d2_stride_bytes, uint32_t b0, uint32_t b1, uint32_t b2) {
    cuuint64_t dims[3] = {d0, rows, d2};
    cuuint64_t strides[2] = {row_stride_bytes, d2_stride_bytes};
    cuuint32_t box[3] = {b0, b1, b2};
    cuuint32_t es[3] = {1, 1, 1};
    enc(m, CU_TENSOR_MAP_DATA_TYPE_BFLOAT16, 3, const_cast<void*>(ptr), dims, strides, box, es, CU_TENSOR_MAP_INTERLEAVE_NONE,
        CU_TENSOR_MAP_SWIZZLE_128B, CU_TENSOR_MAP_L2_PROMOTION_L2_256B, CU_TENSOR_MAP_FLOAT_OOB_FILL_NONE);
}

void make_map_plain(PFN_encodeTiled enc, CUtensorMap* m, const void* ptr, uint64_t cols, uint64_t rows, uint32_t bcols, uint32_t brows) {
    cuuint64_t dims[2] = {cols, rows};
    cuuint64_t strides[1] = {cols * 2};
    cuuint32_t box[2] = {bcols, brows};
    cuuint32_t es[2] = {1, 1};
    enc(m, CU_TENSOR_MAP_DATA_TYPE_BFLOAT16, 2, const_cast<void*>(ptr), dims, strides, box, es, CU_TENSOR_MAP_INTERLEAVE_NONE,
        CU_TENSOR_MAP_SWIZZLE_NONE, CU_TENSOR_MAP_L2_PROMOTION_NONE, CU_TENSOR_MAP_FLOAT_OOB_FILL_NONE);
}

template <typename... KArgs, typename... Args>
void launch(void (*kern)(KArgs...), int grid, int block, int smem, bool pdl, Args... args) {
    cudaLaunchConfig_t cfg = {};
    cfg.gridDim = dim3(grid);
    cfg.blockDim = dim3(block);
    cfg.dynamicSmemBytes = smem;
    cfg.stream = cudaStreamPerThread;
    cudaLaunchAttribute at[1];
    at[0].id = cudaLaunchAttributeProgrammaticStreamSerialization;
    at[0].val.programmaticStreamSerializationAllowed = 1;
    cfg.attrs = at;
    cfg.numAttrs = pdl ? 1 : 0;
    cudaLaunchKernelEx(&cfg, kern, KArgs(args)...);
}

}

extern "C" void kernel_launch(void* const* d_in, const int* in_sizes, int n_in, void* d_out, int out_size) {
    const __nv_bfloat16* x = (const __nv_bfloat16*)d_in[0];
    const __nv_bfloat16* wqkv = (const __nv_bfloat16*)d_in[1];
    const __nv_bfloat16* wo = (const __nv_bfloat16*)d_in[2];
    const __nv_bfloat16* w_r = (const __nv_bfloat16*)d_in[4];
    const __nv_bfloat16* w_gate = (const __nv_bfloat16*)d_in[5];
    const __nv_bfloat16* w_up = (const __nv_bfloat16*)d_in[6];
    const __nv_bfloat16* w_down = (const __nv_bfloat16*)d_in[7];
    __nv_bfloat16* out = (__nv_bfloat16*)d_out;

    static PFN_encodeTiled enc = nullptr;
    static void* g_o_ptr = nullptr;
    if (!enc) {
        cudaDriverEntryPointQueryResult qres;
        void* fn = nullptr;
        cudaGetDriverEntryPoint("cuTensorMapEncodeTiled", &fn, cudaEnableDefault, &qres);
        enc = (PFN_encodeTiled)fn;
        cudaGetSymbolAddress(&g_o_ptr, g_o);
        cudaFuncSetAttribute(k1_qkv, cudaFuncAttributeMaxDynamicSharedMemorySize, K1_SMEM);
        cudaFuncSetAttribute(kf_main, cudaFuncAttributeMaxDynamicSharedMemorySize, KF_SMEM);
    }
    CUtensorMap tm_x, tm_w, tm_o, tm_wo, tm_g, tm_u, tm_d;
    make_map_plain(enc, &tm_d, w_down, DM, FF, 8, 256);
    make_map_plain(enc, &tm_g, w_gate, FF, DM, 16, 128);
    make_map_plain(enc, &tm_u, w_up, FF, DM, 16, 128);
    make_map(enc, &tm_x, x, DM, SEQ, 64, 128);
    make_map3(enc, &tm_w, wqkv, DM, DM, 3, 3 * DM * 2, DM * 2, 64, 64, 3);
    make_map3(enc, &tm_o, g_o_ptr, 64, SEQ, 8, DM * 2, 128, 64, 64, 1);
    make_map3(enc, &tm_wo, wo, 64, DM, 8, DM * 2, 128, 64, 64, 2);

    const bool pdl = true;
    launch(k1_qkv, 128, 544, K1_SMEM, false, tm_x, tm_w, x);
    launch(kf_main, 128, 512, KF_SMEM, pdl, tm_o, tm_wo, tm_g, tm_u, tm_d, x, wo, w_r, w_gate, w_up, w_down, out);
}
```

```cpp
#include <cuda_runtime.h>
#include <cuda_bf16.h>
#include <cuda.h>
#include <stdint.h>

namespace {

constexpr int SEQ = 2048, DM = 512, NH = 32, FF = 1792;

__device__ __align__(1024) uint8_t g_q[NH * 2 * SEQ * 16];
__device__ __align__(1024) uint8_t g_kv[NH * 8 * 16384];
__device__ float g_norm[16 * NH * 3];
__device__ __align__(1024) __nv_bfloat16 g_o[SEQ * DM];
__device__ __align__(1024) __nv_bfloat16 g_h[SEQ * DM];
__device__ __align__(16) uint4 g_cand[64];
__device__ unsigned int g_oflag[32 * 32];
__device__ unsigned int g_hflag[32];
__device__ unsigned int g_sflag[32];
__device__ __align__(8) uint2 g_act[FF];
__device__ unsigned int g_kvflag[8 * 16 * 8];
__device__ unsigned int g_epoch;
__device__ __align__(16) float4 g_ln1[SEQ];
__device__ __align__(16) float4 g_part[32 * 8 * 64];

#define TSTAMP(K, I)
#define TSTAMP0(K, I)
__device__ __forceinline__ uint32_t smem_u32(const void* p) { return (uint32_t)__cvta_generic_to_shared(p); }
__device__ __forceinline__ void wg_fence() { asm volatile("wgmma.fence.sync.aligned;" ::: "memory"); }
__device__ __forceinline__ void wg_commit() { asm volatile("wgmma.commit_group.sync.aligned;" ::: "memory"); }
template <int N> __device__ __forceinline__ void wg_wait() { asm volatile("wgmma.wait_group.sync.aligned %0;" ::"n"(N) : "memory"); }
template <int N> __device__ __forceinline__ void fence_regs(float (&r)[N]) {
#pragma unroll
    for (int i = 0; i < N; i++) asm volatile("" : "+f"(r[i])::"memory");
}
__device__ __forceinline__ uint64_t make_desc(uint32_t addr, uint32_t lbo, uint32_t sbo, uint32_t swz) {
    uint64_t d = 0;
    d |= (uint64_t)((addr & 0x3FFFF) >> 4);
    d |= (uint64_t)((lbo & 0x3FFFF) >> 4) << 16;
    d |= (uint64_t)((sbo & 0x3FFFF) >> 4) << 32;
    d |= (uint64_t)swz << 62;
    return d;
}
__device__ __forceinline__ void mbar_init(uint32_t bar, uint32_t cnt) {
    asm volatile("mbarrier.init.shared::cta.b64 [%0], %1;" ::"r"(bar), "r"(cnt) : "memory");
}
__device__ __forceinline__ void mbar_expect_tx(uint32_t bar, uint32_t bytes) {
    asm volatile("mbarrier.arrive.expect_tx.shared::cta.b64 _, [%0], %1;" ::"r"(bar), "r"(bytes) : "memory");
}
__device__ __forceinline__ void mbar_arrive(uint32_t bar) {
    asm volatile("mbarrier.arrive.shared::cta.b64 _, [%0];" ::"r"(bar) : "memory");
}
__device__ __forceinline__ void mbar_wait(uint32_t bar, uint32_t parity) {
    asm volatile(
        "{\n.reg .pred p;\nWAIT_%=:\n"
        "mbarrier.try_wait.parity.shared::cta.b64 p, [%0], %1;\n"
        "@p bra DONE_%=;\nbra WAIT_%=;\nDONE_%=:\n}\n" ::"r"(bar), "r"(parity) : "memory");
}
__device__ __forceinline__ void bulk_g2s(uint32_t dst, const void* src, uint32_t bytes, uint32_t bar) {
    asm volatile("cp.async.bulk.shared::cluster.global.mbarrier::complete_tx::bytes [%0], [%1], %2, [%3];" ::"r"(dst),
                 "l"(src), "r"(bytes), "r"(bar) : "memory");
}
__device__ __forceinline__ void bulk_s2g(void* dst, uint32_t src, uint32_t bytes) {
    asm volatile("cp.async.bulk.global.shared::cta.bulk_group [%0], [%1], %2;" ::"l"(dst), "r"(src), "r"(bytes) : "memory");
}
__device__ __forceinline__ void tma_load_2d(uint32_t dst, const CUtensorMap* tm, int c0, int c1, uint32_t bar) {
    asm volatile("cp.async.bulk.tensor.2d.shared::cluster.global.mbarrier::complete_tx::bytes [%0], [%1, {%3, %4}], [%2];" ::"r"(dst),
                 "l"(tm), "r"(bar), "r"(c0), "r"(c1) : "memory");
}
__device__ __forceinline__ void tma_load_3d(uint32_t dst, const CUtensorMap* tm, int c0, int c1, int c2, uint32_t bar) {
    asm volatile("cp.async.bulk.tensor.3d.shared::cluster.global.mbarrier::complete_tx::bytes [%0], [%1, {%3, %4, %5}], [%2];" ::"r"(dst),
                 "l"(tm), "r"(bar), "r"(c0), "r"(c1), "r"(c2) : "memory");
}
__device__ __forceinline__ void tma_load_2d_mc(uint32_t dst, const CUtensorMap* tm, int c0, int c1, uint32_t bar, uint16_t mask) {
    asm volatile("cp.async.bulk.tensor.2d.shared::cluster.global.mbarrier::complete_tx::bytes.multicast::cluster [%0], [%1, {%3, %4}], [%2], %5;" ::"r"(dst),
                 "l"(tm), "r"(bar), "r"(c0), "r"(c1), "h"(mask) : "memory");
}
__device__ __forceinline__ void mbar_arrive_cluster(uint32_t bar, uint32_t cta) {
    asm volatile("{\n.reg .b32 ra;\nmapa.shared::cluster.u32 ra, %0, %1;\nmbarrier.arrive.release.cluster.shared::cluster.b64 _, [ra];\n}" ::"r"(bar), "r"(cta) : "memory");
}
__device__ __forceinline__ void cluster_sync() {
    asm volatile("barrier.cluster.arrive.release.aligned;\nbarrier.cluster.wait.acquire.aligned;" ::: "memory");
}
__device__ __forceinline__ void prefetch_l2(const void* p, uint32_t bytes) {
    asm volatile("cp.async.bulk.prefetch.L2.global [%0], %1;" ::"l"(p), "r"(bytes) : "memory");
}
__device__ __forceinline__ void fence_proxy_async() { asm volatile("fence.proxy.async.shared::cta;" ::: "memory"); }
__device__ __forceinline__ void fence_barrier_init() { asm volatile("fence.mbarrier_init.release.cluster;" ::: "memory"); }
__device__ __forceinline__ void pdl_launch() { asm volatile("griddepcontrol.launch_dependents;" ::: "memory"); }
__device__ __forceinline__ void pdl_wait() { asm volatile("griddepcontrol.wait;" ::: "memory"); }
__device__ __forceinline__ void named_sync(int id, int n) { asm volatile("bar.sync %0, %1;" ::"r"(id), "r"(n) : "memory"); }
__device__ __forceinline__ void named_arrive(int id, int n) { asm volatile("bar.arrive %0, %1;" ::"r"(id), "r"(n) : "memory"); }

__device__ __forceinline__ float ex2f(float x) { float y; asm("ex2.approx.ftz.f32 %0, %1;" : "=f"(y) : "f"(x)); return y; }
__device__ __forceinline__ uint32_t pack_bf16(float lo, float hi) {
    uint32_t r; asm("cvt.rn.bf16x2.f32 %0, %1, %2;" : "=r"(r) : "f"(hi), "f"(lo)); return r;
}
__device__ __forceinline__ float bf_lo(uint32_t v) { return __uint_as_float(v << 16); }
__device__ __forceinline__ float bf_hi(uint32_t v) { return __uint_as_float(v & 0xFFFF0000u); }
__device__ __forceinline__ float rbf(float x) { return __bfloat162float(__float2bfloat16_rn(x)); }
__device__ __forceinline__ uint32_t fma_bf16x2(uint32_t a, uint32_t b, uint32_t c) {
    uint32_t r; asm("fma.rn.bf16x2 %0, %1, %2, %3;" : "=r"(r) : "r"(a), "r"(b), "r"(c)); return r;
}
__device__ __forceinline__ void stmatrix_x4(uint32_t addr, uint32_t r0, uint32_t r1, uint32_t r2, uint32_t r3) {
    asm volatile("stmatrix.sync.aligned.m8n8.x4.shared.b16 [%0], {%1, %2, %3, %4};" ::"r"(addr), "r"(r0), "r"(r1), "r"(r2), "r"(r3) : "memory");
}
__device__ __forceinline__ void stmatrix_x4_trans(uint32_t addr, uint32_t r0, uint32_t r1, uint32_t r2, uint32_t r3) {
    asm volatile("stmatrix.sync.aligned.m8n8.x4.trans.shared.b16 [%0], {%1, %2, %3, %4};" ::"r"(addr), "r"(r0), "r"(r1), "r"(r2), "r"(r3) : "memory");
}

__device__ __forceinline__ void wgmma_k1_n136(float (&d)[68], uint64_t desca, uint64_t descb, int scale_d) {
  asm volatile("{\n.reg .pred p;\nsetp.ne.b32 p, %70, 0;\n"
    "wgmma.mma_async.sync.aligned.m64n136k16.f32.bf16.bf16 "
    "{%0, %1, %2, %3, %4, %5, %6, %7, %8, %9, %10, %11, %12, %13, %14, %15, %16, %17, %18, %19, %20, %21, %22, %23, %24, %25, %26, %27, %28, %29, %30, %31, %32, %33, %34, %35, %36, %37, %38, %39, %40, %41, %42, %43, %44, %45, %46, %47, %48, %49, %50, %51, %52, %53, %54, %55, %56, %57, %58, %59, %60, %61, %62, %63, %64, %65, %66, %67}, "
    "%68, %69, p, 1, 1, 1, 0;\n}\n"
    : "+f"(d[0]), "+f"(d[1]), "+f"(d[2]), "+f"(d[3]), "+f"(d[4]), "+f"(d[5]), "+f"(d[6]), "+f"(d[7]), "+f"(d[8]), "+f"(d[9]), "+f"(d[10]), "+f"(d[11]), "+f"(d[12]), "+f"(d[13]), "+f"(d[14]), "+f"(d[15]), "+f"(d[16]), "+f"(d[17]), "+f"(d[18]), "+f"(d[19]), "+f"(d[20]), "+f"(d[21]), "+f"(d[22]), "+f"(d[23]), "+f"(d[24]), "+f"(d[25]), "+f"(d[26]), "+f"(d[27]), "+f"(d[28]), "+f"(d[29]), "+f"(d[30]), "+f"(d[31]), "+f"(d[32]), "+f"(d[33]), "+f"(d[34]), "+f"(d[35]), "+f"(d[36]), "+f"(d[37]), "+f"(d[38]), "+f"(d[39]), "+f"(d[40]), "+f"(d[41]), "+f"(d[42]), "+f"(d[43]), "+f"(d[44]), "+f"(d[45]), "+f"(d[46]), "+f"(d[47]), "+f"(d[48]), "+f"(d[49]), "+f"(d[50]), "+f"(d[51]), "+f"(d[52]), "+f"(d[53]), "+f"(d[54]), "+f"(d[55]), "+f"(d[56]), "+f"(d[57]), "+f"(d[58]), "+f"(d[59]), "+f"(d[60]), "+f"(d[61]), "+f"(d[62]), "+f"(d[63]), "+f"(d[64]), "+f"(d[65]), "+f"(d[66]), "+f"(d[67])
    : "l"(desca), "l"(descb), "r"(scale_d));
}
__device__ __forceinline__ void wgmma_qk_n64(float (&d)[32], uint32_t a0, uint32_t a1, uint32_t a2, uint32_t a3, uint64_t descb) {
  asm volatile("{\n.reg .pred p;\nsetp.ne.b32 p, 0, 0;\n"
    "wgmma.mma_async.sync.aligned.m64n64k16.f32.bf16.bf16 "
    "{%0, %1, %2, %3, %4, %5, %6, %7, %8, %9, %10, %11, %12, %13, %14, %15, %16, %17, %18, %19, %20, %21, %22, %23, %24, %25, %26, %27, %28, %29, %30, %31}, "
    "{%32, %33, %34, %35}, %36, p, 1, 1, 0;\n}\n"
    : "=f"(d[0]), "=f"(d[1]), "=f"(d[2]), "=f"(d[3]), "=f"(d[4]), "=f"(d[5]), "=f"(d[6]), "=f"(d[7]), "=f"(d[8]), "=f"(d[9]), "=f"(d[10]), "=f"(d[11]), "=f"(d[12]), "=f"(d[13]), "=f"(d[14]), "=f"(d[15]), "=f"(d[16]), "=f"(d[17]), "=f"(d[18]), "=f"(d[19]), "=f"(d[20]), "=f"(d[21]), "=f"(d[22]), "=f"(d[23]), "=f"(d[24]), "=f"(d[25]), "=f"(d[26]), "=f"(d[27]), "=f"(d[28]), "=f"(d[29]), "=f"(d[30]), "=f"(d[31])
    : "r"(a0), "r"(a1), "r"(a2), "r"(a3), "l"(descb));
}
__device__ __forceinline__ void wgmma_pv_n24(float (&d)[12], uint32_t a0, uint32_t a1, uint32_t a2, uint32_t a3, uint64_t descb) {
  asm volatile("{\n.reg .pred p;\nsetp.eq.b32 p, 0, 0;\n"
    "wgmma.mma_async.sync.aligned.m64n24k16.f32.bf16.bf16 "
    "{%0, %1, %2, %3, %4, %5, %6, %7, %8, %9, %10, %11}, "
    "{%12, %13, %14, %15}, %16, p, 1, 1, 1;\n}\n"
    : "+f"(d[0]), "+f"(d[1]), "+f"(d[2]), "+f"(d[3]), "+f"(d[4]), "+f"(d[5]), "+f"(d[6]), "+f"(d[7]), "+f"(d[8]), "+f"(d[9]), "+f"(d[10]), "+f"(d[11])
    : "r"(a0), "r"(a1), "r"(a2), "r"(a3), "l"(descb));
}
__device__ __forceinline__ void wgmma_k3_n64(float (&d)[32], uint64_t desca, uint64_t descb, int scale_d) {
  asm volatile("{\n.reg .pred p;\nsetp.ne.b32 p, %34, 0;\n"
    "wgmma.mma_async.sync.aligned.m64n64k16.f32.bf16.bf16 "
    "{%0, %1, %2, %3, %4, %5, %6, %7, %8, %9, %10, %11, %12, %13, %14, %15, %16, %17, %18, %19, %20, %21, %22, %23, %24, %25, %26, %27, %28, %29, %30, %31}, "
    "%32, %33, p, 1, 1, 0, 1;\n}\n"
    : "+f"(d[0]), "+f"(d[1]), "+f"(d[2]), "+f"(d[3]), "+f"(d[4]), "+f"(d[5]), "+f"(d[6]), "+f"(d[7]), "+f"(d[8]), "+f"(d[9]), "+f"(d[10]), "+f"(d[11]), "+f"(d[12]), "+f"(d[13]), "+f"(d[14]), "+f"(d[15]), "+f"(d[16]), "+f"(d[17]), "+f"(d[18]), "+f"(d[19]), "+f"(d[20]), "+f"(d[21]), "+f"(d[22]), "+f"(d[23]), "+f"(d[24]), "+f"(d[25]), "+f"(d[26]), "+f"(d[27]), "+f"(d[28]), "+f"(d[29]), "+f"(d[30]), "+f"(d[31])
    : "l"(desca), "l"(descb), "r"(scale_d));
}

constexpr int K1_XS = 17408;
constexpr int K1_WS = 24576;
constexpr int K1_ST = K1_XS + K1_WS;
constexpr int K1_NST = 5;
constexpr int K1_OFF_MISC = K1_NST * K1_ST;
constexpr int K1_SMEM = K1_OFF_MISC + 2048 + 1024;
constexpr int K1_OFF_BAR = 229376 + 1088;
constexpr float QSCALE = 0.25f * 1.4426950408889634f;

__device__ __forceinline__ void phase_qkv(const CUtensorMap& tm_x, const CUtensorMap& tm_w, const __nv_bfloat16* __restrict__ x,
                                          const uint32_t sb, uint8_t* sp, const unsigned int tag) {
    const uint32_t full = sb + K1_OFF_BAR;
    const uint32_t empty = full + 40;
    float* s_mr = (float*)(sp + K1_OFF_MISC + 256);

    const int tid = threadIdx.x, warp = tid >> 5, lane = tid & 31;
    const int mt = blockIdx.x >> 3, nt = blockIdx.x & 7;
    if (tid == 384) {
        for (int i = 0; i < K1_NST; i++) { mbar_init(full + 8 * i, 1); mbar_init(empty + 8 * i, 3); }
        fence_barrier_init();
        for (int kb = 0; kb < K1_NST; kb++) {
            mbar_expect_tx(full + 8 * kb, 16384 + K1_WS);
            tma_load_2d(sb + kb * K1_ST, &tm_x, kb * 64, mt * 128, full + 8 * kb);
            tma_load_3d(sb + kb * K1_ST + K1_XS, &tm_w, nt * 64, kb * 64, 0, full + 8 * kb);
        }
    }
    if (tid < K1_NST * 64) {
        *(uint4*)(sp + (tid >> 6) * K1_ST + 16384 + (tid & 63) * 16) =
            make_uint4(0x3F803F80u, 0x3F803F80u, 0x3F803F80u, 0x3F803F80u);
    }
    fence_proxy_async();
    __syncthreads();

    if (warp == 12) {
        if (lane == 0) {
            for (int kb = K1_NST; kb < 8; kb++) {
                const int s = kb % K1_NST;
                mbar_wait(empty + 8 * s, 0);
                mbar_expect_tx(full + 8 * s, 16384 + K1_WS);
                tma_load_2d(sb + s * K1_ST, &tm_x, kb * 64, mt * 128, full + 8 * s);
                tma_load_3d(sb + s * K1_ST + K1_XS, &tm_w, nt * 64, kb * 64, 0, full + 8 * s);
            }
        }
        __syncwarp();
    } else if (warp == 13 || warp == 14) {
        const int r = tid - 416;
        {
            const int row = mt * 128 + nt * 16 + (r >> 2);
            const uint4* xp = (const uint4*)(x + (size_t)row * DM) + (r & 3);
            uint4 v[16];
#pragma unroll
            for (int i = 0; i < 16; i++) v[i] = __ldg(xp + i * 4);
            float s1 = 0.f;
#pragma unroll
            for (int i = 0; i < 16; i++)
                s1 += ((bf_lo(v[i].x) + bf_hi(v[i].x)) + (bf_lo(v[i].y) + bf_hi(v[i].y))) + ((bf_lo(v[i].z) + bf_hi(v[i].z)) + (bf_lo(v[i].w) + bf_hi(v[i].w)));
#pragma unroll
            for (int o = 1; o < 4; o <<= 1) s1 += __shfl_xor_sync(0xffffffffu, s1, o);
            const float mean = s1 * (1.f / DM);
            float q0 = 0.f, q1 = 0.f;
#pragma unroll
            for (int i = 0; i < 16; i++) {
                const uint32_t w[4] = {v[i].x, v[i].y, v[i].z, v[i].w};
#pragma unroll
                for (int j = 0; j < 4; j++) {
                    const float a = bf_lo(w[j]) - mean, b = bf_hi(w[j]) - mean;
                    q0 = fmaf(a, a, q0); q1 = fmaf(b, b, q1);
                }
            }
            float q = q0 + q1;
#pragma unroll
            for (int o = 1; o < 4; o <<= 1) q += __shfl_xor_sync(0xffffffffu, q, o);
            const float den = rbf(sqrtf(rbf(rbf(q * (1.f / DM)) + 1e-5f)));
            if ((r & 3) == 0)
                asm volatile("st.relaxed.gpu.global.v4.f32 [%0], {%1, %2, %3, %4};" ::"l"(g_ln1 + row), "f"(rbf(mean)), "f"(1.f / den),
                             "f"(__uint_as_float(tag)), "f"(0.f) : "memory");
        }
        if (r == 0) TSTAMP0(0, 6);
#pragma unroll
        for (int h2 = 0; h2 < 2; h2++) {
            const int rr = r + 64 * h2;
            float4 v;
            int spins = 0;
            do {
                asm volatile("ld.relaxed.gpu.global.v4.f32 {%0, %1, %2, %3}, [%4];" : "=f"(v.x), "=f"(v.y), "=f"(v.z), "=f"(v.w) : "l"(g_ln1 + mt * 128 + rr) : "memory");
            } while (__float_as_uint(v.z) != tag && ++spins < (1 << 22));
            s_mr[(rr >> 1) * 4 + (rr & 1)] = v.x;
            s_mr[(rr >> 1) * 4 + 2 + (rr & 1)] = v.y;
        }
        if (r == 0) TSTAMP0(0, 7);
        named_arrive(11, 448);
    } else if (warp < 12) {
        const int part = warp >> 2, hw = warp & 3;
        float acc[68];
#pragma unroll
        for (int i = 0; i < 68; i++) acc[i] = 0.f;
        fence_regs(acc);
#pragma unroll 1
        for (int kb = 0; kb < 8; kb++) {
            const int s = kb % K1_NST;
            mbar_wait(full + 8 * s, (kb / K1_NST) & 1);
            const uint64_t da = make_desc(sb + s * K1_ST + K1_XS + part * 8192, 1024, 1024, 1);
            const uint64_t db = make_desc(sb + s * K1_ST, 16, 1024, 1);
            wg_fence();
#pragma unroll
            for (int k = 0; k < 4; k++) wgmma_k1_n136(acc, da + k * 128, db + k * 2, (kb | k) != 0);
            wg_commit();
            if (kb > 0 && kb <= 8 - K1_NST) {
                wg_wait<1>();
                if ((tid & 127) == 0) mbar_arrive(empty + 8 * (kb - 1));
            }
        }
        wg_wait<0>();
        fence_regs(acc);
        if (tid == 0) TSTAMP0(0, 1);
        named_sync(11, 448);
        if (tid == 0) TSTAMP0(0, 2);

        const int t = lane & 3;
        const float cs0 = acc[64], cs1 = acc[66];
        const float sc = (part == 0) ? QSCALE : 1.f;
        const uint32_t stg = sb + (hw >> 1) * K1_ST + K1_XS + part * 8192 + (hw & 1) * 4096;
        const uint32_t st_addr = stg + ((lane >> 3) & 1) * 2048 + ((lane >> 4) * 8 + (lane & 7)) * 16;
#pragma unroll
        for (int j = 0; j < 16; j += 2) {
            uint32_t rr[4];
#pragma unroll
            for (int u = 0; u < 2; u++) {
                const int jj = j + u;
                const float4 mr = *(const float4*)(s_mr + (4 * jj + t) * 4);
                const float2 m2 = make_float2(mr.x, mr.y);
                const float ra = mr.z * sc, rb = mr.w * sc;
                rr[2 * u] = pack_bf16((acc[4 * jj] - m2.x * cs0) * ra, (acc[4 * jj + 1] - m2.y * cs0) * rb);
                rr[2 * u + 1] = pack_bf16((acc[4 * jj + 2] - m2.x * cs1) * ra, (acc[4 * jj + 3] - m2.y * cs1) * rb);
            }
            stmatrix_x4_trans(st_addr + j * 128, rr[0], rr[1], rr[2], rr[3]);
        }
        fence_proxy_async();
        __syncwarp();
        if (tid == 0) TSTAMP0(0, 4);
        const int head = nt * 4 + hw;
        if (lane == 0) {
            uint8_t* dst;
            uint32_t hstride;
            if (part == 0) { dst = g_q + (size_t)head * 65536 + mt * 2048; hstride = 32768; }
            else { dst = g_kv + (size_t)head * 131072 + (mt >> 1) * 16384 + (part - 1) * 8192 + (mt & 1) * 2048; hstride = 4096; }
            bulk_s2g(dst, stg, 2048);
            bulk_s2g(dst + hstride, stg + 2048, 2048);
            asm volatile("cp.async.bulk.commit_group;" ::: "memory");
        }
        float nmax = 0.f;
#pragma unroll
        for (int i = 0; i < 4; i++) {
            const int tok = lane + 32 * i;
            const uint4 a = *(const uint4*)(sp + (stg - sb) + tok * 16);
            const uint4 b = *(const uint4*)(sp + (stg - sb) + 2048 + tok * 16);
            uint32_t n0 = fma_bf16x2(a.x, a.x, 0u), n1 = fma_bf16x2(b.x, b.x, 0u);
            n0 = fma_bf16x2(a.y, a.y, n0); n1 = fma_bf16x2(b.y, b.y, n1);
            n0 = fma_bf16x2(a.z, a.z, n0); n1 = fma_bf16x2(b.z, b.z, n1);
            n0 = fma_bf16x2(a.w, a.w, n0); n1 = fma_bf16x2(b.w, b.w, n1);
            const float n2 = ((bf_lo(n0) + bf_hi(n0)) + (bf_lo(n1) + bf_hi(n1))) * 1.125f;
            nmax = (n2 > nmax || n2 != n2) ? n2 : nmax;
        }
#pragma unroll
        for (int o = 16; o > 0; o >>= 1) {
            const float v = __shfl_xor_sync(0xffffffffu, nmax, o);
            nmax = (v > nmax || v != v) ? v : nmax;
        }
        if (tid == 0) TSTAMP0(0, 5);
        if (lane == 0) {
            g_norm[(head * 16 + mt) * 3 + part] = nmax;
            asm volatile("cp.async.bulk.wait_group.read 0;" ::: "memory");
            if (tid == 0) TSTAMP0(0, 3);
        }
        __syncwarp();
    }
    __syncthreads();
    if (warp < 12 && lane == 0) {
        asm volatile("cp.async.bulk.wait_group 0;" ::: "memory");
        asm volatile("fence.proxy.async.global;" ::: "memory");
        asm volatile("red.release.gpu.global.add.u32 [%0], 1;" ::"l"(&g_kvflag[(nt * 16 + mt) * 8]) : "memory");
        if (tid == 0) TSTAMP0(0, 8);
    }
    __syncwarp();
}

#define POLL_NS 50
constexpr int KF_CH_G = 16384, KF_CH_S = 20480, KF_NCH = 8;
constexpr int KF_OFF_WO = KF_NCH * KF_CH_S;
constexpr int KF_OFF_MISC = KF_OFF_WO + 65536;
constexpr int KF_SMEM = KF_OFF_MISC + 1280 + 1024;

__device__ __forceinline__ uint32_t exp2_pair_poly(float s0, float s1) {
    const float KB = 65536.0f + 127.0f;
    const float t0 = s0 + KB, t1 = s1 + KB;
    const uint32_t w = __byte_perm(__float_as_uint(t0), __float_as_uint(t1), 0x5410);
    uint32_t z;
    asm("lop3.b32 %0, %1, %2, %3, 0xEA;" : "=r"(z) : "r"(w), "r"(0x007F007Fu), "r"(0x3F803F80u));
    uint32_t p = fma_bf16x2(0x3eab3eabu, z, 0xbc73bc73u);
    p = fma_bf16x2(p, z, 0x3f2f3f2fu);
    return p + w - z;
}
#define EMASK 0x5757u
constexpr uint32_t KF_EMASK = EMASK;
template <int LO, int HI>
__device__ __forceinline__ void softmax_part(const float (&s)[32], uint32_t (&p)[16]) {
#pragma unroll
    for (int i = LO; i < HI; i++) {
        if ((KF_EMASK >> i) & 1) p[i] = exp2_pair_poly(s[2 * i], s[2 * i + 1]);
        else p[i] = pack_bf16(ex2f(s[2 * i]), ex2f(s[2 * i + 1]));
    }
}
#define KF_PV(P, OFF)                                                                              \
    _Pragma("unroll") for (int kk = 0; kk < 4; kk++)                                               \
        wgmma_pv_n24(o, P[4 * kk], P[4 * kk + 1], P[4 * kk + 2], P[4 * kk + 3], dv + ((OFF) + kk * 16));

__device__ __forceinline__ uint32_t make_key(float r_bf16, int token) {
    const uint32_t u = __float_as_uint(r_bf16) >> 16;
    const uint32_t o = (u & 0x8000u) ? (~u & 0xFFFFu) : (u | 0x8000u);
    return (o << 16) | (uint32_t)(0xFFFF - token);
}
__device__ __forceinline__ float key_value(uint32_t k) {
    const uint32_t o = k >> 16;
    const uint32_t u = (o & 0x8000u) ? (o & 0x7FFFu) : (~o & 0xFFFFu);
    return __uint_as_float(u << 16);
}
__device__ __forceinline__ int key_token(uint32_t k) { return 0xFFFF - (int)(k & 0xFFFFu); }
__device__ __forceinline__ void warp_top2(uint32_t a, uint32_t b, uint32_t& k1, uint32_t& k2) {
    k1 = __reduce_max_sync(0xffffffffu, a > b ? a : b);
    const uint32_t a2 = (a == k1) ? 0u : a, b2 = (b == k1) ? 0u : b;
    k2 = __reduce_max_sync(0xffffffffu, a2 > b2 ? a2 : b2);
}
__device__ __forceinline__ unsigned int ld_acquire(const unsigned int* p) {
    unsigned int v; asm volatile("ld.acquire.gpu.global.u32 %0, [%1];" : "=r"(v) : "l"(p) : "memory"); return v;
}
__device__ __forceinline__ void red_release_add(unsigned int* p) {
    asm volatile("red.release.gpu.global.add.u32 [%0], 1;" ::"l"(p) : "memory");
}

__global__ void __launch_bounds__(512, 1)
kf_main(const __grid_constant__ CUtensorMap tm_x, const __grid_constant__ CUtensorMap tm_w,
        const __grid_constant__ CUtensorMap tm_o, const __grid_constant__ CUtensorMap tm_wo,
        const __grid_constant__ CUtensorMap tm_g, const __grid_constant__ CUtensorMap tm_u, const __grid_constant__ CUtensorMap tm_d,
        const __nv_bfloat16* __restrict__ x, const __nv_bfloat16* __restrict__ wo, const __nv_bfloat16* __restrict__ w_r,
        const __nv_bfloat16* __restrict__ w_gate, const __nv_bfloat16* __restrict__ w_up, const __nv_bfloat16* __restrict__ w_down,
        __nv_bfloat16* __restrict__ out) {
    extern __shared__ uint8_t smem_raw[];
    const uint32_t sraw = smem_u32(smem_raw);
    const uint32_t sb = (sraw + 1023) & ~1023u;
    uint8_t* sp = smem_raw + (sb - sraw);
    const uint32_t kvbar = sb + KF_OFF_MISC;
    const uint32_t wbar = kvbar + 64;
    const uint32_t obar = wbar + 64;
    const uint32_t gbar = obar + 64;
    const uint32_t dbar = gbar + 8;
    unsigned int* s_cnt = (unsigned int*)(sp + KF_OFF_MISC + 208);
    volatile unsigned int* s_order = (volatile unsigned int*)(sp + KF_OFF_MISC + 1056);
    uint32_t* s_key = (uint32_t*)(sp + KF_OFF_MISC + 256);
    float* s_gu = (float*)(sp + KF_OFF_MISC + 768);
    uint4* s_sel = (uint4*)(sp + KF_OFF_MISC + 1024);
    const int tid = threadIdx.x;
    const int head = blockIdx.x >> 2, quarter = blockIdx.x & 3;
    const int mt = blockIdx.x >> 2, nt = blockIdx.x & 3;
    if (tid == 0) TSTAMP0(0, 0);
    const unsigned int tag = *(volatile unsigned int*)&g_epoch + 1u;
    if (tid == 0) {
        for (int c = 0; c < 26; c++) mbar_init(kvbar + 8 * c, 1);
        for (int c = 0; c < 4; c++) s_cnt[c] = 0;
        fence_barrier_init();
    }
    phase_qkv(tm_x, tm_w, x, sb, sp, tag);

    if (tid == 0) TSTAMP0(1, 0);
    const uint8_t* kvsrc = g_kv + (size_t)head * (KF_NCH * KF_CH_G);
    const unsigned int* kvf = g_kvflag + (head >> 2) * 16 * 8;
    if (tid >= 384) {
        for (int i = tid - 384; i < KF_NCH * 256; i += 128)
            *(uint4*)(sp + (i >> 8) * KF_CH_S + 16384 + (i & 255) * 16) =
                make_uint4(0x3F803F80u, 0x3F803F80u, 0x3F803F80u, 0x3F803F80u);
        fence_proxy_async();
        if (tid == 384) {
            for (int kb = 0; kb < 4; kb++) {
                mbar_expect_tx(wbar + 8 * kb, 16384);
                tma_load_3d(sb + KF_OFF_WO + kb * 16384, &tm_wo, 0, kb * 64, nt * 2, wbar + 8 * kb);
            }
        }
        if (tid == 416) {
            int spins = 0;
            while (((int)(ld_acquire(kvf) - 12u * tag) < 0 || (int)(ld_acquire(kvf + 8) - 12u * tag) < 0) && ++spins < (1 << 22)) __nanosleep(40);
            asm volatile("fence.proxy.async.global;" ::: "memory");
            mbar_expect_tx(kvbar, KF_CH_G);
            bulk_g2s(sb, kvsrc, KF_CH_G, kvbar);
        }
        __syncwarp();
    }
    const int wg = tid >> 7, warp = (tid >> 5) & 3, lane = tid & 31, g = lane >> 2, t = lane & 3;
    if (tid < 32) {
        const int m16 = lane & 15;
        {
            int spins = 0;
            while (!__all_sync(0xffffffffu, (int)(ld_acquire(kvf + m16 * 8) - 12u * tag) >= 0) && ++spins < (1 << 22)) __nanosleep(40);
        }
        if (tid == 0) TSTAMP0(1, 1);
        float kn = __ldcg(&g_norm[(head * 16 + m16) * 3 + 1]);
        float vn = __ldcg(&g_norm[(head * 16 + m16) * 3 + 2]);
        float qn = __ldcg(&g_norm[(head * 16 + quarter * 4 + (lane & 3)) * 3 + 0]);
        const bool bad = !(kn < 1e30f) || !(vn < 1e30f) || !(qn < 1e30f);
#pragma unroll
        for (int o = 8; o > 0; o >>= 1) {
            kn = fmaxf(kn, __shfl_xor_sync(0xffffffffu, kn, o));
            qn = fmaxf(qn, __shfl_xor_sync(0xffffffffu, qn, o));
        }
        const bool ok = __all_sync(0xffffffffu, !bad && (qn * kn <= 3500.f));
        if (lane == 0) s_cnt[4] = ok ? 1u : 0u;
    }
    __syncthreads();
    const bool fast = __all_sync(0xffffffffu, s_cnt[4] != 0u);
    uint32_t qn2[2][4];
#pragma unroll
    for (int ps = 0; ps < 2; ps++) {
        const uint8_t* qb = g_q + (size_t)head * 65536 + (quarter * 512 + ps * 256 + wg * 64 + warp * 16 + g) * 16 + t * 4;
        qn2[ps][0] = __ldcg((const uint32_t*)(qb));
        qn2[ps][1] = __ldcg((const uint32_t*)(qb + 128));
        qn2[ps][2] = __ldcg((const uint32_t*)(qb + 32768));
        qn2[ps][3] = __ldcg((const uint32_t*)(qb + 32768 + 128));
    }

    if (tid == 416) {
        asm volatile("fence.proxy.async.global;" ::: "memory");
        __nanosleep(300);
        for (int c = 1; c < KF_NCH; c++) {
            mbar_expect_tx(kvbar + 8 * c, KF_CH_G);
            bulk_g2s(sb + c * KF_CH_S, kvsrc + c * KF_CH_G, KF_CH_G, kvbar + 8 * c);
        }
        prefetch_l2((const uint8_t*)wo + blockIdx.x * 4096, 4096);
        prefetch_l2((const uint8_t*)w_gate + blockIdx.x * 14336, 14336);
        prefetch_l2((const uint8_t*)w_up + blockIdx.x * 14336, 14336);
        prefetch_l2((const uint8_t*)w_down + blockIdx.x * 14336, 14336);
    }
    if (tid == 0) TSTAMP0(1, 8);
    const uint64_t dk0 = make_desc(sb, 4096, 128, 0);
    const uint64_t dv0 = make_desc(sb + 8192, 128, 4096, 0);

#pragma unroll 1
    for (int pass = 0; pass < 2; pass++) {
        const int row0 = quarter * 512 + pass * 256 + wg * 64 + warp * 16 + g;
        uint32_t qa[4];
#pragma unroll
        for (int i = 0; i < 4; i++) qa[i] = pass ? qn2[1][i] : qn2[0][i];
        float o[12];
#pragma unroll
        for (int i = 0; i < 12; i++) o[i] = 0.f;
        fence_regs(o);
#define KF_RELEASE_CHUNK(c)                                                                          \
        if (pass == 1 && (c) >= 1 && (c) <= 4) {                                                     \
            named_sync(4 + wg, 128);            \
            if ((tid & 127) == 0 && atomicAdd(&s_cnt[(c) - 1], 1u) == 3u) {                          \
                mbar_expect_tx(wbar + 8 * (3 + (c)), 16384);                                         \
                tma_load_3d(sb + ((c) - 1) * KF_CH_S, &tm_wo, 0, (3 + (c)) * 64, nt * 2, wbar + 8 * (3 + (c))); \
            }                                                                                        \
        }
        if (fast) {
#pragma unroll 1
            for (int c = 0; c < KF_NCH; c++) {
                const uint64_t dk = dk0 + (uint64_t)(c * (KF_CH_S >> 4));
                const uint64_t dv = dv0 + (uint64_t)(c * (KF_CH_S >> 4));
                float s0[32], s1[32], s2[32], s3[32];
                uint32_t p0[16], p1[16], p2[16], p3[16];
                mbar_wait(kvbar + 8 * c, 0);
                wg_wait<1>();
                wg_fence();
                wgmma_qk_n64(s0, qa[0], qa[1], qa[2], qa[3], dk);
                wg_commit();
                wg_wait<1>();
                KF_RELEASE_CHUNK(c);
                wg_fence();
                wgmma_qk_n64(s1, qa[0], qa[1], qa[2], qa[3], dk + 64);
                wg_commit();
                wg_wait<1>();
                fence_regs(s0);
                softmax_part<0, 16>(s0, p0);
                wg_fence();
                KF_PV(p0, 0);
                wg_commit();
                wg_wait<1>();
                fence_regs(s1);
                softmax_part<0, 8>(s1, p1);
                wg_wait<0>();
                wg_fence();
                wgmma_qk_n64(s2, qa[0], qa[1], qa[2], qa[3], dk + 128);
                wg_commit();
                softmax_part<8, 16>(s1, p1);
                wg_fence();
                KF_PV(p1, 64);
                wg_commit();
                wg_wait<1>();
                fence_regs(s2);
                softmax_part<0, 8>(s2, p2);
                wg_wait<0>();
                wg_fence();
                wgmma_qk_n64(s3, qa[0], qa[1], qa[2], qa[3], dk + 192);
                wg_commit();
                softmax_part<8, 16>(s2, p2);
                wg_fence();
                KF_PV(p2, 128);
                wg_commit();
                wg_wait<1>();
                fence_regs(s3);
                softmax_part<0, 16>(s3, p3);
                wg_fence();
                KF_PV(p3, 192);
                wg_commit();
            }
            wg_wait<0>();
            fence_regs(o);
        } else {
            float m0 = -INFINITY, m1 = -INFINITY;
#pragma unroll 1
            for (int b = 0; b < 32; b++) {
                const int c = b >> 2;
                const uint64_t dk = dk0 + (uint64_t)(c * (KF_CH_S >> 4) + (b & 3) * 64);
                const uint64_t dv = dv0 + (uint64_t)(c * (KF_CH_S >> 4) + (b & 3) * 64);
                float s[32];
                uint32_t p[16];
                mbar_wait(kvbar + 8 * c, 0);
                wg_fence();
                wgmma_qk_n64(s, qa[0], qa[1], qa[2], qa[3], dk);
                wg_commit();
                if ((b & 3) == 0) { KF_RELEASE_CHUNK(c); }
                wg_wait<0>();
                fence_regs(s);
                float x0 = s[0], x1 = s[2];
#pragma unroll
                for (int j = 0; j < 8; j++) {
                    x0 = fmaxf(x0, fmaxf(s[4 * j], s[4 * j + 1]));
                    x1 = fmaxf(x1, fmaxf(s[4 * j + 2], s[4 * j + 3]));
                }
                x0 = fmaxf(x0, __shfl_xor_sync(0xffffffffu, x0, 1));
                x0 = fmaxf(x0, __shfl_xor_sync(0xffffffffu, x0, 2));
                x1 = fmaxf(x1, __shfl_xor_sync(0xffffffffu, x1, 1));
                x1 = fmaxf(x1, __shfl_xor_sync(0xffffffffu, x1, 2));
                const float n0 = fmaxf(m0, x0), n1 = fmaxf(m1, x1);
                const float c0 = ex2f(m0 - n0), c1 = ex2f(m1 - n1);
                m0 = n0; m1 = n1;
#pragma unroll
                for (int j = 0; j < 3; j++) {
                    o[4 * j] *= c0; o[4 * j + 1] *= c0; o[4 * j + 2] *= c1; o[4 * j + 3] *= c1;
                }
#pragma unroll
                for (int j = 0; j < 8; j++) {
                    p[2 * j] = pack_bf16(ex2f(s[4 * j] - n0), ex2f(s[4 * j + 1] - n0));
                    p[2 * j + 1] = pack_bf16(ex2f(s[4 * j + 2] - n1), ex2f(s[4 * j + 3] - n1));
                }
                fence_regs(o);
                wg_fence();
                KF_PV(p, 0);
                wg_commit();
                wg_wait<0>();
                fence_regs(o);
            }
        }
        const float inv0 = 1.f / o[8], inv1 = 1.f / o[10];
        {
            uint32_t v0 = pack_bf16(o[0] * inv0, o[1] * inv0), v1 = pack_bf16(o[4] * inv0, o[5] * inv0);
            uint32_t v2 = pack_bf16(o[2] * inv1, o[3] * inv1), v3 = pack_bf16(o[6] * inv1, o[7] * inv1);
            const bool o1 = t & 1, o2 = t & 2;
            uint32_t s0 = o1 ? v0 : v1, s1 = o1 ? v2 : v3;
            s0 = __shfl_xor_sync(0xffffffffu, s0, 1); s1 = __shfl_xor_sync(0xffffffffu, s1, 1);
            uint32_t a0 = o1 ? s0 : v0, a1 = o1 ? v1 : s0, b0 = o1 ? s1 : v2, b1 = o1 ? v3 : s1;
            uint32_t x0 = o2 ? a0 : b0, x1 = o2 ? a1 : b1;
            x0 = __shfl_xor_sync(0xffffffffu, x0, 2); x1 = __shfl_xor_sync(0xffffffffu, x1, 2);
            uint4 r;
            r.x = o2 ? x0 : a0; r.y = o2 ? x1 : a1; r.z = o2 ? b0 : x0; r.w = o2 ? b1 : x1;
            *(uint4*)(g_o + (size_t)(row0 + (t >> 1) * 8) * DM + head * 16 + (t & 1) * 8) = r;
        }
        if (tid == 0) TSTAMP0(1, 4 + pass);
    }
    if ((tid >> 5) != 10) named_arrive(1, 512);
    named_sync(4 + wg, 128);
    if ((tid & 127) == 0) {
        asm volatile("fence.acq_rel.gpu;" ::: "memory");
        asm volatile("red.relaxed.gpu.global.add.u32 [%0], 1;" ::"l"(&g_oflag[(quarter * 8 + 4 + wg) * 32 + (head >> 2) * 4]) : "memory");
        asm volatile("red.relaxed.gpu.global.add.u32 [%0], 1;" ::"l"(&g_oflag[(quarter * 8 + wg) * 32 + (head >> 2) * 4]) : "memory");
    }
    if (tid == 0) TSTAMP0(1, 3);

    if (wg < 2) {
        const int wi = warp;
        const int r0 = mt * 64 + wi * 16 + g;
        const int cb = nt * 128 + wg * 64;
        uint32_t xr[16], wr[8];
#pragma unroll
        for (int j = 0; j < 8; j++) {
            xr[2 * j] = __ldg((const uint32_t*)(x + (size_t)r0 * DM + cb + 8 * j + 2 * t));
            xr[2 * j + 1] = __ldg((const uint32_t*)(x + (size_t)(r0 + 8) * DM + cb + 8 * j + 2 * t));
            wr[j] = __ldg((const uint32_t*)(w_r + cb + 8 * j + 2 * t));
        }
        float wsum = 0.f;
        {
            const uint4 a = __ldg((const uint4*)(w_r + lane * 16)), b = __ldg((const uint4*)(w_r + lane * 16 + 8));
            const uint32_t w[8] = {a.x, a.y, a.z, a.w, b.x, b.y, b.z, b.w};
#pragma unroll
            for (int i = 0; i < 8; i++) wsum += bf_lo(w[i]) + bf_hi(w[i]);
#pragma unroll
            for (int o = 16; o > 0; o >>= 1) wsum += __shfl_xor_sync(0xffffffffu, wsum, o);
        }
        float acc[32];
#pragma unroll
        for (int i = 0; i < 32; i++) acc[i] = 0.f;
        fence_regs(acc);
#pragma unroll 1
        for (int i = 0; i < 8; i++) {
            mbar_wait(obar + 8 * i, 0);
            const int kb = __shfl_sync(0xffffffffu, (int)s_order[i], 0);
            mbar_wait(wbar + 8 * kb, 0);
            const uint32_t wa = (kb < 4) ? (KF_OFF_WO + kb * 16384) : ((kb - 4) * KF_CH_S);
            const uint64_t da = make_desc(sb + (4 + (kb >> 1)) * KF_CH_S + (kb & 1) * 8192, 16, 1024, 1);
            const uint64_t db = make_desc(sb + wa + wg * 8192, 1024, 1024, 1);
            wg_fence();
#pragma unroll
            for (int k = 0; k < 4; k++) wgmma_k3_n64(acc, da + k * 2, db + k * 128, (i | k) != 0);
            wg_commit();
        }
        wg_wait<0>();
        fence_regs(acc);
        if (tid == 0) TSTAMP0(2, 2);
        float hv[32];
        uint32_t hp[16];
        float s0 = 0.f, s1 = 0.f, d0 = 0.f, d1 = 0.f;
#pragma unroll
        for (int j = 0; j < 8; j++) {
            const uint32_t a01 = pack_bf16(acc[4 * j], acc[4 * j + 1]), a23 = pack_bf16(acc[4 * j + 2], acc[4 * j + 3]);
            hp[2 * j] = pack_bf16(bf_lo(xr[2 * j]) + bf_lo(a01), bf_hi(xr[2 * j]) + bf_hi(a01));
            hp[2 * j + 1] = pack_bf16(bf_lo(xr[2 * j + 1]) + bf_lo(a23), bf_hi(xr[2 * j + 1]) + bf_hi(a23));
            hv[4 * j] = bf_lo(hp[2 * j]); hv[4 * j + 1] = bf_hi(hp[2 * j]);
            hv[4 * j + 2] = bf_lo(hp[2 * j + 1]); hv[4 * j + 3] = bf_hi(hp[2 * j + 1]);
            const float wl = bf_lo(wr[j]), wh = bf_hi(wr[j]);
            s0 += hv[4 * j] + hv[4 * j + 1];
            s1 += hv[4 * j + 2] + hv[4 * j + 3];
            d0 = fmaf(hv[4 * j], wl, fmaf(hv[4 * j + 1], wh, d0));
            d1 = fmaf(hv[4 * j + 2], wl, fmaf(hv[4 * j + 3], wh, d1));
        }
        float mu0 = s0 * (1.f / 16), mu1 = s1 * (1.f / 16);
        float q0 = 0.f, q1 = 0.f;
#pragma unroll
        for (int j = 0; j < 8; j++) {
            float a = hv[4 * j] - mu0, b = hv[4 * j + 1] - mu0, c = hv[4 * j + 2] - mu1, d = hv[4 * j + 3] - mu1;
            q0 = fmaf(a, a, fmaf(b, b, q0));
            q1 = fmaf(c, c, fmaf(d, d, q1));
        }
#pragma unroll
        for (int o = 1; o < 4; o <<= 1) {
            const float m0 = __shfl_xor_sync(0xffffffffu, mu0, o), m1 = __shfl_xor_sync(0xffffffffu, mu1, o);
            const float e0 = __shfl_xor_sync(0xffffffffu, q0, o), e1 = __shfl_xor_sync(0xffffffffu, q1, o);
            d0 += __shfl_xor_sync(0xffffffffu, d0, o);
            d1 += __shfl_xor_sync(0xffffffffu, d1, o);
            const float f0 = mu0 - m0, f1 = mu1 - m1;
            q0 = q0 + e0 + f0 * f0 * (8.f * o);
            q1 = q1 + e1 + f1 * f1 * (8.f * o);
            mu0 = 0.5f * (mu0 + m0); mu1 = 0.5f * (mu1 + m1);
        }
        float4* part = g_part + (size_t)mt * 512 + wi * 16 + g;
        if (t < 2) {
            float4* dst = part + (nt * 2 + wg) * 64 + t * 8;
            const float a = t ? mu1 : mu0, b = t ? q1 : q0, c = t ? d1 : d0;
            asm volatile("st.relaxed.gpu.global.v4.f32 [%0], {%1, %2, %3, %4};" ::"l"(dst), "f"(a), "f"(b), "f"(c), "f"(__uint_as_float(tag)) : "memory");
        }
        if (tid == 0) TSTAMP0(2, 5);
        const uint32_t stg_off = KF_OFF_WO + (wi >> 1) * 16384 + wg * 8192 + (wi & 1) * 4096;
        const uint32_t stg_o = sb + stg_off, stg_h = stg_o + 2048;
        const int srow = (lane & 7) + ((lane >> 3) & 1) * 8;
        const int sj = lane >> 4;
        named_sync(4 + wg, 128);
#pragma unroll
        for (int j = 0; j < 8; j += 2) {
            const uint32_t off = srow * 128 + (((j + sj) ^ (srow & 7)) << 4);
            stmatrix_x4(stg_h + off, hp[2 * j], hp[2 * j + 1], hp[2 * j + 2], hp[2 * j + 3]);
        }
        __syncwarp();
#pragma unroll
        for (int i = 0; i < 4; i++) {
            const int row = i * 4 + (lane >> 3), ch = lane & 7;
            const uint4 vh = *(const uint4*)(sp + stg_off + 2048 + row * 128 + ((ch ^ (row & 7)) << 4));
            *(uint4*)(g_h + (size_t)(mt * 64 + wi * 16 + row) * DM + cb + ch * 8) = vh;
        }
        named_arrive(8, 288);
        if (tid == 0) TSTAMP0(2, 6);
        float mean[2], den[2], rr[2];
        {
            float4 v[4];
            int spins = 0;
            while (true) {
#pragma unroll
                for (int i = 0; i < 4; i++) {
                    const float4* p = part + (t + (i & 1) * 4) * 64 + (i >> 1) * 8;
                    asm volatile("ld.relaxed.gpu.global.v4.f32 {%0, %1, %2, %3}, [%4];" : "=f"(v[i].x), "=f"(v[i].y), "=f"(v[i].z), "=f"(v[i].w) : "l"(p) : "memory");
                }
                const bool ok = (__float_as_uint(v[0].w) == tag) && (__float_as_uint(v[1].w) == tag) && (__float_as_uint(v[2].w) == tag) && (__float_as_uint(v[3].w) == tag);
                if (__all_sync(0xffffffffu, ok) || ++spins > (1 << 22)) break;
            }
#pragma unroll
            for (int u = 0; u < 2; u++) {
                float mu = v[2 * u].x + v[2 * u + 1].x, m2 = v[2 * u].y + v[2 * u + 1].y, hw = v[2 * u].z + v[2 * u + 1].z;
#pragma unroll
                for (int o = 1; o < 4; o <<= 1) {
                    mu += __shfl_xor_sync(0xffffffffu, mu, o);
                    m2 += __shfl_xor_sync(0xffffffffu, m2, o);
                    hw += __shfl_xor_sync(0xffffffffu, hw, o);
                }
                mu *= 0.125f;
                const float da = v[2 * u].x - mu, db = v[2 * u + 1].x - mu;
                float dd = 64.f * (da * da + db * db);
#pragma unroll
                for (int o = 1; o < 4; o <<= 1) dd += __shfl_xor_sync(0xffffffffu, dd, o);
                m2 += dd;
                mean[u] = rbf(mu);
                den[u] = rbf(sqrtf(rbf(rbf(m2 * (1.f / DM)) + 1e-5f)));
                rr[u] = rbf((hw - mean[u] * wsum) / den[u]);
            }
        }
        if (tid == 0) TSTAMP0(2, 3);
        named_arrive(3, 512);
        if (nt == 0 && wg == 0) {
            float2* s_st = (float2*)(sp + KF_OFF_WO + 49152);
            if (t == 0) {
                s_key[wi * 16 + g] = make_key(rr[0], r0);
                s_key[wi * 16 + g + 8] = make_key(rr[1], r0 + 8);
                s_st[wi * 16 + g] = make_float2(mean[0], den[0]);
                s_st[wi * 16 + g + 8] = make_float2(mean[1], den[1]);
            }
            named_sync(4, 128);
            if (warp == 0) {
                uint32_t k1, k2;
                warp_top2(s_key[lane], s_key[lane + 32], k1, k2);
                if (lane < 2) {
                    const uint32_t k = lane ? k2 : k1;
                    const float2 st = s_st[key_token(k) & 63];
                    asm volatile("st.relaxed.gpu.global.v4.u32 [%0], {%1, %2, %3, %4};" ::"l"(g_cand + mt * 2 + lane), "r"(k),
                                 "r"(tag), "r"(__float_as_uint(st.x)), "r"(__float_as_uint(st.y)) : "memory");
                }
            }
        }
        const float i0 = 1.f / den[0], i1 = 1.f / den[1];
#pragma unroll
        for (int j = 0; j < 8; j += 2) {
            uint32_t ro[4];
#pragma unroll
            for (int u = 0; u < 2; u++) {
                const int jj = j + u;
                const float a = hv[4 * jj], b = hv[4 * jj + 1], c = hv[4 * jj + 2], d = hv[4 * jj + 3];
                const uint32_t u01 = pack_bf16(a - mean[0], b - mean[0]), u23 = pack_bf16(c - mean[1], d - mean[1]);
                const uint32_t n01 = pack_bf16(bf_lo(u01) * i0, bf_hi(u01) * i0), n23 = pack_bf16(bf_lo(u23) * i1, bf_hi(u23) * i1);
                ro[2 * u] = pack_bf16(a + bf_lo(n01), b + bf_hi(n01));
                ro[2 * u + 1] = pack_bf16(c + bf_lo(n23), d + bf_hi(n23));
            }
            const uint32_t off = srow * 128 + (((j + sj) ^ (srow & 7)) << 4);
            stmatrix_x4(stg_o + off, ro[0], ro[1], ro[2], ro[3]);
        }
        __syncwarp();
#pragma unroll
        for (int i = 0; i < 4; i++) {
            const int row = i * 4 + (lane >> 3), ch = lane & 7;
            const uint4 vo = *(const uint4*)(sp + stg_off + row * 128 + ((ch ^ (row & 7)) << 4));
            *(uint4*)(out + (size_t)(mt * 64 + wi * 16 + row) * DM + cb + ch * 8) = vo;
        }
        named_sync(4 + wg, 128);
        if ((tid & 127) == 0) red_release_add(&g_sflag[mt]);
        if (tid == 0) TSTAMP0(2, 4);
    } else {
        const bool worker = blockIdx.x < FF / 16;
        const bool downer = blockIdx.x >= 64;
        const int mtid = tid - 256, mwarp = mtid >> 5;
        const int c0 = (blockIdx.x - 64) * 8;
        float* s_x = (float*)(sp + KF_OFF_WO + 49152 + 8192);
        float* s_red = (float*)(sp + KF_OFF_WO + 49152 + 8192 + 4096);
        if (mwarp == 2) {
            named_sync(1, 512);
            uint32_t done = 0;
            int n = 0, spins = 0;
            while (done != 0xFFu && ++spins < (1 << 22)) {
                const bool rdy = lane < 8 && (int)(ld_acquire(&g_oflag[mt * 32 + lane * 4]) - 4u * tag) >= 0;
                uint32_t todo = __ballot_sync(0xffffffffu, rdy) & ~done;
                done |= todo;
                if (todo && lane == 0) {
                    asm volatile("fence.proxy.async.global;" ::: "memory");
                    while (todo) {
                        const int kb = __ffs(todo) - 1;
                        todo &= todo - 1;
                        s_order[n] = kb;
                        mbar_expect_tx(obar + 8 * n, 8192);
                        tma_load_3d(sb + (4 + (kb >> 1)) * KF_CH_S + (kb & 1) * 8192, &tm_o, 0, mt * 64, kb, obar + 8 * n);
                        n++;
                    }
                }
                n = __shfl_sync(0xffffffffu, n, 0);
                if (done != 0xFFu) __nanosleep(POLL_NS);
            }
            if (lane == 0) TSTAMP0(2, 1);
            if (lane == 0 && worker) {
                mbar_expect_tx(gbar, 32768);
                for (int i = 0; i < 4; i++) {
                    tma_load_2d(sb + i * KF_CH_S + 16384, &tm_g, blockIdx.x * 16, i * 128, gbar);
                    tma_load_2d(sb + (4 + i) * KF_CH_S + 16384, &tm_u, blockIdx.x * 16, i * 128, gbar);
                }
            }
        }
        if (mwarp == 1) {
            named_sync(8, 288);
            if (lane == 0) {
                red_release_add(&g_hflag[mt]);
                if (downer) {
                    mbar_expect_tx(dbar, 7 * 4096);
                    for (int i = 0; i < 7; i++) tma_load_2d(sb + (4 + (i >> 2)) * KF_CH_S + (i & 3) * 4096, &tm_d, c0, i * 256, dbar);
                }
            }
            __syncwarp();
        }
        if (mtid == 0) TSTAMP0(3, 0);
        named_sync(3, 512);
        if (mwarp == 0) {
            uint4 ca, cb4;
            int spins = 0;
            while (true) {
                asm volatile("ld.relaxed.gpu.global.v4.u32 {%0, %1, %2, %3}, [%4];" : "=r"(ca.x), "=r"(ca.y), "=r"(ca.z), "=r"(ca.w) : "l"(g_cand + 2 * lane) : "memory");
                asm volatile("ld.relaxed.gpu.global.v4.u32 {%0, %1, %2, %3}, [%4];" : "=r"(cb4.x), "=r"(cb4.y), "=r"(cb4.z), "=r"(cb4.w) : "l"(g_cand + 2 * lane + 1) : "memory");
                const unsigned int hf = ld_acquire(&g_hflag[lane]);
                const bool ok = ca.y == tag && cb4.y == tag && (int)(hf - 4u * tag) >= 0;
                if (__all_sync(0xffffffffu, ok) || ++spins > (1 << 22)) break;
            }
            uint32_t k1, k2;
            warp_top2(ca.x, cb4.x, k1, k2);
            if (ca.x == k1) s_sel[0] = ca;
            if (cb4.x == k1) s_sel[0] = cb4;
            if (ca.x == k2) s_sel[1] = ca;
            if (cb4.x == k2) s_sel[1] = cb4;
        }
        named_sync(2, 256);
        if (mtid == 0) TSTAMP0(3, 1);
        int idx[2];
        float mean[2], inv[2], rv[2];
#pragma unroll
        for (int u = 0; u < 2; u++) {
            const uint4 c = s_sel[u];
            idx[u] = key_token(c.x);
            rv[u] = key_value(c.x);
            mean[u] = __uint_as_float(c.z);
            inv[u] = 1.f / __uint_as_float(c.w);
        }
        float hfin = 0.f;
        if (downer && mtid < 16) hfin = __bfloat162float(__ldcg((const __nv_bfloat16*)(g_h + (size_t)((mtid >> 3) ? idx[1] : idx[0]) * DM + c0 + (mtid & 7))));
        if (worker) {
            {
                const uint32_t h0 = __ldcg((const uint32_t*)(g_h + (size_t)idx[0] * DM + 2 * mtid));
                const uint32_t h1 = __ldcg((const uint32_t*)(g_h + (size_t)idx[1] * DM + 2 * mtid));
                const uint32_t u0 = pack_bf16(bf_lo(h0) - mean[0], bf_hi(h0) - mean[0]), u1 = pack_bf16(bf_lo(h1) - mean[1], bf_hi(h1) - mean[1]);
                const uint32_t n0 = pack_bf16(bf_lo(u0) * inv[0], bf_hi(u0) * inv[0]), n1 = pack_bf16(bf_lo(u1) * inv[1], bf_hi(u1) * inv[1]);
                *(float4*)(s_x + 4 * mtid) = make_float4(bf_lo(n0), bf_lo(n1), bf_hi(n0), bf_hi(n1));
            }
            if (mtid == 0) TSTAMP0(3, 5);
            mbar_wait(gbar, 0);
            named_sync(2, 256);
            if (mtid == 0) TSTAMP0(3, 6);
            float acc[8];
#pragma unroll
            for (int i = 0; i < 8; i++) acc[i] = 0.f;
            const uint8_t* wbase = sp + (mwarp >> 2) * (4 * KF_CH_S) + 16384 + lane * 32 + (mwarp & 3) * 8;
#pragma unroll
            for (int k = 0; k < 16; k++) {
                const uint2 w = *(const uint2*)(wbase + (k >> 2) * KF_CH_S + (k & 3) * 1024);
                const float2 xx = *(const float2*)(s_x + 2 * (lane + 32 * k));
                const float x0 = xx.x, x1 = xx.y;
                const float w0 = bf_lo(w.x), w1 = bf_hi(w.x), w2 = bf_lo(w.y), w3 = bf_hi(w.y);
                acc[0] = fmaf(x0, w0, acc[0]); acc[1] = fmaf(x0, w1, acc[1]); acc[2] = fmaf(x0, w2, acc[2]); acc[3] = fmaf(x0, w3, acc[3]);
                acc[4] = fmaf(x1, w0, acc[4]); acc[5] = fmaf(x1, w1, acc[5]); acc[6] = fmaf(x1, w2, acc[6]); acc[7] = fmaf(x1, w3, acc[7]);
            }
#define KF_STEP(O, N)                                                          \
            {                                                                  \
                const bool up = (lane & (O)) != 0;                             \
                _Pragma("unroll") for (int i = 0; i < (N); i++) {              \
                    const float send = up ? acc[i] : acc[i + (N)];             \
                    const float keep = up ? acc[i + (N)] : acc[i];             \
                    acc[i] = keep + __shfl_xor_sync(0xffffffffu, send, (O));   \
                }                                                              \
            }
            KF_STEP(16, 4) KF_STEP(8, 2) KF_STEP(4, 1)
            acc[0] += __shfl_xor_sync(0xffffffffu, acc[0], 2);
            acc[0] += __shfl_xor_sync(0xffffffffu, acc[0], 1);
            if ((lane & 3) == 0) {
                const int v = ((lane & 16) ? 4 : 0) + ((lane & 8) ? 2 : 0) + ((lane & 4) ? 1 : 0);
                s_gu[(v >> 2) * 32 + mwarp * 4 + (v & 3)] = acc[0];
            }
            named_sync(2, 256);
            if (mtid < 16) {
                uint32_t a2 = 0;
#pragma unroll
                for (int u = 0; u < 2; u++) {
                    const float gb = rbf(s_gu[u * 32 + mtid]);
                    const float sg = rbf(gb / (1.f + __expf(-gb)));
                    float a = sg * rbf(s_gu[u * 32 + 16 + mtid]);
                    a2 |= (uint32_t)__bfloat16_as_ushort(__float2bfloat16_rn(a)) << (16 * u);
                }
                asm volatile("st.relaxed.gpu.global.v2.u32 [%0], {%1, %2};" ::"l"(g_act + blockIdx.x * 16 + mtid), "r"(a2), "r"(tag) : "memory");
            }
            if (mtid == 0) TSTAMP0(3, 2);
        }
        if (downer) {
            uint32_t av[7];
            {
                int spins = 0;
                while (true) {
                    bool ok = true;
#pragma unroll
                    for (int j = 0; j < 7; j++) {
                        uint32_t tg;
                        asm volatile("ld.relaxed.gpu.global.v2.u32 {%0, %1}, [%2];" : "=r"(av[j]), "=r"(tg) : "l"(g_act + mtid + 256 * j) : "memory");
                        ok = ok && tg == tag;
                    }
                    if (mtid < 2) ok = ok && ((int)(ld_acquire(&g_sflag[(mtid ? idx[1] : idx[0]) >> 6]) - 8u * tag) >= 0);
                    if (__all_sync(0xffffffffu, ok) || ++spins > (1 << 20)) break;
                    __nanosleep(20);
                }
            }
            if (mtid == 0) TSTAMP0(3, 3);
            mbar_wait(dbar, 0);
            float acc[16];
#pragma unroll
            for (int i = 0; i < 16; i++) acc[i] = 0.f;
#pragma unroll
            for (int j = 0; j < 7; j++) {
                const uint4 w = *(const uint4*)(sp + (4 + (j >> 2)) * KF_CH_S + (j & 3) * 4096 + mtid * 16);
                const float a0 = bf_lo(av[j]), a1 = bf_hi(av[j]);
                const uint32_t ww[4] = {w.x, w.y, w.z, w.w};
#pragma unroll
                for (int q = 0; q < 4; q++) {
                    const float wl = bf_lo(ww[q]), wh = bf_hi(ww[q]);
                    acc[2 * q] = fmaf(a0, wl, acc[2 * q]); acc[2 * q + 1] = fmaf(a0, wh, acc[2 * q + 1]);
                    acc[8 + 2 * q] = fmaf(a1, wl, acc[8 + 2 * q]); acc[8 + 2 * q + 1] = fmaf(a1, wh, acc[8 + 2 * q + 1]);
                }
            }
            KF_STEP(16, 8) KF_STEP(8, 4) KF_STEP(4, 2) KF_STEP(2, 1)
            acc[0] += __shfl_xor_sync(0xffffffffu, acc[0], 1);
            if ((lane & 1) == 0) {
                const int v = ((lane & 16) ? 8 : 0) + ((lane & 8) ? 4 : 0) + ((lane & 4) ? 2 : 0) + ((lane & 2) ? 1 : 0);
                s_red[mwarp * 16 + v] = acc[0];
            }
            named_sync(2, 256);
            if (mtid < 16) {
                const int u = mtid >> 3;
                float y = 0.f;
#pragma unroll
                for (int w = 0; w < 8; w++) y += s_red[w * 16 + mtid];
                const float sig = rbf(1.f / (1.f + __expf(-(u ? rv[1] : rv[0]))));
                const float xn = rbf(rbf(hfin - (u ? mean[1] : mean[0])) * (u ? inv[1] : inv[0]));
                const float ov = hfin + rbf(xn + rbf(rbf(y) * sig));
                out[(size_t)(u ? idx[1] : idx[0]) * DM + c0 + (mtid & 7)] = __float2bfloat16_rn(ov);
            }
            if (blockIdx.x == gridDim.x - 1 && mtid == 0) g_epoch = tag;
            if (mtid == 0) TSTAMP0(3, 4);
        }
    }
}

typedef CUresult (*PFN_encodeTiled)(CUtensorMap*, CUtensorMapDataType, cuuint32_t, void*, const cuuint64_t*, const cuuint64_t*,
                                    const cuuint32_t*, const cuuint32_t*, CUtensorMapInterleave, CUtensorMapSwizzle,
                                    CUtensorMapL2promotion, CUtensorMapFloatOOBfill);

void make_map(PFN_encodeTiled enc, CUtensorMap* m, const void* ptr, uint64_t cols, uint64_t rows, uint32_t bcols, uint32_t brows) {
    cuuint64_t dims[2] = {cols, rows};
    cuuint64_t strides[1] = {cols * 2};
    cuuint32_t box[2] = {bcols, brows};
    cuuint32_t es[2] = {1, 1};
    enc(m, CU_TENSOR_MAP_DATA_TYPE_BFLOAT16, 2, const_cast<void*>(ptr), dims, strides, box, es, CU_TENSOR_MAP_INTERLEAVE_NONE,
        CU_TENSOR_MAP_SWIZZLE_128B, CU_TENSOR_MAP_L2_PROMOTION_L2_256B, CU_TENSOR_MAP_FLOAT_OOB_FILL_NONE);
}

void make_map3(PFN_encodeTiled enc, CUtensorMap* m, const void* ptr, uint64_t d0, uint64_t rows, uint64_t d2, uint64_t row_stride_bytes,
               uint64_t d2_stride_bytes, uint32_t b0, uint32_t b1, uint32_t b2) {
    cuuint64_t dims[3] = {d0, rows, d2};
    cuuint64_t strides[2] = {row_stride_bytes, d2_stride_bytes};
    cuuint32_t box[3] = {b0, b1, b2};
    cuuint32_t es[3] = {1, 1, 1};
    enc(m, CU_TENSOR_MAP_DATA_TYPE_BFLOAT16, 3, const_cast<void*>(ptr), dims, strides, box, es, CU_TENSOR_MAP_INTERLEAVE_NONE,
        CU_TENSOR_MAP_SWIZZLE_128B, CU_TENSOR_MAP_L2_PROMOTION_L2_256B, CU_TENSOR_MAP_FLOAT_OOB_FILL_NONE);
}

void make_map_plain(PFN_encodeTiled enc, CUtensorMap* m, const void* ptr, uint64_t cols, uint64_t rows, uint32_t bcols, uint32_t brows) {
    cuuint64_t dims[2] = {cols, rows};
    cuuint64_t strides[1] = {cols * 2};
    cuuint32_t box[2] = {bcols, brows};
    cuuint32_t es[2] = {1, 1};
    enc(m, CU_TENSOR_MAP_DATA_TYPE_BFLOAT16, 2, const_cast<void*>(ptr), dims, strides, box, es, CU_TENSOR_MAP_INTERLEAVE_NONE,
        CU_TENSOR_MAP_SWIZZLE_NONE, CU_TENSOR_MAP_L2_PROMOTION_NONE, CU_TENSOR_MAP_FLOAT_OOB_FILL_NONE);
}

template <typename... KArgs, typename... Args>
void launch(void (*kern)(KArgs...), int grid, int block, int smem, bool pdl, Args... args) {
    cudaLaunchConfig_t cfg = {};
    cfg.gridDim = dim3(grid);
    cfg.blockDim = dim3(block);
    cfg.dynamicSmemBytes = smem;
    cfg.stream = cudaStreamPerThread;
    cudaLaunchAttribute at[1];
    at[0].id = cudaLaunchAttributeProgrammaticStreamSerialization;
    at[0].val.programmaticStreamSerializationAllowed = 1;
    cfg.attrs = at;
    cfg.numAttrs = pdl ? 1 : 0;
    cudaLaunchKernelEx(&cfg, kern, KArgs(args)...);
}

}

extern "C" void kernel_launch(void* const* d_in, const int* in_sizes, int n_in, void* d_out, int out_size) {
    const __nv_bfloat16* x = (const __nv_bfloat16*)d_in[0];
    const __nv_bfloat16* wqkv = (const __nv_bfloat16*)d_in[1];
    const __nv_bfloat16* wo = (const __nv_bfloat16*)d_in[2];
    const __nv_bfloat16* w_r = (const __nv_bfloat16*)d_in[4];
    const __nv_bfloat16* w_gate = (const __nv_bfloat16*)d_in[5];
    const __nv_bfloat16* w_up = (const __nv_bfloat16*)d_in[6];
    const __nv_bfloat16* w_down = (const __nv_bfloat16*)d_in[7];
    __nv_bfloat16* out = (__nv_bfloat16*)d_out;

    static PFN_encodeTiled enc = nullptr;
    static void* g_o_ptr = nullptr;
    if (!enc) {
        cudaDriverEntryPointQueryResult qres;
        void* fn = nullptr;
        cudaGetDriverEntryPoint("cuTensorMapEncodeTiled", &fn, cudaEnableDefault, &qres);
        enc = (PFN_encodeTiled)fn;
        cudaGetSymbolAddress(&g_o_ptr, g_o);
        cudaFuncSetAttribute(kf_main, cudaFuncAttributeMaxDynamicSharedMemorySize, KF_SMEM);
    }
    CUtensorMap tm_x, tm_w, tm_o, tm_wo, tm_g, tm_u, tm_d;
    make_map_plain(enc, &tm_d, w_down, DM, FF, 8, 256);
    make_map_plain(enc, &tm_g, w_gate, FF, DM, 16, 128);
    make_map_plain(enc, &tm_u, w_up, FF, DM, 16, 128);
    make_map(enc, &tm_x, x, DM, SEQ, 64, 128);
    make_map3(enc, &tm_w, wqkv, DM, DM, 3, 3 * DM * 2, DM * 2, 64, 64, 3);
    make_map3(enc, &tm_o, g_o_ptr, 64, SEQ, 8, DM * 2, 128, 64, 64, 1);
    make_map3(enc, &tm_wo, wo, 64, DM, 8, DM * 2, 128, 64, 64, 2);

    launch(kf_main, 128, 512, KF_SMEM, false, tm_x, tm_w, tm_o, tm_wo, tm_g, tm_u, tm_d, x, wo, w_r, w_gate, w_up, w_down, out);
}
```

```cpp
#include <cuda_runtime.h>
#include <cuda_bf16.h>
#include <cuda.h>
#include <stdint.h>

namespace {

constexpr int SEQ = 2048, DM = 512, NH = 32, FF = 1792;

__device__ __align__(1024) uint8_t g_q[NH * 2 * SEQ * 16];
__device__ __align__(1024) uint8_t g_kv[NH * 8 * 16384];
__device__ float g_norm[16 * NH * 3];
__device__ __align__(1024) __nv_bfloat16 g_o[SEQ * DM];
__device__ __align__(1024) __nv_bfloat16 g_h[SEQ * DM];
__device__ __align__(16) uint4 g_cand[64];
__device__ unsigned int g_oflag[32 * 32];
__device__ unsigned int g_hflag[32];
__device__ unsigned int g_sflag[32];
__device__ __align__(8) uint2 g_act[FF];
__device__ unsigned int g_kvflag[8 * 16 * 8];
__device__ unsigned int g_epoch;
__device__ __align__(16) float4 g_ln1[SEQ];
__device__ __align__(16) float4 g_part[32 * 8 * 64];

#define TSTAMP(K, I)
#define TSTAMP0(K, I)
__device__ __forceinline__ uint32_t smem_u32(const void* p) { return (uint32_t)__cvta_generic_to_shared(p); }
__device__ __forceinline__ void wg_fence() { asm volatile("wgmma.fence.sync.aligned;" ::: "memory"); }
__device__ __forceinline__ void wg_commit() { asm volatile("wgmma.commit_group.sync.aligned;" ::: "memory"); }
template <int N> __device__ __forceinline__ void wg_wait() { asm volatile("wgmma.wait_group.sync.aligned %0;" ::"n"(N) : "memory"); }
template <int N> __device__ __forceinline__ void fence_regs(float (&r)[N]) {
#pragma unroll
    for (int i = 0; i < N; i++) asm volatile("" : "+f"(r[i])::"memory");
}
__device__ __forceinline__ uint64_t make_desc(uint32_t addr, uint32_t lbo, uint32_t sbo, uint32_t swz) {
    uint64_t d = 0;
    d |= (uint64_t)((addr & 0x3FFFF) >> 4);
    d |= (uint64_t)((lbo & 0x3FFFF) >> 4) << 16;
    d |= (uint64_t)((sbo & 0x3FFFF) >> 4) << 32;
    d |= (uint64_t)swz << 62;
    return d;
}
__device__ __forceinline__ void mbar_init(uint32_t bar, uint32_t cnt) {
    asm volatile("mbarrier.init.shared::cta.b64 [%0], %1;" ::"r"(bar), "r"(cnt) : "memory");
}
__device__ __forceinline__ void mbar_expect_tx(uint32_t bar, uint32_t bytes) {
    asm volatile("mbarrier.arrive.expect_tx.shared::cta.b64 _, [%0], %1;" ::"r"(bar), "r"(bytes) : "memory");
}
__device__ __forceinline__ void mbar_arrive(uint32_t bar) {
    asm volatile("mbarrier.arrive.shared::cta.b64 _, [%0];" ::"r"(bar) : "memory");
}
__device__ __forceinline__ void mbar_wait(uint32_t bar, uint32_t parity) {
    asm volatile(
        "{\n.reg .pred p;\nWAIT_%=:\n"
        "mbarrier.try_wait.parity.shared::cta.b64 p, [%0], %1;\n"
        "@p bra DONE_%=;\nbra WAIT_%=;\nDONE_%=:\n}\n" ::"r"(bar), "r"(parity) : "memory");
}
__device__ __forceinline__ void bulk_g2s(uint32_t dst, const void* src, uint32_t bytes, uint32_t bar) {
    asm volatile("cp.async.bulk.shared::cluster.global.mbarrier::complete_tx::bytes [%0], [%1], %2, [%3];" ::"r"(dst),
                 "l"(src), "r"(bytes), "r"(bar) : "memory");
}
__device__ __forceinline__ void bulk_s2g(void* dst, uint32_t src, uint32_t bytes) {
    asm volatile("cp.async.bulk.global.shared::cta.bulk_group [%0], [%1], %2;" ::"l"(dst), "r"(src), "r"(bytes) : "memory");
}
__device__ __forceinline__ void tma_load_2d(uint32_t dst, const CUtensorMap* tm, int c0, int c1, uint32_t bar) {
    asm volatile("cp.async.bulk.tensor.2d.shared::cluster.global.mbarrier::complete_tx::bytes [%0], [%1, {%3, %4}], [%2];" ::"r"(dst),
                 "l"(tm), "r"(bar), "r"(c0), "r"(c1) : "memory");
}
__device__ __forceinline__ void tma_load_3d(uint32_t dst, const CUtensorMap* tm, int c0, int c1, int c2, uint32_t bar) {
    asm volatile("cp.async.bulk.tensor.3d.shared::cluster.global.mbarrier::complete_tx::bytes [%0], [%1, {%3, %4, %5}], [%2];" ::"r"(dst),
                 "l"(tm), "r"(bar), "r"(c0), "r"(c1), "r"(c2) : "memory");
}
__device__ __forceinline__ void tma_load_2d_mc(uint32_t dst, const CUtensorMap* tm, int c0, int c1, uint32_t bar, uint16_t mask) {
    asm volatile("cp.async.bulk.tensor.2d.shared::cluster.global.mbarrier::complete_tx::bytes.multicast::cluster [%0], [%1, {%3, %4}], [%2], %5;" ::"r"(dst),
                 "l"(tm), "r"(bar), "r"(c0), "r"(c1), "h"(mask) : "memory");
}
__device__ __forceinline__ void mbar_arrive_cluster(uint32_t bar, uint32_t cta) {
    asm volatile("{\n.reg .b32 ra;\nmapa.shared::cluster.u32 ra, %0, %1;\nmbarrier.arrive.release.cluster.shared::cluster.b64 _, [ra];\n}" ::"r"(bar), "r"(cta) : "memory");
}
__device__ __forceinline__ void cluster_sync() {
    asm volatile("barrier.cluster.arrive.release.aligned;\nbarrier.cluster.wait.acquire.aligned;" ::: "memory");
}
__device__ __forceinline__ void prefetch_l2(const void* p, uint32_t bytes) {
    asm volatile("cp.async.bulk.prefetch.L2.global [%0], %1;" ::"l"(p), "r"(bytes) : "memory");
}
__device__ __forceinline__ void fence_proxy_async() { asm volatile("fence.proxy.async.shared::cta;" ::: "memory"); }
__device__ __forceinline__ void fence_barrier_init() { asm volatile("fence.mbarrier_init.release.cluster;" ::: "memory"); }
__device__ __forceinline__ void pdl_launch() { asm volatile("griddepcontrol.launch_dependents;" ::: "memory"); }
__device__ __forceinline__ void pdl_wait() { asm volatile("griddepcontrol.wait;" ::: "memory"); }
__device__ __forceinline__ void named_sync(int id, int n) { asm volatile("bar.sync %0, %1;" ::"r"(id), "r"(n) : "memory"); }
__device__ __forceinline__ void named_arrive(int id, int n) { asm volatile("bar.arrive %0, %1;" ::"r"(id), "r"(n) : "memory"); }

__device__ __forceinline__ float ex2f(float x) { float y; asm("ex2.approx.ftz.f32 %0, %1;" : "=f"(y) : "f"(x)); return y; }
__device__ __forceinline__ uint32_t pack_bf16(float lo, float hi) {
    uint32_t r; asm("cvt.rn.bf16x2.f32 %0, %1, %2;" : "=r"(r) : "f"(hi), "f"(lo)); return r;
}
__device__ __forceinline__ float bf_lo(uint32_t v) { return __uint_as_float(v << 16); }
__device__ __forceinline__ float bf_hi(uint32_t v) { return __uint_as_float(v & 0xFFFF0000u); }
__device__ __forceinline__ float rbf(float x) { return __bfloat162float(__float2bfloat16_rn(x)); }
__device__ __forceinline__ uint32_t fma_bf16x2(uint32_t a, uint32_t b, uint32_t c) {
    uint32_t r; asm("fma.rn.bf16x2 %0, %1, %2, %3;" : "=r"(r) : "r"(a), "r"(b), "r"(c)); return r;
}
__device__ __forceinline__ void stmatrix_x4(uint32_t addr, uint32_t r0, uint32_t r1, uint32_t r2, uint32_t r3) {
    asm volatile("stmatrix.sync.aligned.m8n8.x4.shared.b16 [%0], {%1, %2, %3, %4};" ::"r"(addr), "r"(r0), "r"(r1), "r"(r2), "r"(r3) : "memory");
}
__device__ __forceinline__ void stmatrix_x4_trans(uint32_t addr, uint32_t r0, uint32_t r1, uint32_t r2, uint32_t r3) {
    asm volatile("stmatrix.sync.aligned.m8n8.x4.trans.shared.b16 [%0], {%1, %2, %3, %4};" ::"r"(addr), "r"(r0), "r"(r1), "r"(r2), "r"(r3) : "memory");
}

__device__ __forceinline__ void wgmma_k1_n136(float (&d)[68], uint64_t desca, uint64_t descb, int scale_d) {
  asm volatile("{\n.reg .pred p;\nsetp.ne.b32 p, %70, 0;\n"
    "wgmma.mma_async.sync.aligned.m64n136k16.f32.bf16.bf16 "
    "{%0, %1, %2, %3, %4, %5, %6, %7, %8, %9, %10, %11, %12, %13, %14, %15, %16, %17, %18, %19, %20, %21, %22, %23, %24, %25, %26, %27, %28, %29, %30, %31, %32, %33, %34, %35, %36, %37, %38, %39, %40, %41, %42, %43, %44, %45, %46, %47, %48, %49, %50, %51, %52, %53, %54, %55, %56, %57, %58, %59, %60, %61, %62, %63, %64, %65, %66, %67}, "
    "%68, %69, p, 1, 1, 1, 0;\n}\n"
    : "+f"(d[0]), "+f"(d[1]), "+f"(d[2]), "+f"(d[3]), "+f"(d[4]), "+f"(d[5]), "+f"(d[6]), "+f"(d[7]), "+f"(d[8]), "+f"(d[9]), "+f"(d[10]), "+f"(d[11]), "+f"(d[12]), "+f"(d[13]), "+f"(d[14]), "+f"(d[15]), "+f"(d[16]), "+f"(d[17]), "+f"(d[18]), "+f"(d[19]), "+f"(d[20]), "+f"(d[21]), "+f"(d[22]), "+f"(d[23]), "+f"(d[24]), "+f"(d[25]), "+f"(d[26]), "+f"(d[27]), "+f"(d[28]), "+f"(d[29]), "+f"(d[30]), "+f"(d[31]), "+f"(d[32]), "+f"(d[33]), "+f"(d[34]), "+f"(d[35]), "+f"(d[36]), "+f"(d[37]), "+f"(d[38]), "+f"(d[39]), "+f"(d[40]), "+f"(d[41]), "+f"(d[42]), "+f"(d[43]), "+f"(d[44]), "+f"(d[45]), "+f"(d[46]), "+f"(d[47]), "+f"(d[48]), "+f"(d[49]), "+f"(d[50]), "+f"(d[51]), "+f"(d[52]), "+f"(d[53]), "+f"(d[54]), "+f"(d[55]), "+f"(d[56]), "+f"(d[57]), "+f"(d[58]), "+f"(d[59]), "+f"(d[60]), "+f"(d[61]), "+f"(d[62]), "+f"(d[63]), "+f"(d[64]), "+f"(d[65]), "+f"(d[66]), "+f"(d[67])
    : "l"(desca), "l"(descb), "r"(scale_d));
}
__device__ __forceinline__ void wgmma_qk_n64(float (&d)[32], uint32_t a0, uint32_t a1, uint32_t a2, uint32_t a3, uint64_t descb) {
  asm volatile("{\n.reg .pred p;\nsetp.ne.b32 p, 0, 0;\n"
    "wgmma.mma_async.sync.aligned.m64n64k16.f32.bf16.bf16 "
    "{%0, %1, %2, %3, %4, %5, %6, %7, %8, %9, %10, %11, %12, %13, %14, %15, %16, %17, %18, %19, %20, %21, %22, %23, %24, %25, %26, %27, %28, %29, %30, %31}, "
    "{%32, %33, %34, %35}, %36, p, 1, 1, 0;\n}\n"
    : "=f"(d[0]), "=f"(d[1]), "=f"(d[2]), "=f"(d[3]), "=f"(d[4]), "=f"(d[5]), "=f"(d[6]), "=f"(d[7]), "=f"(d[8]), "=f"(d[9]), "=f"(d[10]), "=f"(d[11]), "=f"(d[12]), "=f"(d[13]), "=f"(d[14]), "=f"(d[15]), "=f"(d[16]), "=f"(d[17]), "=f"(d[18]), "=f"(d[19]), "=f"(d[20]), "=f"(d[21]), "=f"(d[22]), "=f"(d[23]), "=f"(d[24]), "=f"(d[25]), "=f"(d[26]), "=f"(d[27]), "=f"(d[28]), "=f"(d[29]), "=f"(d[30]), "=f"(d[31])
    : "r"(a0), "r"(a1), "r"(a2), "r"(a3), "l"(descb));
}
__device__ __forceinline__ void wgmma_pv_n24(float (&d)[12], uint32_t a0, uint32_t a1, uint32_t a2, uint32_t a3, uint64_t descb) {
  asm volatile("{\n.reg .pred p;\nsetp.eq.b32 p, 0, 0;\n"
    "wgmma.mma_async.sync.aligned.m64n24k16.f32.bf16.bf16 "
    "{%0, %1, %2, %3, %4, %5, %6, %7, %8, %9, %10, %11}, "
    "{%12, %13, %14, %15}, %16, p, 1, 1, 1;\n}\n"
    : "+f"(d[0]), "+f"(d[1]), "+f"(d[2]), "+f"(d[3]), "+f"(d[4]), "+f"(d[5]), "+f"(d[6]), "+f"(d[7]), "+f"(d[8]), "+f"(d[9]), "+f"(d[10]), "+f"(d[11])
    : "r"(a0), "r"(a1), "r"(a2), "r"(a3), "l"(descb));
}
__device__ __forceinline__ void wgmma_k3_n64(float (&d)[32], uint64_t desca, uint64_t descb, int scale_d) {
  asm volatile("{\n.reg .pred p;\nsetp.ne.b32 p, %34, 0;\n"
    "wgmma.mma_async.sync.aligned.m64n64k16.f32.bf16.bf16 "
    "{%0, %1, %2, %3, %4, %5, %6, %7, %8, %9, %10, %11, %12, %13, %14, %15, %16, %17, %18, %19, %20, %21, %22, %23, %24, %25, %26, %27, %28, %29, %30, %31}, "
    "%32, %33, p, 1, 1, 0, 1;\n}\n"
    : "+f"(d[0]), "+f"(d[1]), "+f"(d[2]), "+f"(d[3]), "+f"(d[4]), "+f"(d[5]), "+f"(d[6]), "+f"(d[7]), "+f"(d[8]), "+f"(d[9]), "+f"(d[10]), "+f"(d[11]), "+f"(d[12]), "+f"(d[13]), "+f"(d[14]), "+f"(d[15]), "+f"(d[16]), "+f"(d[17]), "+f"(d[18]), "+f"(d[19]), "+f"(d[20]), "+f"(d[21]), "+f"(d[22]), "+f"(d[23]), "+f"(d[24]), "+f"(d[25]), "+f"(d[26]), "+f"(d[27]), "+f"(d[28]), "+f"(d[29]), "+f"(d[30]), "+f"(d[31])
    : "l"(desca), "l"(descb), "r"(scale_d));
}

constexpr int K1_XS = 17408;
constexpr int K1_WS = 24576;
constexpr int K1_ST = K1_XS + K1_WS;
constexpr int K1_NST = 5;
constexpr int K1_OFF_MISC = K1_NST * K1_ST;
constexpr int K1_SMEM = K1_OFF_MISC + 2048 + 1024;
constexpr int K1_OFF_BAR = 229376 + 1088;
constexpr float QSCALE = 0.25f * 1.4426950408889634f;

__device__ __forceinline__ void phase_qkv(const CUtensorMap& tm_x, const CUtensorMap& tm_w, const __nv_bfloat16* __restrict__ x,
                                          const uint32_t sb, uint8_t* sp, const unsigned int tag) {
    const uint32_t full = sb + K1_OFF_BAR;
    const uint32_t empty = full + 40;
    float* s_mr = (float*)(sp + K1_OFF_MISC + 256);

    const int tid = threadIdx.x, lane = tid & 31;
    const int warp = __shfl_sync(0xffffffffu, tid >> 5, 0);
    const int mt = blockIdx.x >> 3, nt = blockIdx.x & 7;
    if (tid == 384) {
        for (int i = 0; i < K1_NST; i++) { mbar_init(full + 8 * i, 1); mbar_init(empty + 8 * i, 3); }
        fence_barrier_init();
        for (int kb = 0; kb < K1_NST; kb++) {
            mbar_expect_tx(full + 8 * kb, 16384 + K1_WS);
            tma_load_2d(sb + kb * K1_ST, &tm_x, kb * 64, mt * 128, full + 8 * kb);
            tma_load_3d(sb + kb * K1_ST + K1_XS, &tm_w, nt * 64, kb * 64, 0, full + 8 * kb);
        }
    }
    if (tid < K1_NST * 64) {
        *(uint4*)(sp + (tid >> 6) * K1_ST + 16384 + (tid & 63) * 16) =
            make_uint4(0x3F803F80u, 0x3F803F80u, 0x3F803F80u, 0x3F803F80u);
    }
    fence_proxy_async();
    __syncthreads();

    if (warp == 12) {
        if (lane == 0) {
            for (int kb = K1_NST; kb < 8; kb++) {
                const int s = kb % K1_NST;
                mbar_wait(empty + 8 * s, 0);
                mbar_expect_tx(full + 8 * s, 16384 + K1_WS);
                tma_load_2d(sb + s * K1_ST, &tm_x, kb * 64, mt * 128, full + 8 * s);
                tma_load_3d(sb + s * K1_ST + K1_XS, &tm_w, nt * 64, kb * 64, 0, full + 8 * s);
            }
        }
        __syncwarp();
    } else if (warp == 13 || warp == 14) {
        const int r = tid - 416;
        {
            const int row = mt * 128 + nt * 16 + (r >> 2);
            const uint4* xp = (const uint4*)(x + (size_t)row * DM) + (r & 3);
            uint4 v[16];
#pragma unroll
            for (int i = 0; i < 16; i++) v[i] = __ldg(xp + i * 4);
            float s1 = 0.f;
#pragma unroll
            for (int i = 0; i < 16; i++)
                s1 += ((bf_lo(v[i].x) + bf_hi(v[i].x)) + (bf_lo(v[i].y) + bf_hi(v[i].y))) + ((bf_lo(v[i].z) + bf_hi(v[i].z)) + (bf_lo(v[i].w) + bf_hi(v[i].w)));
#pragma unroll
            for (int o = 1; o < 4; o <<= 1) s1 += __shfl_xor_sync(0xffffffffu, s1, o);
            const float mean = s1 * (1.f / DM);
            float q0 = 0.f, q1 = 0.f;
#pragma unroll
            for (int i = 0; i < 16; i++) {
                const uint32_t w[4] = {v[i].x, v[i].y, v[i].z, v[i].w};
#pragma unroll
                for (int j = 0; j < 4; j++) {
                    const float a = bf_lo(w[j]) - mean, b = bf_hi(w[j]) - mean;
                    q0 = fmaf(a, a, q0); q1 = fmaf(b, b, q1);
                }
            }
            float q = q0 + q1;
#pragma unroll
            for (int o = 1; o < 4; o <<= 1) q += __shfl_xor_sync(0xffffffffu, q, o);
            const float den = rbf(sqrtf(rbf(rbf(q * (1.f / DM)) + 1e-5f)));
            if ((r & 3) == 0)
                asm volatile("st.relaxed.gpu.global.v4.f32 [%0], {%1, %2, %3, %4};" ::"l"(g_ln1 + row), "f"(rbf(mean)), "f"(1.f / den),
                             "f"(__uint_as_float(tag)), "f"(0.f) : "memory");
        }
        if (r == 0) TSTAMP0(0, 6);
#pragma unroll
        for (int h2 = 0; h2 < 2; h2++) {
            const int rr = r + 64 * h2;
            float4 v;
            int spins = 0;
            do {
                asm volatile("ld.relaxed.gpu.global.v4.f32 {%0, %1, %2, %3}, [%4];" : "=f"(v.x), "=f"(v.y), "=f"(v.z), "=f"(v.w) : "l"(g_ln1 + mt * 128 + rr) : "memory");
            } while (__float_as_uint(v.z) != tag && ++spins < (1 << 22));
            s_mr[(rr >> 1) * 4 + (rr & 1)] = v.x;
            s_mr[(rr >> 1) * 4 + 2 + (rr & 1)] = v.y;
        }
        if (r == 0) TSTAMP0(0, 7);
        named_arrive(11, 448);
    } else if (warp < 12) {
        const int part = warp >> 2, hw = warp & 3;
        float acc[68];
#pragma unroll
        for (int i = 0; i < 68; i++) acc[i] = 0.f;
        fence_regs(acc);
#pragma unroll 1
        for (int kb = 0; kb < 8; kb++) {
            const int s = kb % K1_NST;
            mbar_wait(full + 8 * s, (kb / K1_NST) & 1);
            const uint64_t da = make_desc(sb + s * K1_ST + K1_XS + part * 8192, 1024, 1024, 1);
            const uint64_t db = make_desc(sb + s * K1_ST, 16, 1024, 1);
            wg_fence();
#pragma unroll
            for (int k = 0; k < 4; k++) wgmma_k1_n136(acc, da + k * 128, db + k * 2, (kb | k) != 0);
            wg_commit();
            if (kb > 0 && kb <= 8 - K1_NST) {
                wg_wait<1>();
                if ((tid & 127) == 0) mbar_arrive(empty + 8 * (kb - 1));
            }
        }
        wg_wait<0>();
        fence_regs(acc);
        if (tid == 0) TSTAMP0(0, 1);
        named_sync(11, 448);
        if (tid == 0) TSTAMP0(0, 2);

        const int t = lane & 3;
        const float cs0 = acc[64], cs1 = acc[66];
        const float sc = (part == 0) ? QSCALE : 1.f;
        const uint32_t stg = sb + (hw >> 1) * K1_ST + K1_XS + part * 8192 + (hw & 1) * 4096;
        const uint32_t st_addr = stg + ((lane >> 3) & 1) * 2048 + ((lane >> 4) * 8 + (lane & 7)) * 16;
#pragma unroll
        for (int j = 0; j < 16; j += 2) {
            uint32_t rr[4];
#pragma unroll
            for (int u = 0; u < 2; u++) {
                const int jj = j + u;
                const float4 mr = *(const float4*)(s_mr + (4 * jj + t) * 4);
                const float2 m2 = make_float2(mr.x, mr.y);
                const float ra = mr.z * sc, rb = mr.w * sc;
                rr[2 * u] = pack_bf16((acc[4 * jj] - m2.x * cs0) * ra, (acc[4 * jj + 1] - m2.y * cs0) * rb);
                rr[2 * u + 1] = pack_bf16((acc[4 * jj + 2] - m2.x * cs1) * ra, (acc[4 * jj + 3] - m2.y * cs1) * rb);
            }
            stmatrix_x4_trans(st_addr + j * 128, rr[0], rr[1], rr[2], rr[3]);
        }
        fence_proxy_async();
        __syncwarp();
        if (tid == 0) TSTAMP0(0, 4);
        const int head = nt * 4 + hw;
        if (lane == 0) {
            uint8_t* dst;
            uint32_t hstride;
            if (part == 0) { dst = g_q + (size_t)head * 65536 + mt * 2048; hstride = 32768; }
            else { dst = g_kv + (size_t)head * 131072 + (mt >> 1) * 16384 + (part - 1) * 8192 + (mt & 1) * 2048; hstride = 4096; }
            bulk_s2g(dst, stg, 2048);
            bulk_s2g(dst + hstride, stg + 2048, 2048);
            asm volatile("cp.async.bulk.commit_group;" ::: "memory");
        }
        float nmax = 0.f;
#pragma unroll
        for (int i = 0; i < 4; i++) {
            const int tok = lane + 32 * i;
            const uint4 a = *(const uint4*)(sp + (stg - sb) + tok * 16);
            const uint4 b = *(const uint4*)(sp + (stg - sb) + 2048 + tok * 16);
            uint32_t n0 = fma_bf16x2(a.x, a.x, 0u), n1 = fma_bf16x2(b.x, b.x, 0u);
            n0 = fma_bf16x2(a.y, a.y, n0); n1 = fma_bf16x2(b.y, b.y, n1);
            n0 = fma_bf16x2(a.z, a.z, n0); n1 = fma_bf16x2(b.z, b.z, n1);
            n0 = fma_bf16x2(a.w, a.w, n0); n1 = fma_bf16x2(b.w, b.w, n1);
            const float n2 = ((bf_lo(n0) + bf_hi(n0)) + (bf_lo(n1) + bf_hi(n1))) * 1.125f;
            nmax = (n2 > nmax || n2 != n2) ? n2 : nmax;
        }
#pragma unroll
        for (int o = 16; o > 0; o >>= 1) {
            const float v = __shfl_xor_sync(0xffffffffu, nmax, o);
            nmax = (v > nmax || v != v) ? v : nmax;
        }
        if (tid == 0) TSTAMP0(0, 5);
        if (lane == 0) {
            g_norm[(head * 16 + mt) * 3 + part] = nmax;
            asm volatile("cp.async.bulk.wait_group.read 0;" ::: "memory");
            if (tid == 0) TSTAMP0(0, 3);
        }
        __syncwarp();
    }
    __syncthreads();
    if (warp < 12 && lane == 0) {
        asm volatile("cp.async.bulk.wait_group 0;" ::: "memory");
        asm volatile("fence.proxy.async.global;" ::: "memory");
        asm volatile("red.release.gpu.global.add.u32 [%0], 1;" ::"l"(&g_kvflag[(nt * 16 + mt) * 8]) : "memory");
        if (tid == 0) TSTAMP0(0, 8);
    }
    __syncwarp();
}

#define POLL_NS 50
constexpr int KF_CH_G = 16384, KF_CH_S = 20480, KF_NCH = 8;
constexpr int KF_OFF_WO = KF_NCH * KF_CH_S;
constexpr int KF_OFF_MISC = KF_OFF_WO + 65536;
constexpr int KF_SMEM = KF_OFF_MISC + 1280 + 1024;

__device__ __forceinline__ uint32_t exp2_pair_poly(float s0, float s1) {
    const float KB = 65536.0f + 127.0f;
    const float t0 = s0 + KB, t1 = s1 + KB;
    const uint32_t w = __byte_perm(__float_as_uint(t0), __float_as_uint(t1), 0x5410);
    uint32_t z;
    asm("lop3.b32 %0, %1, %2, %3, 0xEA;" : "=r"(z) : "r"(w), "r"(0x007F007Fu), "r"(0x3F803F80u));
    uint32_t p = fma_bf16x2(0x3eab3eabu, z, 0xbc73bc73u);
    p = fma_bf16x2(p, z, 0x3f2f3f2fu);
    return p + w - z;
}
#define EMASK 0x5757u
constexpr uint32_t KF_EMASK = EMASK;
template <int LO, int HI>
__device__ __forceinline__ void softmax_part(const float (&s)[32], uint32_t (&p)[16]) {
#pragma unroll
    for (int i = LO; i < HI; i++) {
        if ((KF_EMASK >> i) & 1) p[i] = exp2_pair_poly(s[2 * i], s[2 * i + 1]);
        else p[i] = pack_bf16(ex2f(s[2 * i]), ex2f(s[2 * i + 1]));
    }
}
#define KF_PV(P, OFF)                                                                              \
    _Pragma("unroll") for (int kk = 0; kk < 4; kk++)                                               \
        wgmma_pv_n24(o, P[4 * kk], P[4 * kk + 1], P[4 * kk + 2], P[4 * kk + 3], dv + ((OFF) + kk * 16));

__device__ __forceinline__ uint32_t make_key(float r_bf16, int token) {
    const uint32_t u = __float_as_uint(r_bf16) >> 16;
    const uint32_t o = (u & 0x8000u) ? (~u & 0xFFFFu) : (u | 0x8000u);
    return (o << 16) | (uint32_t)(0xFFFF - token);
}
__device__ __forceinline__ float key_value(uint32_t k) {
    const uint32_t o = k >> 16;
    const uint32_t u = (o & 0x8000u) ? (o & 0x7FFFu) : (~o & 0xFFFFu);
    return __uint_as_float(u << 16);
}
__device__ __forceinline__ int key_token(uint32_t k) { return 0xFFFF - (int)(k & 0xFFFFu); }
__device__ __forceinline__ void warp_top2(uint32_t a, uint32_t b, uint32_t& k1, uint32_t& k2) {
    k1 = __reduce_max_sync(0xffffffffu, a > b ? a : b);
    const uint32_t a2 = (a == k1) ? 0u : a, b2 = (b == k1) ? 0u : b;
    k2 = __reduce_max_sync(0xffffffffu, a2 > b2 ? a2 : b2);
}
__device__ __forceinline__ unsigned int ld_acquire(const unsigned int* p) {
    unsigned int v; asm volatile("ld.acquire.gpu.global.u32 %0, [%1];" : "=r"(v) : "l"(p) : "memory"); return v;
}
__device__ __forceinline__ void red_release_add(unsigned int* p) {
    asm volatile("red.release.gpu.global.add.u32 [%0], 1;" ::"l"(p) : "memory");
}

__global__ void __launch_bounds__(512, 1)
kf_main(const __grid_constant__ CUtensorMap tm_x, const __grid_constant__ CUtensorMap tm_w,
        const __grid_constant__ CUtensorMap tm_o, const __grid_constant__ CUtensorMap tm_wo,
        const __grid_constant__ CUtensorMap tm_g, const __grid_constant__ CUtensorMap tm_u, const __grid_constant__ CUtensorMap tm_d,
        const __nv_bfloat16* __restrict__ x, const __nv_bfloat16* __restrict__ wo, const __nv_bfloat16* __restrict__ w_r,
        const __nv_bfloat16* __restrict__ w_gate, const __nv_bfloat16* __restrict__ w_up, const __nv_bfloat16* __restrict__ w_down,
        __nv_bfloat16* __restrict__ out) {
    extern __shared__ uint8_t smem_raw[];
    const uint32_t sraw = smem_u32(smem_raw);
    const uint32_t sb = (sraw + 1023) & ~1023u;
    uint8_t* sp = smem_raw + (sb - sraw);
    const uint32_t kvbar = sb + KF_OFF_MISC;
    const uint32_t wbar = kvbar + 64;
    const uint32_t obar = wbar + 64;
    const uint32_t gbar = obar + 64;
    const uint32_t dbar = gbar + 8;
    unsigned int* s_cnt = (unsigned int*)(sp + KF_OFF_MISC + 208);
    volatile unsigned int* s_order = (volatile unsigned int*)(sp + KF_OFF_MISC + 1056);
    uint32_t* s_key = (uint32_t*)(sp + KF_OFF_MISC + 256);
    float* s_gu = (float*)(sp + KF_OFF_MISC + 768);
    uint4* s_sel = (uint4*)(sp + KF_OFF_MISC + 1024);
    const int tid = threadIdx.x;
    const int head = blockIdx.x >> 2, quarter = blockIdx.x & 3;
    const int mt = blockIdx.x >> 2, nt = blockIdx.x & 3;
    if (tid == 0) TSTAMP0(0, 0);
    const unsigned int tag = *(volatile unsigned int*)&g_epoch + 1u;
    if (tid == 0) {
        for (int c = 0; c < 26; c++) mbar_init(kvbar + 8 * c, 1);
        for (int c = 0; c < 4; c++) s_cnt[c] = 0;
        fence_barrier_init();
    }
    phase_qkv(tm_x, tm_w, x, sb, sp, tag);
    const int warp_u = __shfl_sync(0xffffffffu, tid >> 5, 0);

    if (tid == 0) TSTAMP0(1, 0);
    const uint8_t* kvsrc = g_kv + (size_t)head * (KF_NCH * KF_CH_G);
    const unsigned int* kvf = g_kvflag + (head >> 2) * 16 * 8;
    if (warp_u >= 12) {
        for (int i = tid - 384; i < KF_NCH * 256; i += 128)
            *(uint4*)(sp + (i >> 8) * KF_CH_S + 16384 + (i & 255) * 16) =
                make_uint4(0x3F803F80u, 0x3F803F80u, 0x3F803F80u, 0x3F803F80u);
        fence_proxy_async();
        if (tid == 384) {
            for (int kb = 0; kb < 4; kb++) {
                mbar_expect_tx(wbar + 8 * kb, 16384);
                tma_load_3d(sb + KF_OFF_WO + kb * 16384, &tm_wo, 0, kb * 64, nt * 2, wbar + 8 * kb);
            }
        }
        if (tid == 416) {
            int spins = 0;
            while (((int)(ld_acquire(kvf) - 12u * tag) < 0 || (int)(ld_acquire(kvf + 8) - 12u * tag) < 0) && ++spins < (1 << 22)) {}
            asm volatile("fence.proxy.async.global;" ::: "memory");
            mbar_expect_tx(kvbar, KF_CH_G);
            bulk_g2s(sb, kvsrc, KF_CH_G, kvbar);
        }
        __syncwarp();
    }
    const int lane = tid & 31, g = lane >> 2, t = lane & 3;
    const int wg = warp_u >> 2, warp = warp_u & 3;
    if (warp_u == 0) {
        const int m16 = lane & 15;
        {
            int spins = 0;
            while (!__all_sync(0xffffffffu, (int)(ld_acquire(kvf + m16 * 8) - 12u * tag) >= 0) && ++spins < (1 << 22)) {}
        }
        if (tid == 0) TSTAMP0(1, 1);
        float kn = __ldcg(&g_norm[(head * 16 + m16) * 3 + 1]);
        float vn = __ldcg(&g_norm[(head * 16 + m16) * 3 + 2]);
        float qn = __ldcg(&g_norm[(head * 16 + quarter * 4 + (lane & 3)) * 3 + 0]);
        const bool bad = !(kn < 1e30f) || !(vn < 1e30f) || !(qn < 1e30f);
#pragma unroll
        for (int o = 8; o > 0; o >>= 1) {
            kn = fmaxf(kn, __shfl_xor_sync(0xffffffffu, kn, o));
            qn = fmaxf(qn, __shfl_xor_sync(0xffffffffu, qn, o));
        }
        const bool ok = __all_sync(0xffffffffu, !bad && (qn * kn <= 3500.f));
        if (lane == 0) s_cnt[4] = ok ? 1u : 0u;
    }
    __syncthreads();
    const bool fast = __all_sync(0xffffffffu, s_cnt[4] != 0u);
    uint32_t qn2[2][4];
#pragma unroll
    for (int ps = 0; ps < 2; ps++) {
        const uint8_t* qb = g_q + (size_t)head * 65536 + (quarter * 512 + ps * 256 + wg * 64 + warp * 16 + g) * 16 + t * 4;
        qn2[ps][0] = __ldcg((const uint32_t*)(qb));
        qn2[ps][1] = __ldcg((const uint32_t*)(qb + 128));
        qn2[ps][2] = __ldcg((const uint32_t*)(qb + 32768));
        qn2[ps][3] = __ldcg((const uint32_t*)(qb + 32768 + 128));
    }

    if (tid == 416) {
        asm volatile("fence.proxy.async.global;" ::: "memory");
        for (int c = 1; c < KF_NCH; c++) {
            mbar_expect_tx(kvbar + 8 * c, KF_CH_G);
            bulk_g2s(sb + c * KF_CH_S, kvsrc + c * KF_CH_G, KF_CH_G, kvbar + 8 * c);
        }
        prefetch_l2((const uint8_t*)wo + blockIdx.x * 4096, 4096);
        prefetch_l2((const uint8_t*)w_gate + blockIdx.x * 14336, 14336);
        prefetch_l2((const uint8_t*)w_up + blockIdx.x * 14336, 14336);
        prefetch_l2((const uint8_t*)w_down + blockIdx.x * 14336, 14336);
    }
    if (tid == 0) TSTAMP0(1, 8);
    const uint64_t dk0 = make_desc(sb, 4096, 128, 0);
    const uint64_t dv0 = make_desc(sb + 8192, 128, 4096, 0);

#pragma unroll 1
    for (int pass = 0; pass < 2; pass++) {
        const int row0 = quarter * 512 + pass * 256 + wg * 64 + warp * 16 + g;
        uint32_t qa[4];
#pragma unroll
        for (int i = 0; i < 4; i++) qa[i] = pass ? qn2[1][i] : qn2[0][i];
        float o[12];
#pragma unroll
        for (int i = 0; i < 12; i++) o[i] = 0.f;
        fence_regs(o);
#define KF_RELEASE_CHUNK(c)                                                                          \
        if (pass == 1 && (c) >= 1 && (c) <= 4) {                                                     \
            named_sync(4 + wg, 128);            \
            if ((tid & 127) == 0 && atomicAdd(&s_cnt[(c) - 1], 1u) == 3u) {                          \
                mbar_expect_tx(wbar + 8 * (3 + (c)), 16384);                                         \
                tma_load_3d(sb + ((c) - 1) * KF_CH_S, &tm_wo, 0, (3 + (c)) * 64, nt * 2, wbar + 8 * (3 + (c))); \
            }                                                                                        \
        }
        if (fast) {
#pragma unroll 1
            for (int c = 0; c < KF_NCH; c++) {
                const uint64_t dk = dk0 + (uint64_t)(c * (KF_CH_S >> 4));
                const uint64_t dv = dv0 + (uint64_t)(c * (KF_CH_S >> 4));
                float s0[32], s1[32], s2[32], s3[32];
                uint32_t p0[16], p1[16], p2[16], p3[16];
                mbar_wait(kvbar + 8 * c, 0);
                wg_wait<1>();
                wg_fence();
                wgmma_qk_n64(s0, qa[0], qa[1], qa[2], qa[3], dk);
                wg_commit();
                wg_wait<1>();
                KF_RELEASE_CHUNK(c);
                wg_fence();
                wgmma_qk_n64(s1, qa[0], qa[1], qa[2], qa[3], dk + 64);
                wg_commit();
                wg_wait<1>();
                fence_regs(s0);
                softmax_part<0, 16>(s0, p0);
                wg_fence();
                KF_PV(p0, 0);
                wg_commit();
                wg_wait<1>();
                fence_regs(s1);
                softmax_part<0, 8>(s1, p1);
                wg_wait<0>();
                wg_fence();
                wgmma_qk_n64(s2, qa[0], qa[1], qa[2], qa[3], dk + 128);
                wg_commit();
                softmax_part<8, 16>(s1, p1);
                wg_fence();
                KF_PV(p1, 64);
                wg_commit();
                wg_wait<1>();
                fence_regs(s2);
                softmax_part<0, 8>(s2, p2);
                wg_wait<0>();
                wg_fence();
                wgmma_qk_n64(s3, qa[0], qa[1], qa[2], qa[3], dk + 192);
                wg_commit();
                softmax_part<8, 16>(s2, p2);
                wg_fence();
                KF_PV(p2, 128);
                wg_commit();
                wg_wait<1>();
                fence_regs(s3);
                softmax_part<0, 16>(s3, p3);
                wg_fence();
                KF_PV(p3, 192);
                wg_commit();
            }
            wg_wait<0>();
            fence_regs(o);
        } else {
            float m0 = -INFINITY, m1 = -INFINITY;
#pragma unroll 1
            for (int b = 0; b < 32; b++) {
                const int c = b >> 2;
                const uint64_t dk = dk0 + (uint64_t)(c * (KF_CH_S >> 4) + (b & 3) * 64);
                const uint64_t dv = dv0 + (uint64_t)(c * (KF_CH_S >> 4) + (b & 3) * 64);
                float s[32];
                uint32_t p[16];
                mbar_wait(kvbar + 8 * c, 0);
                wg_fence();
                wgmma_qk_n64(s, qa[0], qa[1], qa[2], qa[3], dk);
                wg_commit();
                if ((b & 3) == 0) { KF_RELEASE_CHUNK(c); }
                wg_wait<0>();
                fence_regs(s);
                float x0 = s[0], x1 = s[2];
#pragma unroll
                for (int j = 0; j < 8; j++) {
                    x0 = fmaxf(x0, fmaxf(s[4 * j], s[4 * j + 1]));
                    x1 = fmaxf(x1, fmaxf(s[4 * j + 2], s[4 * j + 3]));
                }
                x0 = fmaxf(x0, __shfl_xor_sync(0xffffffffu, x0, 1));
                x0 = fmaxf(x0, __shfl_xor_sync(0xffffffffu, x0, 2));
                x1 = fmaxf(x1, __shfl_xor_sync(0xffffffffu, x1, 1));
                x1 = fmaxf(x1, __shfl_xor_sync(0xffffffffu, x1, 2));
                const float n0 = fmaxf(m0, x0), n1 = fmaxf(m1, x1);
                const float c0 = ex2f(m0 - n0), c1 = ex2f(m1 - n1);
                m0 = n0; m1 = n1;
#pragma unroll
                for (int j = 0; j < 3; j++) {
                    o[4 * j] *= c0; o[4 * j + 1] *= c0; o[4 * j + 2] *= c1; o[4 * j + 3] *= c1;
                }
#pragma unroll
                for (int j = 0; j < 8; j++) {
                    p[2 * j] = pack_bf16(ex2f(s[4 * j] - n0), ex2f(s[4 * j + 1] - n0));
                    p[2 * j + 1] = pack_bf16(ex2f(s[4 * j + 2] - n1), ex2f(s[4 * j + 3] - n1));
                }
                fence_regs(o);
                wg_fence();
                KF_PV(p, 0);
                wg_commit();
                wg_wait<0>();
                fence_regs(o);
            }
        }
        const float inv0 = 1.f / o[8], inv1 = 1.f / o[10];
        {
            uint32_t v0 = pack_bf16(o[0] * inv0, o[1] * inv0), v1 = pack_bf16(o[4] * inv0, o[5] * inv0);
            uint32_t v2 = pack_bf16(o[2] * inv1, o[3] * inv1), v3 = pack_bf16(o[6] * inv1, o[7] * inv1);
            const bool o1 = t & 1, o2 = t & 2;
            uint32_t s0 = o1 ? v0 : v1, s1 = o1 ? v2 : v3;
            s0 = __shfl_xor_sync(0xffffffffu, s0, 1); s1 = __shfl_xor_sync(0xffffffffu, s1, 1);
            uint32_t a0 = o1 ? s0 : v0, a1 = o1 ? v1 : s0, b0 = o1 ? s1 : v2, b1 = o1 ? v3 : s1;
            uint32_t x0 = o2 ? a0 : b0, x1 = o2 ? a1 : b1;
            x0 = __shfl_xor_sync(0xffffffffu, x0, 2); x1 = __shfl_xor_sync(0xffffffffu, x1, 2);
            uint4 r;
            r.x = o2 ? x0 : a0; r.y = o2 ? x1 : a1; r.z = o2 ? b0 : x0; r.w = o2 ? b1 : x1;
            *(uint4*)(g_o + (size_t)(row0 + (t >> 1) * 8) * DM + head * 16 + (t & 1) * 8) = r;
        }
        if (tid == 0) TSTAMP0(1, 4 + pass);
    }
    if (warp_u != 10) named_arrive(1, 512);
    named_sync(4 + wg, 128);
    if ((tid & 127) == 0) {
        asm volatile("fence.acq_rel.gpu;" ::: "memory");
        asm volatile("red.relaxed.gpu.global.add.u32 [%0], 1;" ::"l"(&g_oflag[(quarter * 8 + 4 + wg) * 32 + (head >> 2) * 4]) : "memory");
        asm volatile("red.relaxed.gpu.global.add.u32 [%0], 1;" ::"l"(&g_oflag[(quarter * 8 + wg) * 32 + (head >> 2) * 4]) : "memory");
    }
    if (tid == 0) TSTAMP0(1, 3);

    if (wg < 2) {
        const int wi = warp;
        const int r0 = mt * 64 + wi * 16 + g;
        const int cb = nt * 128 + wg * 64;
        uint32_t xr[16], wr[8];
#pragma unroll
        for (int j = 0; j < 8; j++) {
            xr[2 * j] = __ldg((const uint32_t*)(x + (size_t)r0 * DM + cb + 8 * j + 2 * t));
            xr[2 * j + 1] = __ldg((const uint32_t*)(x + (size_t)(r0 + 8) * DM + cb + 8 * j + 2 * t));
            wr[j] = __ldg((const uint32_t*)(w_r + cb + 8 * j + 2 * t));
        }
        float wsum = 0.f;
        {
            const uint4 a = __ldg((const uint4*)(w_r + lane * 16)), b = __ldg((const uint4*)(w_r + lane * 16 + 8));
            const uint32_t w[8] = {a.x, a.y, a.z, a.w, b.x, b.y, b.z, b.w};
#pragma unroll
            for (int i = 0; i < 8; i++) wsum += bf_lo(w[i]) + bf_hi(w[i]);
#pragma unroll
            for (int o = 16; o > 0; o >>= 1) wsum += __shfl_xor_sync(0xffffffffu, wsum, o);
        }
        float acc[32];
#pragma unroll
        for (int i = 0; i < 32; i++) acc[i] = 0.f;
        fence_regs(acc);
#pragma unroll 1
        for (int i = 0; i < 8; i++) {
            mbar_wait(obar + 8 * i, 0);
            const int kb = __shfl_sync(0xffffffffu, (int)s_order[i], 0);
            mbar_wait(wbar + 8 * kb, 0);
            const uint32_t wa = (kb < 4) ? (KF_OFF_WO + kb * 16384) : ((kb - 4) * KF_CH_S);
            const uint64_t da = make_desc(sb + (4 + (kb >> 1)) * KF_CH_S + (kb & 1) * 8192, 16, 1024, 1);
            const uint64_t db = make_desc(sb + wa + wg * 8192, 1024, 1024, 1);
            wg_fence();
#pragma unroll
            for (int k = 0; k < 4; k++) wgmma_k3_n64(acc, da + k * 2, db + k * 128, (i | k) != 0);
            wg_commit();
        }
        wg_wait<0>();
        fence_regs(acc);
        if (tid == 0) TSTAMP0(2, 2);
        float hv[32];
        uint32_t hp[16];
        float s0 = 0.f, s1 = 0.f, d0 = 0.f, d1 = 0.f;
#pragma unroll
        for (int j = 0; j < 8; j++) {
            const uint32_t a01 = pack_bf16(acc[4 * j], acc[4 * j + 1]), a23 = pack_bf16(acc[4 * j + 2], acc[4 * j + 3]);
            hp[2 * j] = pack_bf16(bf_lo(xr[2 * j]) + bf_lo(a01), bf_hi(xr[2 * j]) + bf_hi(a01));
            hp[2 * j + 1] = pack_bf16(bf_lo(xr[2 * j + 1]) + bf_lo(a23), bf_hi(xr[2 * j + 1]) + bf_hi(a23));
            hv[4 * j] = bf_lo(hp[2 * j]); hv[4 * j + 1] = bf_hi(hp[2 * j]);
            hv[4 * j + 2] = bf_lo(hp[2 * j + 1]); hv[4 * j + 3] = bf_hi(hp[2 * j + 1]);
            const float wl = bf_lo(wr[j]), wh = bf_hi(wr[j]);
            s0 += hv[4 * j] + hv[4 * j + 1];
            s1 += hv[4 * j + 2] + hv[4 * j + 3];
            d0 = fmaf(hv[4 * j], wl, fmaf(hv[4 * j + 1], wh, d0));
            d1 = fmaf(hv[4 * j + 2], wl, fmaf(hv[4 * j + 3], wh, d1));
        }
        float mu0 = s0 * (1.f / 16), mu1 = s1 * (1.f / 16);
        float q0 = 0.f, q1 = 0.f;
#pragma unroll
        for (int j = 0; j < 8; j++) {
            float a = hv[4 * j] - mu0, b = hv[4 * j + 1] - mu0, c = hv[4 * j + 2] - mu1, d = hv[4 * j + 3] - mu1;
            q0 = fmaf(a, a, fmaf(b, b, q0));
            q1 = fmaf(c, c, fmaf(d, d, q1));
        }
#pragma unroll
        for (int o = 1; o < 4; o <<= 1) {
            const float m0 = __shfl_xor_sync(0xffffffffu, mu0, o), m1 = __shfl_xor_sync(0xffffffffu, mu1, o);
            const float e0 = __shfl_xor_sync(0xffffffffu, q0, o), e1 = __shfl_xor_sync(0xffffffffu, q1, o);
            d0 += __shfl_xor_sync(0xffffffffu, d0, o);
            d1 += __shfl_xor_sync(0xffffffffu, d1, o);
            const float f0 = mu0 - m0, f1 = mu1 - m1;
            q0 = q0 + e0 + f0 * f0 * (8.f * o);
            q1 = q1 + e1 + f1 * f1 * (8.f * o);
            mu0 = 0.5f * (mu0 + m0); mu1 = 0.5f * (mu1 + m1);
        }
        float4* part = g_part + (size_t)mt * 512 + wi * 16 + g;
        if (t < 2) {
            float4* dst = part + (nt * 2 + wg) * 64 + t * 8;
            const float a = t ? mu1 : mu0, b = t ? q1 : q0, c = t ? d1 : d0;
            asm volatile("st.relaxed.gpu.global.v4.f32 [%0], {%1, %2, %3, %4};" ::"l"(dst), "f"(a), "f"(b), "f"(c), "f"(__uint_as_float(tag)) : "memory");
        }
        if (tid == 0) TSTAMP0(2, 5);
        const uint32_t stg_off = KF_OFF_WO + (wi >> 1) * 16384 + wg * 8192 + (wi & 1) * 4096;
        const uint32_t stg_o = sb + stg_off, stg_h = stg_o + 2048;
        const int srow = (lane & 7) + ((lane >> 3) & 1) * 8;
        const int sj = lane >> 4;
        named_sync(4 + wg, 128);
#pragma unroll
        for (int j = 0; j < 8; j += 2) {
            const uint32_t off = srow * 128 + (((j + sj) ^ (srow & 7)) << 4);
            stmatrix_x4(stg_h + off, hp[2 * j], hp[2 * j + 1], hp[2 * j + 2], hp[2 * j + 3]);
        }
        __syncwarp();
#pragma unroll
        for (int i = 0; i < 4; i++) {
            const int row = i * 4 + (lane >> 3), ch = lane & 7;
            const uint4 vh = *(const uint4*)(sp + stg_off + 2048 + row * 128 + ((ch ^ (row & 7)) << 4));
            *(uint4*)(g_h + (size_t)(mt * 64 + wi * 16 + row) * DM + cb + ch * 8) = vh;
        }
        named_arrive(8, 288);
        if (tid == 0) TSTAMP0(2, 6);
        float mean[2], den[2], rr[2];
        {
            float4 v[4];
            int spins = 0;
            while (true) {
#pragma unroll
                for (int i = 0; i < 4; i++) {
                    const float4* p = part + (t + (i & 1) * 4) * 64 + (i >> 1) * 8;
                    asm volatile("ld.relaxed.gpu.global.v4.f32 {%0, %1, %2, %3}, [%4];" : "=f"(v[i].x), "=f"(v[i].y), "=f"(v[i].z), "=f"(v[i].w) : "l"(p) : "memory");
                }
                const bool ok = (__float_as_uint(v[0].w) == tag) && (__float_as_uint(v[1].w) == tag) && (__float_as_uint(v[2].w) == tag) && (__float_as_uint(v[3].w) == tag);
                if (__all_sync(0xffffffffu, ok) || ++spins > (1 << 22)) break;
            }
#pragma unroll
            for (int u = 0; u < 2; u++) {
                float mu = v[2 * u].x + v[2 * u + 1].x, m2 = v[2 * u].y + v[2 * u + 1].y, hw = v[2 * u].z + v[2 * u + 1].z;
#pragma unroll
                for (int o = 1; o < 4; o <<= 1) {
                    mu += __shfl_xor_sync(0xffffffffu, mu, o);
                    m2 += __shfl_xor_sync(0xffffffffu, m2, o);
                    hw += __shfl_xor_sync(0xffffffffu, hw, o);
                }
                mu *= 0.125f;
                const float da = v[2 * u].x - mu, db = v[2 * u + 1].x - mu;
                float dd = 64.f * (da * da + db * db);
#pragma unroll
                for (int o = 1; o < 4; o <<= 1) dd += __shfl_xor_sync(0xffffffffu, dd, o);
                m2 += dd;
                mean[u] = rbf(mu);
                den[u] = rbf(sqrtf(rbf(rbf(m2 * (1.f / DM)) + 1e-5f)));
                rr[u] = rbf((hw - mean[u] * wsum) / den[u]);
            }
        }
        if (tid == 0) TSTAMP0(2, 3);
        named_arrive(3, 512);
        if (nt == 0 && wg == 0) {
            float2* s_st = (float2*)(sp + KF_OFF_WO + 49152);
            if (t == 0) {
                s_key[wi * 16 + g] = make_key(rr[0], r0);
                s_key[wi * 16 + g + 8] = make_key(rr[1], r0 + 8);
                s_st[wi * 16 + g] = make_float2(mean[0], den[0]);
                s_st[wi * 16 + g + 8] = make_float2(mean[1], den[1]);
            }
            named_sync(4, 128);
            if (warp == 0) {
                uint32_t k1, k2;
                warp_top2(s_key[lane], s_key[lane + 32], k1, k2);
                if (lane < 2) {
                    const uint32_t k = lane ? k2 : k1;
                    const float2 st = s_st[key_token(k) & 63];
                    asm volatile("st.relaxed.gpu.global.v4.u32 [%0], {%1, %2, %3, %4};" ::"l"(g_cand + mt * 2 + lane), "r"(k),
                                 "r"(tag), "r"(__float_as_uint(st.x)), "r"(__float_as_uint(st.y)) : "memory");
                }
            }
        }
        const float i0 = 1.f / den[0], i1 = 1.f / den[1];
#pragma unroll
        for (int j = 0; j < 8; j += 2) {
            uint32_t ro[4];
#pragma unroll
            for (int u = 0; u < 2; u++) {
                const int jj = j + u;
                const float a = hv[4 * jj], b = hv[4 * jj + 1], c = hv[4 * jj + 2], d = hv[4 * jj + 3];
                const uint32_t u01 = pack_bf16(a - mean[0], b - mean[0]), u23 = pack_bf16(c - mean[1], d - mean[1]);
                const uint32_t n01 = pack_bf16(bf_lo(u01) * i0, bf_hi(u01) * i0), n23 = pack_bf16(bf_lo(u23) * i1, bf_hi(u23) * i1);
                ro[2 * u] = pack_bf16(a + bf_lo(n01), b + bf_hi(n01));
                ro[2 * u + 1] = pack_bf16(c + bf_lo(n23), d + bf_hi(n23));
            }
            const uint32_t off = srow * 128 + (((j + sj) ^ (srow & 7)) << 4);
            stmatrix_x4(stg_o + off, ro[0], ro[1], ro[2], ro[3]);
        }
        __syncwarp();
#pragma unroll
        for (int i = 0; i < 4; i++) {
            const int row = i * 4 + (lane >> 3), ch = lane & 7;
            const uint4 vo = *(const uint4*)(sp + stg_off + row * 128 + ((ch ^ (row & 7)) << 4));
            *(uint4*)(out + (size_t)(mt * 64 + wi * 16 + row) * DM + cb + ch * 8) = vo;
        }
        named_sync(4 + wg, 128);
        if ((tid & 127) == 0) red_release_add(&g_sflag[mt]);
        if (tid == 0) TSTAMP0(2, 4);
    } else {
        const bool worker = blockIdx.x < FF / 16;
        const bool downer = blockIdx.x >= 64;
        const int mtid = tid - 256, mwarp = warp_u - 8;
        const int c0 = (blockIdx.x - 64) * 8;
        float* s_x = (float*)(sp + KF_OFF_WO + 49152 + 8192);
        float* s_red = (float*)(sp + KF_OFF_WO + 49152 + 8192 + 4096);
        if (mwarp == 2) {
            named_sync(1, 512);
            uint32_t done = 0;
            int n = 0, spins = 0;
            while (done != 0xFFu && ++spins < (1 << 22)) {
                const bool rdy = lane < 8 && (int)(ld_acquire(&g_oflag[mt * 32 + lane * 4]) - 4u * tag) >= 0;
                uint32_t todo = __ballot_sync(0xffffffffu, rdy) & ~done;
                done |= todo;
                if (todo && lane == 0) {
                    asm volatile("fence.proxy.async.global;" ::: "memory");
                    while (todo) {
                        const int kb = __ffs(todo) - 1;
                        todo &= todo - 1;
                        s_order[n] = kb;
                        mbar_expect_tx(obar + 8 * n, 8192);
                        tma_load_3d(sb + (4 + (kb >> 1)) * KF_CH_S + (kb & 1) * 8192, &tm_o, 0, mt * 64, kb, obar + 8 * n);
                        n++;
                    }
                }
                n = __shfl_sync(0xffffffffu, n, 0);
                if (done != 0xFFu) __nanosleep(POLL_NS);
            }
            if (lane == 0) TSTAMP0(2, 1);
            if (lane == 0 && worker) {
                mbar_expect_tx(gbar, 32768);
                for (int i = 0; i < 4; i++) {
                    tma_load_2d(sb + i * KF_CH_S + 16384, &tm_g, blockIdx.x * 16, i * 128, gbar);
                    tma_load_2d(sb + (4 + i) * KF_CH_S + 16384, &tm_u, blockIdx.x * 16, i * 128, gbar);
                }
            }
        }
        if (mwarp == 1) {
            named_sync(8, 288);
            if (lane == 0) {
                red_release_add(&g_hflag[mt]);
                if (downer) {
                    mbar_expect_tx(dbar, 7 * 4096);
                    for (int i = 0; i < 7; i++) tma_load_2d(sb + (4 + (i >> 2)) * KF_CH_S + (i & 3) * 4096, &tm_d, c0, i * 256, dbar);
                }
            }
            __syncwarp();
        }
        if (mtid == 0) TSTAMP0(3, 0);
        named_sync(3, 512);
        if (mwarp == 0) {
            uint4 ca, cb4;
            int spins = 0;
            while (true) {
                asm volatile("ld.relaxed.gpu.global.v4.u32 {%0, %1, %2, %3}, [%4];" : "=r"(ca.x), "=r"(ca.y), "=r"(ca.z), "=r"(ca.w) : "l"(g_cand + 2 * lane) : "memory");
                asm volatile("ld.relaxed.gpu.global.v4.u32 {%0, %1, %2, %3}, [%4];" : "=r"(cb4.x), "=r"(cb4.y), "=r"(cb4.z), "=r"(cb4.w) : "l"(g_cand + 2 * lane + 1) : "memory");
                const unsigned int hf = ld_acquire(&g_hflag[lane]);
                const bool ok = ca.y == tag && cb4.y == tag && (int)(hf - 4u * tag) >= 0;
                if (__all_sync(0xffffffffu, ok) || ++spins > (1 << 22)) break;
            }
            uint32_t k1, k2;
            warp_top2(ca.x, cb4.x, k1, k2);
            if (ca.x == k1) s_sel[0] = ca;
            if (cb4.x == k1) s_sel[0] = cb4;
            if (ca.x == k2) s_sel[1] = ca;
            if (cb4.x == k2) s_sel[1] = cb4;
        }
        named_sync(2, 256);
        if (mtid == 0) TSTAMP0(3, 1);
        int idx[2];
        float mean[2], inv[2], rv[2];
#pragma unroll
        for (int u = 0; u < 2; u++) {
            const uint4 c = s_sel[u];
            idx[u] = key_token(c.x);
            rv[u] = key_value(c.x);
            mean[u] = __uint_as_float(c.z);
            inv[u] = 1.f / __uint_as_float(c.w);
        }
        float hfin = 0.f;
        if (downer && mtid < 16) hfin = __bfloat162float(__ldcg((const __nv_bfloat16*)(g_h + (size_t)((mtid >> 3) ? idx[1] : idx[0]) * DM + c0 + (mtid & 7))));
        if (worker) {
            {
                const uint32_t h0 = __ldcg((const uint32_t*)(g_h + (size_t)idx[0] * DM + 2 * mtid));
                const uint32_t h1 = __ldcg((const uint32_t*)(g_h + (size_t)idx[1] * DM + 2 * mtid));
                const uint32_t u0 = pack_bf16(bf_lo(h0) - mean[0], bf_hi(h0) - mean[0]), u1 = pack_bf16(bf_lo(h1) - mean[1], bf_hi(h1) - mean[1]);
                const uint32_t n0 = pack_bf16(bf_lo(u0) * inv[0], bf_hi(u0) * inv[0]), n1 = pack_bf16(bf_lo(u1) * inv[1], bf_hi(u1) * inv[1]);
                *(float4*)(s_x + 4 * mtid) = make_float4(bf_lo(n0), bf_lo(n1), bf_hi(n0), bf_hi(n1));
            }
            if (mtid == 0) TSTAMP0(3, 5);
            mbar_wait(gbar, 0);
            named_sync(2, 256);
            if (mtid == 0) TSTAMP0(3, 6);
            float acc[8];
#pragma unroll
            for (int i = 0; i < 8; i++) acc[i] = 0.f;
            const uint8_t* wbase = sp + (mwarp >> 2) * (4 * KF_CH_S) + 16384 + lane * 32 + (mwarp & 3) * 8;
#pragma unroll
            for (int k = 0; k < 16; k++) {
                const uint2 w = *(const uint2*)(wbase + (k >> 2) * KF_CH_S + (k & 3) * 1024);
                const float2 xx = *(const float2*)(s_x + 2 * (lane + 32 * k));
                const float x0 = xx.x, x1 = xx.y;
                const float w0 = bf_lo(w.x), w1 = bf_hi(w.x), w2 = bf_lo(w.y), w3 = bf_hi(w.y);
                acc[0] = fmaf(x0, w0, acc[0]); acc[1] = fmaf(x0, w1, acc[1]); acc[2] = fmaf(x0, w2, acc[2]); acc[3] = fmaf(x0, w3, acc[3]);
                acc[4] = fmaf(x1, w0, acc[4]); acc[5] = fmaf(x1, w1, acc[5]); acc[6] = fmaf(x1, w2, acc[6]); acc[7] = fmaf(x1, w3, acc[7]);
            }
#define KF_STEP(O, N)                                                          \
            {                                                                  \
                const bool up = (lane & (O)) != 0;                             \
                _Pragma("unroll") for (int i = 0; i < (N); i++) {              \
                    const float send = up ? acc[i] : acc[i + (N)];             \
                    const float keep = up ? acc[i + (N)] : acc[i];             \
                    acc[i] = keep + __shfl_xor_sync(0xffffffffu, send, (O));   \
                }                                                              \
            }
            KF_STEP(16, 4) KF_STEP(8, 2) KF_STEP(4, 1)
            acc[0] += __shfl_xor_sync(0xffffffffu, acc[0], 2);
            acc[0] += __shfl_xor_sync(0xffffffffu, acc[0], 1);
            if ((lane & 3) == 0) {
                const int v = ((lane & 16) ? 4 : 0) + ((lane & 8) ? 2 : 0) + ((lane & 4) ? 1 : 0);
                s_gu[(v >> 2) * 32 + mwarp * 4 + (v & 3)] = acc[0];
            }
            named_sync(2, 256);
            if (mtid < 16) {
                uint32_t a2 = 0;
#pragma unroll
                for (int u = 0; u < 2; u++) {
                    const float gb = rbf(s_gu[u * 32 + mtid]);
                    const float sg = rbf(gb / (1.f + __expf(-gb)));
                    float a = sg * rbf(s_gu[u * 32 + 16 + mtid]);
                    a2 |= (uint32_t)__bfloat16_as_ushort(__float2bfloat16_rn(a)) << (16 * u);
                }
                asm volatile("st.relaxed.gpu.global.v2.u32 [%0], {%1, %2};" ::"l"(g_act + blockIdx.x * 16 + mtid), "r"(a2), "r"(tag) : "memory");
            }
            if (mtid == 0) TSTAMP0(3, 2);
        }
        if (downer) {
            uint32_t av[7];
            {
                int spins = 0;
                while (true) {
                    bool ok = true;
#pragma unroll
                    for (int j = 0; j < 7; j++) {
                        uint32_t tg;
                        asm volatile("ld.relaxed.gpu.global.v2.u32 {%0, %1}, [%2];" : "=r"(av[j]), "=r"(tg) : "l"(g_act + mtid + 256 * j) : "memory");
                        ok = ok && tg == tag;
                    }
                    if (mtid < 2) ok = ok && ((int)(ld_acquire(&g_sflag[(mtid ? idx[1] : idx[0]) >> 6]) - 8u * tag) >= 0);
                    if (__all_sync(0xffffffffu, ok) || ++spins > (1 << 20)) break;
                    __nanosleep(20);
                }
            }
            if (mtid == 0) TSTAMP0(3, 3);
            mbar_wait(dbar, 0);
            float acc[16];
#pragma unroll
            for (int i = 0; i < 16; i++) acc[i] = 0.f;
#pragma unroll
            for (int j = 0; j < 7; j++) {
                const uint4 w = *(const uint4*)(sp + (4 + (j >> 2)) * KF_CH_S + (j & 3) * 4096 + mtid * 16);
                const float a0 = bf_lo(av[j]), a1 = bf_hi(av[j]);
                const uint32_t ww[4] = {w.x, w.y, w.z, w.w};
#pragma unroll
                for (int q = 0; q < 4; q++) {
                    const float wl = bf_lo(ww[q]), wh = bf_hi(ww[q]);
                    acc[2 * q] = fmaf(a0, wl, acc[2 * q]); acc[2 * q + 1] = fmaf(a0, wh, acc[2 * q + 1]);
                    acc[8 + 2 * q] = fmaf(a1, wl, acc[8 + 2 * q]); acc[8 + 2 * q + 1] = fmaf(a1, wh, acc[8 + 2 * q + 1]);
                }
            }
            KF_STEP(16, 8) KF_STEP(8, 4) KF_STEP(4, 2) KF_STEP(2, 1)
            acc[0] += __shfl_xor_sync(0xffffffffu, acc[0], 1);
            if ((lane & 1) == 0) {
                const int v = ((lane & 16) ? 8 : 0) + ((lane & 8) ? 4 : 0) + ((lane & 4) ? 2 : 0) + ((lane & 2) ? 1 : 0);
                s_red[mwarp * 16 + v] = acc[0];
            }
            named_sync(2, 256);
            if (mtid < 16) {
                const int u = mtid >> 3;
                float y = 0.f;
#pragma unroll
                for (int w = 0; w < 8; w++) y += s_red[w * 16 + mtid];
                const float sig = rbf(1.f / (1.f + __expf(-(u ? rv[1] : rv[0]))));
                const float xn = rbf(rbf(hfin - (u ? mean[1] : mean[0])) * (u ? inv[1] : inv[0]));
                const float ov = hfin + rbf(xn + rbf(rbf(y) * sig));
                out[(size_t)(u ? idx[1] : idx[0]) * DM + c0 + (mtid & 7)] = __float2bfloat16_rn(ov);
            }
            if (blockIdx.x == gridDim.x - 1 && mtid == 0) g_epoch = tag;
            if (mtid == 0) TSTAMP0(3, 4);
        }
    }
}

typedef CUresult (*PFN_encodeTiled)(CUtensorMap*, CUtensorMapDataType, cuuint32_t, void*, const cuuint64_t*, const cuuint64_t*,
                                    const cuuint32_t*, const cuuint32_t*, CUtensorMapInterleave, CUtensorMapSwizzle,
                                    CUtensorMapL2promotion, CUtensorMapFloatOOBfill);

void make_map(PFN_encodeTiled enc, CUtensorMap* m, const void* ptr, uint64_t cols, uint64_t rows, uint32_t bcols, uint32_t brows) {
    cuuint64_t dims[2] = {cols, rows};
    cuuint64_t strides[1] = {cols * 2};
    cuuint32_t box[2] = {bcols, brows};
    cuuint32_t es[2] = {1, 1};
    enc(m, CU_TENSOR_MAP_DATA_TYPE_BFLOAT16, 2, const_cast<void*>(ptr), dims, strides, box, es, CU_TENSOR_MAP_INTERLEAVE_NONE,
        CU_TENSOR_MAP_SWIZZLE_128B, CU_TENSOR_MAP_L2_PROMOTION_L2_256B, CU_TENSOR_MAP_FLOAT_OOB_FILL_NONE);
}

void make_map3(PFN_encodeTiled enc, CUtensorMap* m, const void* ptr, uint64_t d0, uint64_t rows, uint64_t d2, uint64_t row_stride_bytes,
               uint64_t d2_stride_bytes, uint32_t b0, uint32_t b1, uint32_t b2) {
    cuuint64_t dims[3] = {d0, rows, d2};
    cuuint64_t strides[2] = {row_stride_bytes, d2_stride_bytes};
    cuuint32_t box[3] = {b0, b1, b2};
    cuuint32_t es[3] = {1, 1, 1};
    enc(m, CU_TENSOR_MAP_DATA_TYPE_BFLOAT16, 3, const_cast<void*>(ptr), dims, strides, box, es, CU_TENSOR_MAP_INTERLEAVE_NONE,
        CU_TENSOR_MAP_SWIZZLE_128B, CU_TENSOR_MAP_L2_PROMOTION_L2_256B, CU_TENSOR_MAP_FLOAT_OOB_FILL_NONE);
}

void make_map_plain(PFN_encodeTiled enc, CUtensorMap* m, const void* ptr, uint64_t cols, uint64_t rows, uint32_t bcols, uint32_t brows) {
    cuuint64_t dims[2] = {cols, rows};
    cuuint64_t strides[1] = {cols * 2};
    cuuint32_t box[2] = {bcols, brows};
    cuuint32_t es[2] = {1, 1};
    enc(m, CU_TENSOR_MAP_DATA_TYPE_BFLOAT16, 2, const_cast<void*>(ptr), dims, strides, box, es, CU_TENSOR_MAP_INTERLEAVE_NONE,
        CU_TENSOR_MAP_SWIZZLE_NONE, CU_TENSOR_MAP_L2_PROMOTION_NONE, CU_TENSOR_MAP_FLOAT_OOB_FILL_NONE);
}

template <typename... KArgs, typename... Args>
void launch(void (*kern)(KArgs...), int grid, int block, int smem, bool pdl, Args... args) {
    cudaLaunchConfig_t cfg = {};
    cfg.gridDim = dim3(grid);
    cfg.blockDim = dim3(block);
    cfg.dynamicSmemBytes = smem;
    cfg.stream = cudaStreamPerThread;
    cudaLaunchAttribute at[1];
    at[0].id = cudaLaunchAttributeProgrammaticStreamSerialization;
    at[0].val.programmaticStreamSerializationAllowed = 1;
    cfg.attrs = at;
    cfg.numAttrs = pdl ? 1 : 0;
    cudaLaunchKernelEx(&cfg, kern, KArgs(args)...);
}

}

extern "C" void kernel_launch(void* const* d_in, const int* in_sizes, int n_in, void* d_out, int out_size) {
    const __nv_bfloat16* x = (const __nv_bfloat16*)d_in[0];
    const __nv_bfloat16* wqkv = (const __nv_bfloat16*)d_in[1];
    const __nv_bfloat16* wo = (const __nv_bfloat16*)d_in[2];
    const __nv_bfloat16* w_r = (const __nv_bfloat16*)d_in[4];
    const __nv_bfloat16* w_gate = (const __nv_bfloat16*)d_in[5];
    const __nv_bfloat16* w_up = (const __nv_bfloat16*)d_in[6];
    const __nv_bfloat16* w_down = (const __nv_bfloat16*)d_in[7];
    __nv_bfloat16* out = (__nv_bfloat16*)d_out;

    static PFN_encodeTiled enc = nullptr;
    static void* g_o_ptr = nullptr;
    if (!enc) {
        cudaDriverEntryPointQueryResult qres;
        void* fn = nullptr;
        cudaGetDriverEntryPoint("cuTensorMapEncodeTiled", &fn, cudaEnableDefault, &qres);
        enc = (PFN_encodeTiled)fn;
        cudaGetSymbolAddress(&g_o_ptr, g_o);
        cudaFuncSetAttribute(kf_main, cudaFuncAttributeMaxDynamicSharedMemorySize, KF_SMEM);
    }
    CUtensorMap tm_x, tm_w, tm_o, tm_wo, tm_g, tm_u, tm_d;
    make_map_plain(enc, &tm_d, w_down, DM, FF, 8, 256);
    make_map_plain(enc, &tm_g, w_gate, FF, DM, 16, 128);
    make_map_plain(enc, &tm_u, w_up, FF, DM, 16, 128);
    make_map(enc, &tm_x, x, DM, SEQ, 64, 128);
    make_map3(enc, &tm_w, wqkv, DM, DM, 3, 3 * DM * 2, DM * 2, 64, 64, 3);
    make_map3(enc, &tm_o, g_o_ptr, 64, SEQ, 8, DM * 2, 128, 64, 64, 1);
    make_map3(enc, &tm_wo, wo, 64, DM, 8, DM * 2, 128, 64, 64, 2);

    launch(kf_main, 128, 512, KF_SMEM, false, tm_x, tm_w, tm_o, tm_wo, tm_g, tm_u, tm_d, x, wo, w_r, w_gate, w_up, w_down, out);
}
```

```cpp
#include <cuda_runtime.h>
#include <cuda_bf16.h>
#include <cuda.h>
#include <stdint.h>

namespace {

constexpr int SEQ = 2048, DM = 512, NH = 32, FF = 1792;

__device__ __align__(1024) uint8_t g_q[NH * 2 * SEQ * 16];
__device__ __align__(1024) uint8_t g_kv[NH * 8 * 16384];
__device__ float g_norm[16 * NH * 3];
__device__ __align__(1024) __nv_bfloat16 g_o[SEQ * DM];
__device__ __align__(1024) __nv_bfloat16 g_h[SEQ * DM];
__device__ __align__(16) uint4 g_cand[64];
__device__ unsigned int g_oflag[32 * 32];
__device__ unsigned int g_hflag[32];
__device__ unsigned int g_sflag[32];
__device__ __align__(8) uint2 g_act[FF];
__device__ unsigned int g_kvflag[8 * 16 * 8];
__device__ unsigned int g_epoch;
__device__ __align__(16) float4 g_ln1[SEQ];
__device__ __align__(16) float4 g_part[32 * 8 * 64];

#define TSTAMP(K, I)
#define TSTAMP0(K, I)
__device__ __forceinline__ uint32_t smem_u32(const void* p) { return (uint32_t)__cvta_generic_to_shared(p); }
__device__ __forceinline__ void wg_fence() { asm volatile("wgmma.fence.sync.aligned;" ::: "memory"); }
__device__ __forceinline__ void wg_commit() { asm volatile("wgmma.commit_group.sync.aligned;" ::: "memory"); }
template <int N> __device__ __forceinline__ void wg_wait() { asm volatile("wgmma.wait_group.sync.aligned %0;" ::"n"(N) : "memory"); }
template <int N> __device__ __forceinline__ void fence_regs(float (&r)[N]) {
#pragma unroll
    for (int i = 0; i < N; i++) asm volatile("" : "+f"(r[i])::"memory");
}
__device__ __forceinline__ uint64_t make_desc(uint32_t addr, uint32_t lbo, uint32_t sbo, uint32_t swz) {
    uint64_t d = 0;
    d |= (uint64_t)((addr & 0x3FFFF) >> 4);
    d |= (uint64_t)((lbo & 0x3FFFF) >> 4) << 16;
    d |= (uint64_t)((sbo & 0x3FFFF) >> 4) << 32;
    d |= (uint64_t)swz << 62;
    return d;
}
__device__ __forceinline__ void mbar_init(uint32_t bar, uint32_t cnt) {
    asm volatile("mbarrier.init.shared::cta.b64 [%0], %1;" ::"r"(bar), "r"(cnt) : "memory");
}
__device__ __forceinline__ void mbar_expect_tx(uint32_t bar, uint32_t bytes) {
    asm volatile("mbarrier.arrive.expect_tx.shared::cta.b64 _, [%0], %1;" ::"r"(bar), "r"(bytes) : "memory");
}
__device__ __forceinline__ void mbar_arrive(uint32_t bar) {
    asm volatile("mbarrier.arrive.shared::cta.b64 _, [%0];" ::"r"(bar) : "memory");
}
__device__ __forceinline__ void mbar_wait(uint32_t bar, uint32_t parity) {
    asm volatile(
        "{\n.reg .pred p;\nWAIT_%=:\n"
        "mbarrier.try_wait.parity.shared::cta.b64 p, [%0], %1;\n"
        "@p bra DONE_%=;\nbra WAIT_%=;\nDONE_%=:\n}\n" ::"r"(bar), "r"(parity) : "memory");
}
__device__ __forceinline__ void bulk_g2s(uint32_t dst, const void* src, uint32_t bytes, uint32_t bar) {
    asm volatile("cp.async.bulk.shared::cluster.global.mbarrier::complete_tx::bytes [%0], [%1], %2, [%3];" ::"r"(dst),
                 "l"(src), "r"(bytes), "r"(bar) : "memory");
}
__device__ __forceinline__ void bulk_s2g(void* dst, uint32_t src, uint32_t bytes) {
    asm volatile("cp.async.bulk.global.shared::cta.bulk_group [%0], [%1], %2;" ::"l"(dst), "r"(src), "r"(bytes) : "memory");
}
__device__ __forceinline__ void tma_load_2d(uint32_t dst, const CUtensorMap* tm, int c0, int c1, uint32_t bar) {
    asm volatile("cp.async.bulk.tensor.2d.shared::cluster.global.mbarrier::complete_tx::bytes [%0], [%1, {%3, %4}], [%2];" ::"r"(dst),
                 "l"(tm), "r"(bar), "r"(c0), "r"(c1) : "memory");
}
__device__ __forceinline__ void tma_load_3d(uint32_t dst, const CUtensorMap* tm, int c0, int c1, int c2, uint32_t bar) {
    asm volatile("cp.async.bulk.tensor.3d.shared::cluster.global.mbarrier::complete_tx::bytes [%0], [%1, {%3, %4, %5}], [%2];" ::"r"(dst),
                 "l"(tm), "r"(bar), "r"(c0), "r"(c1), "r"(c2) : "memory");
}
__device__ __forceinline__ void tma_load_2d_mc(uint32_t dst, const CUtensorMap* tm, int c0, int c1, uint32_t bar, uint16_t mask) {
    asm volatile("cp.async.bulk.tensor.2d.shared::cluster.global.mbarrier::complete_tx::bytes.multicast::cluster [%0], [%1, {%3, %4}], [%2], %5;" ::"r"(dst),
                 "l"(tm), "r"(bar), "r"(c0), "r"(c1), "h"(mask) : "memory");
}
__device__ __forceinline__ void mbar_arrive_cluster(uint32_t bar, uint32_t cta) {
    asm volatile("{\n.reg .b32 ra;\nmapa.shared::cluster.u32 ra, %0, %1;\nmbarrier.arrive.release.cluster.shared::cluster.b64 _, [ra];\n}" ::"r"(bar), "r"(cta) : "memory");
}
__device__ __forceinline__ void cluster_sync() {
    asm volatile("barrier.cluster.arrive.release.aligned;\nbarrier.cluster.wait.acquire.aligned;" ::: "memory");
}
__device__ __forceinline__ void prefetch_l2(const void* p, uint32_t bytes) {
    asm volatile("cp.async.bulk.prefetch.L2.global [%0], %1;" ::"l"(p), "r"(bytes) : "memory");
}
__device__ __forceinline__ void fence_proxy_async() { asm volatile("fence.proxy.async.shared::cta;" ::: "memory"); }
__device__ __forceinline__ void fence_barrier_init() { asm volatile("fence.mbarrier_init.release.cluster;" ::: "memory"); }
__device__ __forceinline__ void pdl_launch() { asm volatile("griddepcontrol.launch_dependents;" ::: "memory"); }
__device__ __forceinline__ void pdl_wait() { asm volatile("griddepcontrol.wait;" ::: "memory"); }
__device__ __forceinline__ void named_sync(int id, int n) { asm volatile("bar.sync %0, %1;" ::"r"(id), "r"(n) : "memory"); }
__device__ __forceinline__ void named_arrive(int id, int n) { asm volatile("bar.arrive %0, %1;" ::"r"(id), "r"(n) : "memory"); }

__device__ __forceinline__ float ex2f(float x) { float y; asm("ex2.approx.ftz.f32 %0, %1;" : "=f"(y) : "f"(x)); return y; }
__device__ __forceinline__ uint32_t pack_bf16(float lo, float hi) {
    uint32_t r; asm("cvt.rn.bf16x2.f32 %0, %1, %2;" : "=r"(r) : "f"(hi), "f"(lo)); return r;
}
__device__ __forceinline__ float bf_lo(uint32_t v) { return __uint_as_float(v << 16); }
__device__ __forceinline__ float bf_hi(uint32_t v) { return __uint_as_float(v & 0xFFFF0000u); }
__device__ __forceinline__ float rbf(float x) { return __bfloat162float(__float2bfloat16_rn(x)); }
__device__ __forceinline__ uint32_t fma_bf16x2(uint32_t a, uint32_t b, uint32_t c) {
    uint32_t r; asm("fma.rn.bf16x2 %0, %1, %2, %3;" : "=r"(r) : "r"(a), "r"(b), "r"(c)); return r;
}
__device__ __forceinline__ void stmatrix_x4(uint32_t addr, uint32_t r0, uint32_t r1, uint32_t r2, uint32_t r3) {
    asm volatile("stmatrix.sync.aligned.m8n8.x4.shared.b16 [%0], {%1, %2, %3, %4};" ::"r"(addr), "r"(r0), "r"(r1), "r"(r2), "r"(r3) : "memory");
}
__device__ __forceinline__ void stmatrix_x4_trans(uint32_t addr, uint32_t r0, uint32_t r1, uint32_t r2, uint32_t r3) {
    asm volatile("stmatrix.sync.aligned.m8n8.x4.trans.shared.b16 [%0], {%1, %2, %3, %4};" ::"r"(addr), "r"(r0), "r"(r1), "r"(r2), "r"(r3) : "memory");
}

__device__ __forceinline__ void wgmma_k1_n136(float (&d)[68], uint64_t desca, uint64_t descb, int scale_d) {
  asm volatile("{\n.reg .pred p;\nsetp.ne.b32 p, %70, 0;\n"
    "wgmma.mma_async.sync.aligned.m64n136k16.f32.bf16.bf16 "
    "{%0, %1, %2, %3, %4, %5, %6, %7, %8, %9, %10, %11, %12, %13, %14, %15, %16, %17, %18, %19, %20, %21, %22, %23, %24, %25, %26, %27, %28, %29, %30, %31, %32, %33, %34, %35, %36, %37, %38, %39, %40, %41, %42, %43, %44, %45, %46, %47, %48, %49, %50, %51, %52, %53, %54, %55, %56, %57, %58, %59, %60, %61, %62, %63, %64, %65, %66, %67}, "
    "%68, %69, p, 1, 1, 1, 0;\n}\n"
    : "+f"(d[0]), "+f"(d[1]), "+f"(d[2]), "+f"(d[3]), "+f"(d[4]), "+f"(d[5]), "+f"(d[6]), "+f"(d[7]), "+f"(d[8]), "+f"(d[9]), "+f"(d[10]), "+f"(d[11]), "+f"(d[12]), "+f"(d[13]), "+f"(d[14]), "+f"(d[15]), "+f"(d[16]), "+f"(d[17]), "+f"(d[18]), "+f"(d[19]), "+f"(d[20]), "+f"(d[21]), "+f"(d[22]), "+f"(d[23]), "+f"(d[24]), "+f"(d[25]), "+f"(d[26]), "+f"(d[27]), "+f"(d[28]), "+f"(d[29]), "+f"(d[30]), "+f"(d[31]), "+f"(d[32]), "+f"(d[33]), "+f"(d[34]), "+f"(d[35]), "+f"(d[36]), "+f"(d[37]), "+f"(d[38]), "+f"(d[39]), "+f"(d[40]), "+f"(d[41]), "+f"(d[42]), "+f"(d[43]), "+f"(d[44]), "+f"(d[45]), "+f"(d[46]), "+f"(d[47]), "+f"(d[48]), "+f"(d[49]), "+f"(d[50]), "+f"(d[51]), "+f"(d[52]), "+f"(d[53]), "+f"(d[54]), "+f"(d[55]), "+f"(d[56]), "+f"(d[57]), "+f"(d[58]), "+f"(d[59]), "+f"(d[60]), "+f"(d[61]), "+f"(d[62]), "+f"(d[63]), "+f"(d[64]), "+f"(d[65]), "+f"(d[66]), "+f"(d[67])
    : "l"(desca), "l"(descb), "r"(scale_d));
}
__device__ __forceinline__ void wgmma_qk_n64(float (&d)[32], uint32_t a0, uint32_t a1, uint32_t a2, uint32_t a3, uint64_t descb) {
  asm volatile("{\n.reg .pred p;\nsetp.ne.b32 p, 0, 0;\n"
    "wgmma.mma_async.sync.aligned.m64n64k16.f32.bf16.bf16 "
    "{%0, %1, %2, %3, %4, %5, %6, %7, %8, %9, %10, %11, %12, %13, %14, %15, %16, %17, %18, %19, %20, %21, %22, %23, %24, %25, %26, %27, %28, %29, %30, %31}, "
    "{%32, %33, %34, %35}, %36, p, 1, 1, 0;\n}\n"
    : "=f"(d[0]), "=f"(d[1]), "=f"(d[2]), "=f"(d[3]), "=f"(d[4]), "=f"(d[5]), "=f"(d[6]), "=f"(d[7]), "=f"(d[8]), "=f"(d[9]), "=f"(d[10]), "=f"(d[11]), "=f"(d[12]), "=f"(d[13]), "=f"(d[14]), "=f"(d[15]), "=f"(d[16]), "=f"(d[17]), "=f"(d[18]), "=f"(d[19]), "=f"(d[20]), "=f"(d[21]), "=f"(d[22]), "=f"(d[23]), "=f"(d[24]), "=f"(d[25]), "=f"(d[26]), "=f"(d[27]), "=f"(d[28]), "=f"(d[29]), "=f"(d[30]), "=f"(d[31])
    : "r"(a0), "r"(a1), "r"(a2), "r"(a3), "l"(descb));
}
__device__ __forceinline__ void wgmma_pv_n24(float (&d)[12], uint32_t a0, uint32_t a1, uint32_t a2, uint32_t a3, uint64_t descb) {
  asm volatile("{\n.reg .pred p;\nsetp.eq.b32 p, 0, 0;\n"
    "wgmma.mma_async.sync.aligned.m64n24k16.f32.bf16.bf16 "
    "{%0, %1, %2, %3, %4, %5, %6, %7, %8, %9, %10, %11}, "
    "{%12, %13, %14, %15}, %16, p, 1, 1, 1;\n}\n"
    : "+f"(d[0]), "+f"(d[1]), "+f"(d[2]), "+f"(d[3]), "+f"(d[4]), "+f"(d[5]), "+f"(d[6]), "+f"(d[7]), "+f"(d[8]), "+f"(d[9]), "+f"(d[10]), "+f"(d[11])
    : "r"(a0), "r"(a1), "r"(a2), "r"(a3), "l"(descb));
}
__device__ __forceinline__ void wgmma_k3_n64(float (&d)[32], uint64_t desca, uint64_t descb, int scale_d) {
  asm volatile("{\n.reg .pred p;\nsetp.ne.b32 p, %34, 0;\n"
    "wgmma.mma_async.sync.aligned.m64n64k16.f32.bf16.bf16 "
    "{%0, %1, %2, %3, %4, %5, %6, %7, %8, %9, %10, %11, %12, %13, %14, %15, %16, %17, %18, %19, %20, %21, %22, %23, %24, %25, %26, %27, %28, %29, %30, %31}, "
    "%32, %33, p, 1, 1, 0, 1;\n}\n"
    : "+f"(d[0]), "+f"(d[1]), "+f"(d[2]), "+f"(d[3]), "+f"(d[4]), "+f"(d[5]), "+f"(d[6]), "+f"(d[7]), "+f"(d[8]), "+f"(d[9]), "+f"(d[10]), "+f"(d[11]), "+f"(d[12]), "+f"(d[13]), "+f"(d[14]), "+f"(d[15]), "+f"(d[16]), "+f"(d[17]), "+f"(d[18]), "+f"(d[19]), "+f"(d[20]), "+f"(d[21]), "+f"(d[22]), "+f"(d[23]), "+f"(d[24]), "+f"(d[25]), "+f"(d[26]), "+f"(d[27]), "+f"(d[28]), "+f"(d[29]), "+f"(d[30]), "+f"(d[31])
    : "l"(desca), "l"(descb), "r"(scale_d));
}

constexpr int K1_XS = 17408;
constexpr int K1_WS = 24576;
constexpr int K1_ST = K1_XS + K1_WS;
constexpr int K1_NST = 5;
constexpr int K1_OFF_MISC = K1_NST * K1_ST;
constexpr int K1_SMEM = K1_OFF_MISC + 2048 + 1024;
constexpr int K1_OFF_BAR = 229376 + 1088;
constexpr float QSCALE = 0.25f * 1.4426950408889634f;

__device__ __forceinline__ void phase_qkv(const CUtensorMap& tm_x, const CUtensorMap& tm_w, const __nv_bfloat16* __restrict__ x,
                                          const uint32_t sb, uint8_t* sp, const unsigned int tag) {
    const uint32_t full = sb + K1_OFF_BAR;
    const uint32_t empty = full + 40;
    float* s_mr = (float*)(sp + K1_OFF_MISC + 256);

    const int tid = threadIdx.x, lane = tid & 31;
    const int warp = __shfl_sync(0xffffffffu, tid >> 5, 0);
    const int mt = blockIdx.x >> 3, nt = blockIdx.x & 7;
    uint4 v[16];
    if (warp == 13 || warp == 14) {
        const int r = tid - 416;
        const uint4* xp = (const uint4*)(x + (size_t)(mt * 128 + nt * 16 + (r >> 2)) * DM) + (r & 3);
#pragma unroll
        for (int i = 0; i < 16; i++) v[i] = __ldg(xp + i * 4);
    }
    if (tid == 384) {
        for (int i = 0; i < K1_NST; i++) { mbar_init(full + 8 * i, 1); mbar_init(empty + 8 * i, 3); }
        fence_barrier_init();
        for (int kb = 0; kb < K1_NST; kb++) {
            mbar_expect_tx(full + 8 * kb, 16384 + K1_WS);
            tma_load_2d(sb + kb * K1_ST, &tm_x, kb * 64, mt * 128, full + 8 * kb);
            tma_load_3d(sb + kb * K1_ST + K1_XS, &tm_w, nt * 64, kb * 64, 0, full + 8 * kb);
        }
    }
    if (tid < K1_NST * 64) {
        *(uint4*)(sp + (tid >> 6) * K1_ST + 16384 + (tid & 63) * 16) =
            make_uint4(0x3F803F80u, 0x3F803F80u, 0x3F803F80u, 0x3F803F80u);
    }
    fence_proxy_async();
    __syncthreads();

    if (warp == 12) {
        if (lane == 0) {
            for (int kb = K1_NST; kb < 8; kb++) {
                const int s = kb % K1_NST;
                mbar_wait(empty + 8 * s, 0);
                mbar_expect_tx(full + 8 * s, 16384 + K1_WS);
                tma_load_2d(sb + s * K1_ST, &tm_x, kb * 64, mt * 128, full + 8 * s);
                tma_load_3d(sb + s * K1_ST + K1_XS, &tm_w, nt * 64, kb * 64, 0, full + 8 * s);
            }
        }
        __syncwarp();
    } else if (warp == 13 || warp == 14) {
        const int r = tid - 416;
        {
            const int row = mt * 128 + nt * 16 + (r >> 2);
            float s1 = 0.f;
#pragma unroll
            for (int i = 0; i < 16; i++)
                s1 += ((bf_lo(v[i].x) + bf_hi(v[i].x)) + (bf_lo(v[i].y) + bf_hi(v[i].y))) + ((bf_lo(v[i].z) + bf_hi(v[i].z)) + (bf_lo(v[i].w) + bf_hi(v[i].w)));
#pragma unroll
            for (int o = 1; o < 4; o <<= 1) s1 += __shfl_xor_sync(0xffffffffu, s1, o);
            const float mean = s1 * (1.f / DM);
            float q0 = 0.f, q1 = 0.f;
#pragma unroll
            for (int i = 0; i < 16; i++) {
                const uint32_t w[4] = {v[i].x, v[i].y, v[i].z, v[i].w};
#pragma unroll
                for (int j = 0; j < 4; j++) {
                    const float a = bf_lo(w[j]) - mean, b = bf_hi(w[j]) - mean;
                    q0 = fmaf(a, a, q0); q1 = fmaf(b, b, q1);
                }
            }
            float q = q0 + q1;
#pragma unroll
            for (int o = 1; o < 4; o <<= 1) q += __shfl_xor_sync(0xffffffffu, q, o);
            const float den = rbf(sqrtf(rbf(rbf(q * (1.f / DM)) + 1e-5f)));
            if ((r & 3) == 0)
                asm volatile("st.relaxed.gpu.global.v4.f32 [%0], {%1, %2, %3, %4};" ::"l"(g_ln1 + row), "f"(rbf(mean)), "f"(1.f / den),
                             "f"(__uint_as_float(tag)), "f"(0.f) : "memory");
        }
        if (r == 0) TSTAMP0(0, 6);
#pragma unroll
        for (int h2 = 0; h2 < 2; h2++) {
            const int rr = r + 64 * h2;
            float4 st;
            int spins = 0;
            do {
                asm volatile("ld.relaxed.gpu.global.v4.f32 {%0, %1, %2, %3}, [%4];" : "=f"(st.x), "=f"(st.y), "=f"(st.z), "=f"(st.w) : "l"(g_ln1 + mt * 128 + rr) : "memory");
            } while (__float_as_uint(st.z) != tag && ++spins < (1 << 22));
            s_mr[(rr >> 1) * 4 + (rr & 1)] = st.x;
            s_mr[(rr >> 1) * 4 + 2 + (rr & 1)] = st.y;
        }
        if (r == 0) TSTAMP0(0, 7);
        named_arrive(11, 448);
    } else if (warp < 12) {
        const int part = warp >> 2, hw = warp & 3;
        float acc[68];
#pragma unroll
        for (int i = 0; i < 68; i++) acc[i] = 0.f;
        fence_regs(acc);
#pragma unroll 1
        for (int kb = 0; kb < 8; kb++) {
            const int s = kb % K1_NST;
            mbar_wait(full + 8 * s, (kb / K1_NST) & 1);
            const uint64_t da = make_desc(sb + s * K1_ST + K1_XS + part * 8192, 1024, 1024, 1);
            const uint64_t db = make_desc(sb + s * K1_ST, 16, 1024, 1);
            wg_fence();
#pragma unroll
            for (int k = 0; k < 4; k++) wgmma_k1_n136(acc, da + k * 128, db + k * 2, (kb | k) != 0);
            wg_commit();
            if (kb > 0 && kb <= 8 - K1_NST) {
                wg_wait<1>();
                if ((tid & 127) == 0) mbar_arrive(empty + 8 * (kb - 1));
            }
        }
        wg_wait<0>();
        fence_regs(acc);
        if (tid == 0) TSTAMP0(0, 1);
        named_sync(11, 448);
        if (tid == 0) TSTAMP0(0, 2);

        const int t = lane & 3;
        const float cs0 = acc[64], cs1 = acc[66];
        const float sc = (part == 0) ? QSCALE : 1.f;
        const uint32_t stg = sb + (hw >> 1) * K1_ST + K1_XS + part * 8192 + (hw & 1) * 4096;
        const uint32_t st_addr = stg + ((lane >> 3) & 1) * 2048 + ((lane >> 4) * 8 + (lane & 7)) * 16;
#pragma unroll
        for (int j = 0; j < 16; j += 2) {
            uint32_t rr[4];
#pragma unroll
            for (int u = 0; u < 2; u++) {
                const int jj = j + u;
                const float4 mr = *(const float4*)(s_mr + (4 * jj + t) * 4);
                const float2 m2 = make_float2(mr.x, mr.y);
                const float ra = mr.z * sc, rb = mr.w * sc;
                rr[2 * u] = pack_bf16((acc[4 * jj] - m2.x * cs0) * ra, (acc[4 * jj + 1] - m2.y * cs0) * rb);
                rr[2 * u + 1] = pack_bf16((acc[4 * jj + 2] - m2.x * cs1) * ra, (acc[4 * jj + 3] - m2.y * cs1) * rb);
            }
            stmatrix_x4_trans(st_addr + j * 128, rr[0], rr[1], rr[2], rr[3]);
        }
        fence_proxy_async();
        __syncwarp();
        if (tid == 0) TSTAMP0(0, 4);
        const int head = nt * 4 + hw;
        if (lane == 0) {
            uint8_t* dst;
            uint32_t hstride;
            if (part == 0) { dst = g_q + (size_t)head * 65536 + mt * 2048; hstride = 32768; }
            else { dst = g_kv + (size_t)head * 131072 + (mt >> 1) * 16384 + (part - 1) * 8192 + (mt & 1) * 2048; hstride = 4096; }
            bulk_s2g(dst, stg, 2048);
            bulk_s2g(dst + hstride, stg + 2048, 2048);
            asm volatile("cp.async.bulk.commit_group;" ::: "memory");
        }
        float nmax = 0.f;
#pragma unroll
        for (int i = 0; i < 4; i++) {
            const int tok = lane + 32 * i;
            const uint4 a = *(const uint4*)(sp + (stg - sb) + tok * 16);
            const uint4 b = *(const uint4*)(sp + (stg - sb) + 2048 + tok * 16);
            uint32_t n0 = fma_bf16x2(a.x, a.x, 0u), n1 = fma_bf16x2(b.x, b.x, 0u);
            n0 = fma_bf16x2(a.y, a.y, n0); n1 = fma_bf16x2(b.y, b.y, n1);
            n0 = fma_bf16x2(a.z, a.z, n0); n1 = fma_bf16x2(b.z, b.z, n1);
            n0 = fma_bf16x2(a.w, a.w, n0); n1 = fma_bf16x2(b.w, b.w, n1);
            const float n2 = ((bf_lo(n0) + bf_hi(n0)) + (bf_lo(n1) + bf_hi(n1))) * 1.125f;
            nmax = (n2 > nmax || n2 != n2) ? n2 : nmax;
        }
#pragma unroll
        for (int o = 16; o > 0; o >>= 1) {
            const float v = __shfl_xor_sync(0xffffffffu, nmax, o);
            nmax = (v > nmax || v != v) ? v : nmax;
        }
        if (tid == 0) TSTAMP0(0, 5);
        if (lane == 0) {
            g_norm[(head * 16 + mt) * 3 + part] = nmax;
            asm volatile("cp.async.bulk.wait_group 0;" ::: "memory");
            if (tid == 0) TSTAMP0(0, 3);
            asm volatile("fence.proxy.async.global;" ::: "memory");
            asm volatile("red.release.gpu.global.add.u32 [%0], 1;" ::"l"(&g_kvflag[(nt * 16 + mt) * 8]) : "memory");
            if (tid == 0) TSTAMP0(0, 8);
        }
        __syncwarp();
    }
    __syncthreads();
}

#define POLL_NS 50
constexpr int KF_CH_G = 16384, KF_CH_S = 20480, KF_NCH = 8;
constexpr int KF_OFF_WO = KF_NCH * KF_CH_S;
constexpr int KF_OFF_MISC = KF_OFF_WO + 65536;
constexpr int KF_SMEM = KF_OFF_MISC + 1280 + 1024;

__device__ __forceinline__ uint32_t exp2_pair_poly(float s0, float s1) {
    const float KB = 65536.0f + 127.0f;
    const float t0 = s0 + KB, t1 = s1 + KB;
    const uint32_t w = __byte_perm(__float_as_uint(t0), __float_as_uint(t1), 0x5410);
    uint32_t z;
    asm("lop3.b32 %0, %1, %2, %3, 0xEA;" : "=r"(z) : "r"(w), "r"(0x007F007Fu), "r"(0x3F803F80u));
    uint32_t p = fma_bf16x2(0x3eab3eabu, z, 0xbc73bc73u);
    p = fma_bf16x2(p, z, 0x3f2f3f2fu);
    return p + w - z;
}
#define EMASK 0x5757u
constexpr uint32_t KF_EMASK = EMASK;
template <int LO, int HI>
__device__ __forceinline__ void softmax_part(const float (&s)[32], uint32_t (&p)[16]) {
#pragma unroll
    for (int i = LO; i < HI; i++) {
        if ((KF_EMASK >> i) & 1) p[i] = exp2_pair_poly(s[2 * i], s[2 * i + 1]);
        else p[i] = pack_bf16(ex2f(s[2 * i]), ex2f(s[2 * i + 1]));
    }
}
#define KF_PV(P, OFF)                                                                              \
    _Pragma("unroll") for (int kk = 0; kk < 4; kk++)                                               \
        wgmma_pv_n24(o, P[4 * kk], P[4 * kk + 1], P[4 * kk + 2], P[4 * kk + 3], dv + ((OFF) + kk * 16));

__device__ __forceinline__ uint32_t make_key(float r_bf16, int token) {
    const uint32_t u = __float_as_uint(r_bf16) >> 16;
    const uint32_t o = (u & 0x8000u) ? (~u & 0xFFFFu) : (u | 0x8000u);
    return (o << 16) | (uint32_t)(0xFFFF - token);
}
__device__ __forceinline__ float key_value(uint32_t k) {
    const uint32_t o = k >> 16;
    const uint32_t u = (o & 0x8000u) ? (o & 0x7FFFu) : (~o & 0xFFFFu);
    return __uint_as_float(u << 16);
}
__device__ __forceinline__ int key_token(uint32_t k) { return 0xFFFF - (int)(k & 0xFFFFu); }
__device__ __forceinline__ void warp_top2(uint32_t a, uint32_t b, uint32_t& k1, uint32_t& k2) {
    k1 = __reduce_max_sync(0xffffffffu, a > b ? a : b);
    const uint32_t a2 = (a == k1) ? 0u : a, b2 = (b == k1) ? 0u : b;
    k2 = __reduce_max_sync(0xffffffffu, a2 > b2 ? a2 : b2);
}
__device__ __forceinline__ unsigned int ld_acquire(const unsigned int* p) {
    unsigned int v; asm volatile("ld.acquire.gpu.global.u32 %0, [%1];" : "=r"(v) : "l"(p) : "memory"); return v;
}
__device__ __forceinline__ void red_release_add(unsigned int* p) {
    asm volatile("red.release.gpu.global.add.u32 [%0], 1;" ::"l"(p) : "memory");
}

__global__ void __launch_bounds__(512, 1)
kf_main(const __grid_constant__ CUtensorMap tm_x, const __grid_constant__ CUtensorMap tm_w,
        const __grid_constant__ CUtensorMap tm_o, const __grid_constant__ CUtensorMap tm_wo,
        const __grid_constant__ CUtensorMap tm_g, const __grid_constant__ CUtensorMap tm_u, const __grid_constant__ CUtensorMap tm_d,
        const __nv_bfloat16* __restrict__ x, const __nv_bfloat16* __restrict__ wo, const __nv_bfloat16* __restrict__ w_r,
        const __nv_bfloat16* __restrict__ w_gate, const __nv_bfloat16* __restrict__ w_up, const __nv_bfloat16* __restrict__ w_down,
        __nv_bfloat16* __restrict__ out) {
    extern __shared__ uint8_t smem_raw[];
    const uint32_t sraw = smem_u32(smem_raw);
    const uint32_t sb = (sraw + 1023) & ~1023u;
    uint8_t* sp = smem_raw + (sb - sraw);
    const uint32_t kvbar = sb + KF_OFF_MISC;
    const uint32_t wbar = kvbar + 64;
    const uint32_t obar = wbar + 64;
    const uint32_t gbar = obar + 64;
    const uint32_t dbar = gbar + 8;
    unsigned int* s_cnt = (unsigned int*)(sp + KF_OFF_MISC + 208);
    volatile unsigned int* s_order = (volatile unsigned int*)(sp + KF_OFF_MISC + 1056);
    uint32_t* s_key = (uint32_t*)(sp + KF_OFF_MISC + 256);
    float* s_gu = (float*)(sp + KF_OFF_MISC + 768);
    uint4* s_sel = (uint4*)(sp + KF_OFF_MISC + 1024);
    const int tid = threadIdx.x;
    const int head = blockIdx.x >> 2, quarter = blockIdx.x & 3;
    const int mt = blockIdx.x >> 2, nt = blockIdx.x & 3;
    if (tid == 0) TSTAMP0(0, 0);
    const unsigned int tag = *(volatile unsigned int*)&g_epoch + 1u;
    if (tid == 0) {
        for (int c = 0; c < 26; c++) mbar_init(kvbar + 8 * c, 1);
        for (int c = 0; c < 4; c++) s_cnt[c] = 0;
        fence_barrier_init();
    }
    phase_qkv(tm_x, tm_w, x, sb, sp, tag);
    const int warp_u = __shfl_sync(0xffffffffu, tid >> 5, 0);

    if (tid == 0) TSTAMP0(1, 0);
    const uint8_t* kvsrc = g_kv + (size_t)head * (KF_NCH * KF_CH_G);
    const unsigned int* kvf = g_kvflag + (head >> 2) * 16 * 8;
    if (warp_u >= 12) {
        for (int i = tid - 384; i < KF_NCH * 256; i += 128)
            *(uint4*)(sp + (i >> 8) * KF_CH_S + 16384 + (i & 255) * 16) =
                make_uint4(0x3F803F80u, 0x3F803F80u, 0x3F803F80u, 0x3F803F80u);
        fence_proxy_async();
        if (tid == 384) {
            for (int kb = 0; kb < 4; kb++) {
                mbar_expect_tx(wbar + 8 * kb, 16384);
                tma_load_3d(sb + KF_OFF_WO + kb * 16384, &tm_wo, 0, kb * 64, nt * 2, wbar + 8 * kb);
            }
        }
        if (tid == 416) {
            int spins = 0;
            while (((int)(ld_acquire(kvf) - 12u * tag) < 0 || (int)(ld_acquire(kvf + 8) - 12u * tag) < 0) && ++spins < (1 << 22)) {}
            asm volatile("fence.proxy.async.global;" ::: "memory");
            mbar_expect_tx(kvbar, KF_CH_G);
            bulk_g2s(sb, kvsrc, KF_CH_G, kvbar);
        }
        __syncwarp();
    }
    const int lane = tid & 31, g = lane >> 2, t = lane & 3;
    const int wg = warp_u >> 2, warp = warp_u & 3;
    if (warp_u == 0) {
        int spins = 0;
        while (!__all_sync(0xffffffffu, (int)(ld_acquire(kvf + (lane & 15) * 8) - 12u * tag) >= 0) && ++spins < (1 << 22)) {}
        if (tid == 0) TSTAMP0(1, 1);
    }
    __syncthreads();
    float kn, vn, qn;
    {
        const int m16 = lane & 15;
        kn = __ldcg(&g_norm[(head * 16 + m16) * 3 + 1]);
        vn = __ldcg(&g_norm[(head * 16 + m16) * 3 + 2]);
        qn = __ldcg(&g_norm[(head * 16 + quarter * 4 + (lane & 3)) * 3 + 0]);
    }
    uint32_t qn2[2][4];
#pragma unroll
    for (int ps = 0; ps < 2; ps++) {
        const uint8_t* qb = g_q + (size_t)head * 65536 + (quarter * 512 + ps * 256 + wg * 64 + warp * 16 + g) * 16 + t * 4;
        qn2[ps][0] = __ldcg((const uint32_t*)(qb));
        qn2[ps][1] = __ldcg((const uint32_t*)(qb + 128));
        qn2[ps][2] = __ldcg((const uint32_t*)(qb + 32768));
        qn2[ps][3] = __ldcg((const uint32_t*)(qb + 32768 + 128));
    }

    bool fast;
    {
        const bool bad = !(kn < 1e30f) || !(vn < 1e30f) || !(qn < 1e30f);
#pragma unroll
        for (int o = 8; o > 0; o >>= 1) {
            kn = fmaxf(kn, __shfl_xor_sync(0xffffffffu, kn, o));
            qn = fmaxf(qn, __shfl_xor_sync(0xffffffffu, qn, o));
        }
        fast = __all_sync(0xffffffffu, !bad && (qn * kn <= 3500.f));
    }
    if (tid == 416) {
        asm volatile("fence.proxy.async.global;" ::: "memory");
        for (int c = 1; c < KF_NCH; c++) {
            mbar_expect_tx(kvbar + 8 * c, KF_CH_G);
            bulk_g2s(sb + c * KF_CH_S, kvsrc + c * KF_CH_G, KF_CH_G, kvbar + 8 * c);
        }
        prefetch_l2((const uint8_t*)wo + blockIdx.x * 4096, 4096);
        prefetch_l2((const uint8_t*)w_gate + blockIdx.x * 14336, 14336);
        prefetch_l2((const uint8_t*)w_up + blockIdx.x * 14336, 14336);
        prefetch_l2((const uint8_t*)w_down + blockIdx.x * 14336, 14336);
    }
    if (tid == 0) TSTAMP0(1, 8);
    const uint64_t dk0 = make_desc(sb, 4096, 128, 0);
    const uint64_t dv0 = make_desc(sb + 8192, 128, 4096, 0);

#pragma unroll 1
    for (int pass = 0; pass < 2; pass++) {
        const int row0 = quarter * 512 + pass * 256 + wg * 64 + warp * 16 + g;
        uint32_t qa[4];
#pragma unroll
        for (int i = 0; i < 4; i++) qa[i] = pass ? qn2[1][i] : qn2[0][i];
        float o[12];
#pragma unroll
        for (int i = 0; i < 12; i++) o[i] = 0.f;
        fence_regs(o);
#define KF_RELEASE_CHUNK(c)                                                                          \
        if (pass == 1 && (c) >= 1 && (c) <= 4) {                                                     \
            named_sync(4 + wg, 128);            \
            if ((tid & 127) == 0 && atomicAdd(&s_cnt[(c) - 1], 1u) == 3u) {                          \
                mbar_expect_tx(wbar + 8 * (3 + (c)), 16384);                                         \
                tma_load_3d(sb + ((c) - 1) * KF_CH_S, &tm_wo, 0, (3 + (c)) * 64, nt * 2, wbar + 8 * (3 + (c))); \
            }                                                                                        \
        }
        if (fast) {
#pragma unroll 1
            for (int c = 0; c < KF_NCH; c++) {
                const uint64_t dk = dk0 + (uint64_t)(c * (KF_CH_S >> 4));
                const uint64_t dv = dv0 + (uint64_t)(c * (KF_CH_S >> 4));
                float s0[32], s1[32], s2[32], s3[32];
                uint32_t p0[16], p1[16], p2[16], p3[16];
                mbar_wait(kvbar + 8 * c, 0);
                wg_wait<1>();
                wg_fence();
                wgmma_qk_n64(s0, qa[0], qa[1], qa[2], qa[3], dk);
                wg_commit();
                wg_wait<1>();
                KF_RELEASE_CHUNK(c);
                wg_fence();
                wgmma_qk_n64(s1, qa[0], qa[1], qa[2], qa[3], dk + 64);
                wg_commit();
                wg_wait<1>();
                fence_regs(s0);
                softmax_part<0, 16>(s0, p0);
                wg_fence();
                KF_PV(p0, 0);
                wg_commit();
                wg_wait<1>();
                fence_regs(s1);
                softmax_part<0, 8>(s1, p1);
                wg_wait<0>();
                wg_fence();
                wgmma_qk_n64(s2, qa[0], qa[1], qa[2], qa[3], dk + 128);
                wg_commit();
                softmax_part<8, 16>(s1, p1);
                wg_fence();
                KF_PV(p1, 64);
                wg_commit();
                wg_wait<1>();
                fence_regs(s2);
                softmax_part<0, 8>(s2, p2);
                wg_wait<0>();
                wg_fence();
                wgmma_qk_n64(s3, qa[0], qa[1], qa[2], qa[3], dk + 192);
                wg_commit();
                softmax_part<8, 16>(s2, p2);
                wg_fence();
                KF_PV(p2, 128);
                wg_commit();
                wg_wait<1>();
                fence_regs(s3);
                softmax_part<0, 16>(s3, p3);
                wg_fence();
                KF_PV(p3, 192);
                wg_commit();
            }
            wg_wait<0>();
            fence_regs(o);
        } else {
            float m0 = -INFINITY, m1 = -INFINITY;
#pragma unroll 1
            for (int b = 0; b < 32; b++) {
                const int c = b >> 2;
                const uint64_t dk = dk0 + (uint64_t)(c * (KF_CH_S >> 4) + (b & 3) * 64);
                const uint64_t dv = dv0 + (uint64_t)(c * (KF_CH_S >> 4) + (b & 3) * 64);
                float s[32];
                uint32_t p[16];
                mbar_wait(kvbar + 8 * c, 0);
                wg_fence();
                wgmma_qk_n64(s, qa[0], qa[1], qa[2], qa[3], dk);
                wg_commit();
                if ((b & 3) == 0) { KF_RELEASE_CHUNK(c); }
                wg_wait<0>();
                fence_regs(s);
                float x0 = s[0], x1 = s[2];
#pragma unroll
                for (int j = 0; j < 8; j++) {
                    x0 = fmaxf(x0, fmaxf(s[4 * j], s[4 * j + 1]));
                    x1 = fmaxf(x1, fmaxf(s[4 * j + 2], s[4 * j + 3]));
                }
                x0 = fmaxf(x0, __shfl_xor_sync(0xffffffffu, x0, 1));
                x0 = fmaxf(x0, __shfl_xor_sync(0xffffffffu, x0, 2));
                x1 = fmaxf(x1, __shfl_xor_sync(0xffffffffu, x1, 1));
                x1 = fmaxf(x1, __shfl_xor_sync(0xffffffffu, x1, 2));
                const float n0 = fmaxf(m0, x0), n1 = fmaxf(m1, x1);
                const float c0 = ex2f(m0 - n0), c1 = ex2f(m1 - n1);
                m0 = n0; m1 = n1;
#pragma unroll
                for (int j = 0; j < 3; j++) {
                    o[4 * j] *= c0; o[4 * j + 1] *= c0; o[4 * j + 2] *= c1; o[4 * j + 3] *= c1;
                }
#pragma unroll
                for (int j = 0; j < 8; j++) {
                    p[2 * j] = pack_bf16(ex2f(s[4 * j] - n0), ex2f(s[4 * j + 1] - n0));
                    p[2 * j + 1] = pack_bf16(ex2f(s[4 * j + 2] - n1), ex2f(s[4 * j + 3] - n1));
                }
                fence_regs(o);
                wg_fence();
                KF_PV(p, 0);
                wg_commit();
                wg_wait<0>();
                fence_regs(o);
            }
        }
        const float inv0 = 1.f / o[8], inv1 = 1.f / o[10];
        {
            uint32_t v0 = pack_bf16(o[0] * inv0, o[1] * inv0), v1 = pack_bf16(o[4] * inv0, o[5] * inv0);
            uint32_t v2 = pack_bf16(o[2] * inv1, o[3] * inv1), v3 = pack_bf16(o[6] * inv1, o[7] * inv1);
            const bool o1 = t & 1, o2 = t & 2;
            uint32_t s0 = o1 ? v0 : v1, s1 = o1 ? v2 : v3;
            s0 = __shfl_xor_sync(0xffffffffu, s0, 1); s1 = __shfl_xor_sync(0xffffffffu, s1, 1);
            uint32_t a0 = o1 ? s0 : v0, a1 = o1 ? v1 : s0, b0 = o1 ? s1 : v2, b1 = o1 ? v3 : s1;
            uint32_t x0 = o2 ? a0 : b0, x1 = o2 ? a1 : b1;
            x0 = __shfl_xor_sync(0xffffffffu, x0, 2); x1 = __shfl_xor_sync(0xffffffffu, x1, 2);
            uint4 r;
            r.x = o2 ? x0 : a0; r.y = o2 ? x1 : a1; r.z = o2 ? b0 : x0; r.w = o2 ? b1 : x1;
            *(uint4*)(g_o + (size_t)(row0 + (t >> 1) * 8) * DM + head * 16 + (t & 1) * 8) = r;
        }
        if (tid == 0) TSTAMP0(1, 4 + pass);
    }
    if (warp_u != 10) named_arrive(1, 512);
    named_sync(4 + wg, 128);
    if ((tid & 127) == 0) {
        asm volatile("fence.acq_rel.gpu;" ::: "memory");
        asm volatile("red.relaxed.gpu.global.add.u32 [%0], 1;" ::"l"(&g_oflag[(quarter * 8 + 4 + wg) * 32 + (head >> 2) * 4]) : "memory");
        asm volatile("red.relaxed.gpu.global.add.u32 [%0], 1;" ::"l"(&g_oflag[(quarter * 8 + wg) * 32 + (head >> 2) * 4]) : "memory");
    }
    if (tid == 0) TSTAMP0(1, 3);

    if (wg < 2) {
        const int wi = warp;
        const int r0 = mt * 64 + wi * 16 + g;
        const int cb = nt * 128 + wg * 64;
        uint32_t xr[16], wr[8];
#pragma unroll
        for (int j = 0; j < 8; j++) {
            xr[2 * j] = __ldg((const uint32_t*)(x + (size_t)r0 * DM + cb + 8 * j + 2 * t));
            xr[2 * j + 1] = __ldg((const uint32_t*)(x + (size_t)(r0 + 8) * DM + cb + 8 * j + 2 * t));
            wr[j] = __ldg((const uint32_t*)(w_r + cb + 8 * j + 2 * t));
        }
        float wsum = 0.f;
        {
            const uint4 a = __ldg((const uint4*)(w_r + lane * 16)), b = __ldg((const uint4*)(w_r + lane * 16 + 8));
            const uint32_t w[8] = {a.x, a.y, a.z, a.w, b.x, b.y, b.z, b.w};
#pragma unroll
            for (int i = 0; i < 8; i++) wsum += bf_lo(w[i]) + bf_hi(w[i]);
#pragma unroll
            for (int o = 16; o > 0; o >>= 1) wsum += __shfl_xor_sync(0xffffffffu, wsum, o);
        }
        float acc[32];
#pragma unroll
        for (int i = 0; i < 32; i++) acc[i] = 0.f;
        fence_regs(acc);
#pragma unroll 1
        for (int i = 0; i < 8; i++) {
            mbar_wait(obar + 8 * i, 0);
            const int kb = __shfl_sync(0xffffffffu, (int)s_order[i], 0);
            mbar_wait(wbar + 8 * kb, 0);
            const uint32_t wa = (kb < 4) ? (KF_OFF_WO + kb * 16384) : ((kb - 4) * KF_CH_S);
            const uint64_t da = make_desc(sb + (4 + (kb >> 1)) * KF_CH_S + (kb & 1) * 8192, 16, 1024, 1);
            const uint64_t db = make_desc(sb + wa + wg * 8192, 1024, 1024, 1);
            wg_fence();
#pragma unroll
            for (int k = 0; k < 4; k++) wgmma_k3_n64(acc, da + k * 2, db + k * 128, (i | k) != 0);
            wg_commit();
        }
        wg_wait<0>();
        fence_regs(acc);
        if (tid == 0) TSTAMP0(2, 2);
        float hv[32];
        uint32_t hp[16];
        float s0 = 0.f, s1 = 0.f, d0 = 0.f, d1 = 0.f;
#pragma unroll
        for (int j = 0; j < 8; j++) {
            const uint32_t a01 = pack_bf16(acc[4 * j], acc[4 * j + 1]), a23 = pack_bf16(acc[4 * j + 2], acc[4 * j + 3]);
            hp[2 * j] = pack_bf16(bf_lo(xr[2 * j]) + bf_lo(a01), bf_hi(xr[2 * j]) + bf_hi(a01));
            hp[2 * j + 1] = pack_bf16(bf_lo(xr[2 * j + 1]) + bf_lo(a23), bf_hi(xr[2 * j + 1]) + bf_hi(a23));
            hv[4 * j] = bf_lo(hp[2 * j]); hv[4 * j + 1] = bf_hi(hp[2 * j]);
            hv[4 * j + 2] = bf_lo(hp[2 * j + 1]); hv[4 * j + 3] = bf_hi(hp[2 * j + 1]);
            const float wl = bf_lo(wr[j]), wh = bf_hi(wr[j]);
            s0 += hv[4 * j] + hv[4 * j + 1];
            s1 += hv[4 * j + 2] + hv[4 * j + 3];
            d0 = fmaf(hv[4 * j], wl, fmaf(hv[4 * j + 1], wh, d0));
            d1 = fmaf(hv[4 * j + 2], wl, fmaf(hv[4 * j + 3], wh, d1));
        }
        float mu0 = s0 * (1.f / 16), mu1 = s1 * (1.f / 16);
        float q0 = 0.f, q1 = 0.f;
#pragma unroll
        for (int j = 0; j < 8; j++) {
            float a = hv[4 * j] - mu0, b = hv[4 * j + 1] - mu0, c = hv[4 * j + 2] - mu1, d = hv[4 * j + 3] - mu1;
            q0 = fmaf(a, a, fmaf(b, b, q0));
            q1 = fmaf(c, c, fmaf(d, d, q1));
        }
#pragma unroll
        for (int o = 1; o < 4; o <<= 1) {
            const float m0 = __shfl_xor_sync(0xffffffffu, mu0, o), m1 = __shfl_xor_sync(0xffffffffu, mu1, o);
            const float e0 = __shfl_xor_sync(0xffffffffu, q0, o), e1 = __shfl_xor_sync(0xffffffffu, q1, o);
            d0 += __shfl_xor_sync(0xffffffffu, d0, o);
            d1 += __shfl_xor_sync(0xffffffffu, d1, o);
            const float f0 = mu0 - m0, f1 = mu1 - m1;
            q0 = q0 + e0 + f0 * f0 * (8.f * o);
            q1 = q1 + e1 + f1 * f1 * (8.f * o);
            mu0 = 0.5f * (mu0 + m0); mu1 = 0.5f * (mu1 + m1);
        }
        float4* part = g_part + (size_t)mt * 512 + wi * 16 + g;
        if (t < 2) {
            float4* dst = part + (nt * 2 + wg) * 64 + t * 8;
            const float a = t ? mu1 : mu0, b = t ? q1 : q0, c = t ? d1 : d0;
            asm volatile("st.relaxed.gpu.global.v4.f32 [%0], {%1, %2, %3, %4};" ::"l"(dst), "f"(a), "f"(b), "f"(c), "f"(__uint_as_float(tag)) : "memory");
        }
        if (tid == 0) TSTAMP0(2, 5);
        const uint32_t stg_off = KF_OFF_WO + (wi >> 1) * 16384 + wg * 8192 + (wi & 1) * 4096;
        const uint32_t stg_o = sb + stg_off, stg_h = stg_o + 2048;
        const int srow = (lane & 7) + ((lane >> 3) & 1) * 8;
        const int sj = lane >> 4;
        named_sync(4 + wg, 128);
#pragma unroll
        for (int j = 0; j < 8; j += 2) {
            const uint32_t off = srow * 128 + (((j + sj) ^ (srow & 7)) << 4);
            stmatrix_x4(stg_h + off, hp[2 * j], hp[2 * j + 1], hp[2 * j + 2], hp[2 * j + 3]);
        }
        __syncwarp();
#pragma unroll
        for (int i = 0; i < 4; i++) {
            const int row = i * 4 + (lane >> 3), ch = lane & 7;
            const uint4 vh = *(const uint4*)(sp + stg_off + 2048 + row * 128 + ((ch ^ (row & 7)) << 4));
            *(uint4*)(g_h + (size_t)(mt * 64 + wi * 16 + row) * DM + cb + ch * 8) = vh;
        }
        named_arrive(8, 288);
        if (tid == 0) TSTAMP0(2, 6);
        float mean[2], den[2], rr[2];
        {
            float4 v[4];
            int spins = 0;
            while (true) {
#pragma unroll
                for (int i = 0; i < 4; i++) {
                    const float4* p = part + (t + (i & 1) * 4) * 64 + (i >> 1) * 8;
                    asm volatile("ld.relaxed.gpu.global.v4.f32 {%0, %1, %2, %3}, [%4];" : "=f"(v[i].x), "=f"(v[i].y), "=f"(v[i].z), "=f"(v[i].w) : "l"(p) : "memory");
                }
                const bool ok = (__float_as_uint(v[0].w) == tag) && (__float_as_uint(v[1].w) == tag) && (__float_as_uint(v[2].w) == tag) && (__float_as_uint(v[3].w) == tag);
                if (__all_sync(0xffffffffu, ok) || ++spins > (1 << 22)) break;
            }
#pragma unroll
            for (int u = 0; u < 2; u++) {
                float mu = v[2 * u].x + v[2 * u + 1].x, m2 = v[2 * u].y + v[2 * u + 1].y, hw = v[2 * u].z + v[2 * u + 1].z;
#pragma unroll
                for (int o = 1; o < 4; o <<= 1) {
                    mu += __shfl_xor_sync(0xffffffffu, mu, o);
                    m2 += __shfl_xor_sync(0xffffffffu, m2, o);
                    hw += __shfl_xor_sync(0xffffffffu, hw, o);
                }
                mu *= 0.125f;
                const float da = v[2 * u].x - mu, db = v[2 * u + 1].x - mu;
                float dd = 64.f * (da * da + db * db);
#pragma unroll
                for (int o = 1; o < 4; o <<= 1) dd += __shfl_xor_sync(0xffffffffu, dd, o);
                m2 += dd;
                mean[u] = rbf(mu);
                den[u] = rbf(sqrtf(rbf(rbf(m2 * (1.f / DM)) + 1e-5f)));
                rr[u] = rbf((hw - mean[u] * wsum) / den[u]);
            }
        }
        if (tid == 0) TSTAMP0(2, 3);
        named_arrive(3, 512);
        if (nt == 0 && wg == 0) {
            float2* s_st = (float2*)(sp + KF_OFF_WO + 49152);
            if (t == 0) {
                s_key[wi * 16 + g] = make_key(rr[0], r0);
                s_key[wi * 16 + g + 8] = make_key(rr[1], r0 + 8);
                s_st[wi * 16 + g] = make_float2(mean[0], den[0]);
                s_st[wi * 16 + g + 8] = make_float2(mean[1], den[1]);
            }
            named_sync(4, 128);
            if (warp == 0) {
                uint32_t k1, k2;
                warp_top2(s_key[lane], s_key[lane + 32], k1, k2);
                if (lane < 2) {
                    const uint32_t k = lane ? k2 : k1;
                    const float2 st = s_st[key_token(k) & 63];
                    asm volatile("st.relaxed.gpu.global.v4.u32 [%0], {%1, %2, %3, %4};" ::"l"(g_cand + mt * 2 + lane), "r"(k),
                                 "r"(tag), "r"(__float_as_uint(st.x)), "r"(__float_as_uint(st.y)) : "memory");
                }
            }
        }
        const float i0 = 1.f / den[0], i1 = 1.f / den[1];
#pragma unroll
        for (int j = 0; j < 8; j += 2) {
            uint32_t ro[4];
#pragma unroll
            for (int u = 0; u < 2; u++) {
                const int jj = j + u;
                const float a = hv[4 * jj], b = hv[4 * jj + 1], c = hv[4 * jj + 2], d = hv[4 * jj + 3];
                const uint32_t u01 = pack_bf16(a - mean[0], b - mean[0]), u23 = pack_bf16(c - mean[1], d - mean[1]);
                const uint32_t n01 = pack_bf16(bf_lo(u01) * i0, bf_hi(u01) * i0), n23 = pack_bf16(bf_lo(u23) * i1, bf_hi(u23) * i1);
                ro[2 * u] = pack_bf16(a + bf_lo(n01), b + bf_hi(n01));
                ro[2 * u + 1] = pack_bf16(c + bf_lo(n23), d + bf_hi(n23));
            }
            const uint32_t off = srow * 128 + (((j + sj) ^ (srow & 7)) << 4);
            stmatrix_x4(stg_o + off, ro[0], ro[1], ro[2], ro[3]);
        }
        __syncwarp();
#pragma unroll
        for (int i = 0; i < 4; i++) {
            const int row = i * 4 + (lane >> 3), ch = lane & 7;
            const uint4 vo = *(const uint4*)(sp + stg_off + row * 128 + ((ch ^ (row & 7)) << 4));
            *(uint4*)(out + (size_t)(mt * 64 + wi * 16 + row) * DM + cb + ch * 8) = vo;
        }
        named_sync(4 + wg, 128);
        if ((tid & 127) == 0) red_release_add(&g_sflag[mt]);
        if (tid == 0) TSTAMP0(2, 4);
    } else {
        const bool worker = blockIdx.x < FF / 16;
        const bool downer = blockIdx.x >= 64;
        const int mtid = tid - 256, mwarp = warp_u - 8;
        const int c0 = (blockIdx.x - 64) * 8;
        float* s_x = (float*)(sp + KF_OFF_WO + 49152 + 8192);
        float* s_red = (float*)(sp + KF_OFF_WO + 49152 + 8192 + 4096);
        if (mwarp == 2) {
            named_sync(1, 512);
            uint32_t done = 0;
            int n = 0, spins = 0;
            while (done != 0xFFu && ++spins < (1 << 22)) {
                const bool rdy = lane < 8 && (int)(ld_acquire(&g_oflag[mt * 32 + lane * 4]) - 4u * tag) >= 0;
                uint32_t todo = __ballot_sync(0xffffffffu, rdy) & ~done;
                done |= todo;
                if (todo && lane == 0) {
                    asm volatile("fence.proxy.async.global;" ::: "memory");
                    while (todo) {
                        const int kb = __ffs(todo) - 1;
                        todo &= todo - 1;
                        s_order[n] = kb;
                        mbar_expect_tx(obar + 8 * n, 8192);
                        tma_load_3d(sb + (4 + (kb >> 1)) * KF_CH_S + (kb & 1) * 8192, &tm_o, 0, mt * 64, kb, obar + 8 * n);
                        n++;
                    }
                }
                n = __shfl_sync(0xffffffffu, n, 0);
                if (done != 0xFFu) __nanosleep(POLL_NS);
            }
            if (lane == 0) TSTAMP0(2, 1);
            if (lane == 0 && worker) {
                mbar_expect_tx(gbar, 32768);
                for (int i = 0; i < 4; i++) {
                    tma_load_2d(sb + i * KF_CH_S + 16384, &tm_g, blockIdx.x * 16, i * 128, gbar);
                    tma_load_2d(sb + (4 + i) * KF_CH_S + 16384, &tm_u, blockIdx.x * 16, i * 128, gbar);
                }
            }
        }
        if (mwarp == 1) {
            named_sync(8, 288);
            if (lane == 0) {
                red_release_add(&g_hflag[mt]);
                if (downer) {
                    mbar_expect_tx(dbar, 7 * 4096);
                    for (int i = 0; i < 7; i++) tma_load_2d(sb + (4 + (i >> 2)) * KF_CH_S + (i & 3) * 4096, &tm_d, c0, i * 256, dbar);
                }
            }
            __syncwarp();
        }
        if (mtid == 0) TSTAMP0(3, 0);
        named_sync(3, 512);
        if (mwarp == 0) {
            uint4 ca, cb4;
            int spins = 0;
            while (true) {
                asm volatile("ld.relaxed.gpu.global.v4.u32 {%0, %1, %2, %3}, [%4];" : "=r"(ca.x), "=r"(ca.y), "=r"(ca.z), "=r"(ca.w) : "l"(g_cand + 2 * lane) : "memory");
                asm volatile("ld.relaxed.gpu.global.v4.u32 {%0, %1, %2, %3}, [%4];" : "=r"(cb4.x), "=r"(cb4.y), "=r"(cb4.z), "=r"(cb4.w) : "l"(g_cand + 2 * lane + 1) : "memory");
                const unsigned int hf = ld_acquire(&g_hflag[lane]);
                const bool ok = ca.y == tag && cb4.y == tag && (int)(hf - 4u * tag) >= 0;
                if (__all_sync(0xffffffffu, ok) || ++spins > (1 << 22)) break;
            }
            uint32_t k1, k2;
            warp_top2(ca.x, cb4.x, k1, k2);
            if (ca.x == k1) s_sel[0] = ca;
            if (cb4.x == k1) s_sel[0] = cb4;
            if (ca.x == k2) s_sel[1] = ca;
            if (cb4.x == k2) s_sel[1] = cb4;
        }
        named_sync(2, 256);
        if (mtid == 0) TSTAMP0(3, 1);
        int idx[2];
        float mean[2], inv[2], rv[2];
#pragma unroll
        for (int u = 0; u < 2; u++) {
            const uint4 c = s_sel[u];
            idx[u] = key_token(c.x);
            rv[u] = key_value(c.x);
            mean[u] = __uint_as_float(c.z);
            inv[u] = 1.f / __uint_as_float(c.w);
        }
        float hfin = 0.f;
        if (downer && mtid < 16) hfin = __bfloat162float(__ldcg((const __nv_bfloat16*)(g_h + (size_t)((mtid >> 3) ? idx[1] : idx[0]) * DM + c0 + (mtid & 7))));
        if (worker) {
            {
                const uint32_t h0 = __ldcg((const uint32_t*)(g_h + (size_t)idx[0] * DM + 2 * mtid));
                const uint32_t h1 = __ldcg((const uint32_t*)(g_h + (size_t)idx[1] * DM + 2 * mtid));
                const uint32_t u0 = pack_bf16(bf_lo(h0) - mean[0], bf_hi(h0) - mean[0]), u1 = pack_bf16(bf_lo(h1) - mean[1], bf_hi(h1) - mean[1]);
                const uint32_t n0 = pack_bf16(bf_lo(u0) * inv[0], bf_hi(u0) * inv[0]), n1 = pack_bf16(bf_lo(u1) * inv[1], bf_hi(u1) * inv[1]);
                *(float4*)(s_x + 4 * mtid) = make_float4(bf_lo(n0), bf_lo(n1), bf_hi(n0), bf_hi(n1));
            }
            if (mtid == 0) TSTAMP0(3, 5);
            mbar_wait(gbar, 0);
            named_sync(2, 256);
            if (mtid == 0) TSTAMP0(3, 6);
            float acc[8];
#pragma unroll
            for (int i = 0; i < 8; i++) acc[i] = 0.f;
            const uint8_t* wbase = sp + (mwarp >> 2) * (4 * KF_CH_S) + 16384 + lane * 32 + (mwarp & 3) * 8;
#pragma unroll
            for (int k = 0; k < 16; k++) {
                const uint2 w = *(const uint2*)(wbase + (k >> 2) * KF_CH_S + (k & 3) * 1024);
                const float2 xx = *(const float2*)(s_x + 2 * (lane + 32 * k));
                const float x0 = xx.x, x1 = xx.y;
                const float w0 = bf_lo(w.x), w1 = bf_hi(w.x), w2 = bf_lo(w.y), w3 = bf_hi(w.y);
                acc[0] = fmaf(x0, w0, acc[0]); acc[1] = fmaf(x0, w1, acc[1]); acc[2] = fmaf(x0, w2, acc[2]); acc[3] = fmaf(x0, w3, acc[3]);
                acc[4] = fmaf(x1, w0, acc[4]); acc[5] = fmaf(x1, w1, acc[5]); acc[6] = fmaf(x1, w2, acc[6]); acc[7] = fmaf(x1, w3, acc[7]);
            }
#define KF_STEP(O, N)                                                          \
            {                                                                  \
                const bool up = (lane & (O)) != 0;                             \
                _Pragma("unroll") for (int i = 0; i < (N); i++) {              \
                    const float send = up ? acc[i] : acc[i + (N)];             \
                    const float keep = up ? acc[i + (N)] : acc[i];             \
                    acc[i] = keep + __shfl_xor_sync(0xffffffffu, send, (O));   \
                }                                                              \
            }
            KF_STEP(16, 4) KF_STEP(8, 2) KF_STEP(4, 1)
            acc[0] += __shfl_xor_sync(0xffffffffu, acc[0], 2);
            acc[0] += __shfl_xor_sync(0xffffffffu, acc[0], 1);
            if ((lane & 3) == 0) {
                const int v = ((lane & 16) ? 4 : 0) + ((lane & 8) ? 2 : 0) + ((lane & 4) ? 1 : 0);
                s_gu[(v >> 2) * 32 + mwarp * 4 + (v & 3)] = acc[0];
            }
            named_sync(2, 256);
            if (mtid < 16) {
                uint32_t a2 = 0;
#pragma unroll
                for (int u = 0; u < 2; u++) {
                    const float gb = rbf(s_gu[u * 32 + mtid]);
                    const float sg = rbf(gb / (1.f + __expf(-gb)));
                    float a = sg * rbf(s_gu[u * 32 + 16 + mtid]);
                    a2 |= (uint32_t)__bfloat16_as_ushort(__float2bfloat16_rn(a)) << (16 * u);
                }
                asm volatile("st.relaxed.gpu.global.v2.u32 [%0], {%1, %2};" ::"l"(g_act + blockIdx.x * 16 + mtid), "r"(a2), "r"(tag) : "memory");
            }
            if (mtid == 0) TSTAMP0(3, 2);
        }
        if (downer) {
            uint32_t av[7];
            {
                int spins = 0;
                while (true) {
                    bool ok = true;
#pragma unroll
                    for (int j = 0; j < 7; j++) {
                        uint32_t tg;
                        asm volatile("ld.relaxed.gpu.global.v2.u32 {%0, %1}, [%2];" : "=r"(av[j]), "=r"(tg) : "l"(g_act + mtid + 256 * j) : "memory");
                        ok = ok && tg == tag;
                    }
                    if (mtid < 2) ok = ok && ((int)(ld_acquire(&g_sflag[(mtid ? idx[1] : idx[0]) >> 6]) - 8u * tag) >= 0);
                    if (__all_sync(0xffffffffu, ok) || ++spins > (1 << 20)) break;
                    __nanosleep(20);
                }
            }
            if (mtid == 0) TSTAMP0(3, 3);
            mbar_wait(dbar, 0);
            float acc[16];
#pragma unroll
            for (int i = 0; i < 16; i++) acc[i] = 0.f;
#pragma unroll
            for (int j = 0; j < 7; j++) {
                const uint4 w = *(const uint4*)(sp + (4 + (j >> 2)) * KF_CH_S + (j & 3) * 4096 + mtid * 16);
                const float a0 = bf_lo(av[j]), a1 = bf_hi(av[j]);
                const uint32_t ww[4] = {w.x, w.y, w.z, w.w};
#pragma unroll
                for (int q = 0; q < 4; q++) {
                    const float wl = bf_lo(ww[q]), wh = bf_hi(ww[q]);
                    acc[2 * q] = fmaf(a0, wl, acc[2 * q]); acc[2 * q + 1] = fmaf(a0, wh, acc[2 * q + 1]);
                    acc[8 + 2 * q] = fmaf(a1, wl, acc[8 + 2 * q]); acc[8 + 2 * q + 1] = fmaf(a1, wh, acc[8 + 2 * q + 1]);
                }
            }
            KF_STEP(16, 8) KF_STEP(8, 4) KF_STEP(4, 2) KF_STEP(2, 1)
            acc[0] += __shfl_xor_sync(0xffffffffu, acc[0], 1);
            if ((lane & 1) == 0) {
                const int v = ((lane & 16) ? 8 : 0) + ((lane & 8) ? 4 : 0) + ((lane & 4) ? 2 : 0) + ((lane & 2) ? 1 : 0);
                s_red[mwarp * 16 + v] = acc[0];
            }
            named_sync(2, 256);
            if (mtid < 16) {
                const int u = mtid >> 3;
                float y = 0.f;
#pragma unroll
                for (int w = 0; w < 8; w++) y += s_red[w * 16 + mtid];
                const float sig = rbf(1.f / (1.f + __expf(-(u ? rv[1] : rv[0]))));
                const float xn = rbf(rbf(hfin - (u ? mean[1] : mean[0])) * (u ? inv[1] : inv[0]));
                const float ov = hfin + rbf(xn + rbf(rbf(y) * sig));
                out[(size_t)(u ? idx[1] : idx[0]) * DM + c0 + (mtid & 7)] = __float2bfloat16_rn(ov);
            }
            if (blockIdx.x == gridDim.x - 1 && mtid == 0) g_epoch = tag;
            if (mtid == 0) TSTAMP0(3, 4);
        }
    }
}

typedef CUresult (*PFN_encodeTiled)(CUtensorMap*, CUtensorMapDataType, cuuint32_t, void*, const cuuint64_t*, const cuuint64_t*,
                                    const cuuint32_t*, const cuuint32_t*, CUtensorMapInterleave, CUtensorMapSwizzle,
                                    CUtensorMapL2promotion, CUtensorMapFloatOOBfill);

void make_map(PFN_encodeTiled enc, CUtensorMap* m, const void* ptr, uint64_t cols, uint64_t rows, uint32_t bcols, uint32_t brows) {
    cuuint64_t dims[2] = {cols, rows};
    cuuint64_t strides[1] = {cols * 2};
    cuuint32_t box[2] = {bcols, brows};
    cuuint32_t es[2] = {1, 1};
    enc(m, CU_TENSOR_MAP_DATA_TYPE_BFLOAT16, 2, const_cast<void*>(ptr), dims, strides, box, es, CU_TENSOR_MAP_INTERLEAVE_NONE,
        CU_TENSOR_MAP_SWIZZLE_128B, CU_TENSOR_MAP_L2_PROMOTION_L2_256B, CU_TENSOR_MAP_FLOAT_OOB_FILL_NONE);
}

void make_map3(PFN_encodeTiled enc, CUtensorMap* m, const void* ptr, uint64_t d0, uint64_t rows, uint64_t d2, uint64_t row_stride_bytes,
               uint64_t d2_stride_bytes, uint32_t b0, uint32_t b1, uint32_t b2) {
    cuuint64_t dims[3] = {d0, rows, d2};
    cuuint64_t strides[2] = {row_stride_bytes, d2_stride_bytes};
    cuuint32_t box[3] = {b0, b1, b2};
    cuuint32_t es[3] = {1, 1, 1};
    enc(m, CU_TENSOR_MAP_DATA_TYPE_BFLOAT16, 3, const_cast<void*>(ptr), dims, strides, box, es, CU_TENSOR_MAP_INTERLEAVE_NONE,
        CU_TENSOR_MAP_SWIZZLE_128B, CU_TENSOR_MAP_L2_PROMOTION_L2_256B, CU_TENSOR_MAP_FLOAT_OOB_FILL_NONE);
}

void make_map_plain(PFN_encodeTiled enc, CUtensorMap* m, const void* ptr, uint64_t cols, uint64_t rows, uint32_t bcols, uint32_t brows) {
    cuuint64_t dims[2] = {cols, rows};
    cuuint64_t strides[1] = {cols * 2};
    cuuint32_t box[2] = {bcols, brows};
    cuuint32_t es[2] = {1, 1};
    enc(m, CU_TENSOR_MAP_DATA_TYPE_BFLOAT16, 2, const_cast<void*>(ptr), dims, strides, box, es, CU_TENSOR_MAP_INTERLEAVE_NONE,
        CU_TENSOR_MAP_SWIZZLE_NONE, CU_TENSOR_MAP_L2_PROMOTION_NONE, CU_TENSOR_MAP_FLOAT_OOB_FILL_NONE);
}

template <typename... KArgs, typename... Args>
void launch(void (*kern)(KArgs...), int grid, int block, int smem, bool pdl, Args... args) {
    cudaLaunchConfig_t cfg = {};
    cfg.gridDim = dim3(grid);
    cfg.blockDim = dim3(block);
    cfg.dynamicSmemBytes = smem;
    cfg.stream = cudaStreamPerThread;
    cudaLaunchAttribute at[1];
    at[0].id = cudaLaunchAttributeProgrammaticStreamSerialization;
    at[0].val.programmaticStreamSerializationAllowed = 1;
    cfg.attrs = at;
    cfg.numAttrs = pdl ? 1 : 0;
    cudaLaunchKernelEx(&cfg, kern, KArgs(args)...);
}

}

extern "C" void kernel_launch(void* const* d_in, const int* in_sizes, int n_in, void* d_out, int out_size) {
    const __nv_bfloat16* x = (const __nv_bfloat16*)d_in[0];
    const __nv_bfloat16* wqkv = (const __nv_bfloat16*)d_in[1];
    const __nv_bfloat16* wo = (const __nv_bfloat16*)d_in[2];
    const __nv_bfloat16* w_r = (const __nv_bfloat16*)d_in[4];
    const __nv_bfloat16* w_gate = (const __nv_bfloat16*)d_in[5];
    const __nv_bfloat16* w_up = (const __nv_bfloat16*)d_in[6];
    const __nv_bfloat16* w_down = (const __nv_bfloat16*)d_in[7];
    __nv_bfloat16* out = (__nv_bfloat16*)d_out;

    static PFN_encodeTiled enc = nullptr;
    static void* g_o_ptr = nullptr;
    if (!enc) {
        cudaDriverEntryPointQueryResult qres;
        void* fn = nullptr;
        cudaGetDriverEntryPoint("cuTensorMapEncodeTiled", &fn, cudaEnableDefault, &qres);
        enc = (PFN_encodeTiled)fn;
        cudaGetSymbolAddress(&g_o_ptr, g_o);
        cudaFuncSetAttribute(kf_main, cudaFuncAttributeMaxDynamicSharedMemorySize, KF_SMEM);
    }
    CUtensorMap tm_x, tm_w, tm_o, tm_wo, tm_g, tm_u, tm_d;
    make_map_plain(enc, &tm_d, w_down, DM, FF, 8, 256);
    make_map_plain(enc, &tm_g, w_gate, FF, DM, 16, 128);
    make_map_plain(enc, &tm_u, w_up, FF, DM, 16, 128);
    make_map(enc, &tm_x, x, DM, SEQ, 64, 128);
    make_map3(enc, &tm_w, wqkv, DM, DM, 3, 3 * DM * 2, DM * 2, 64, 64, 3);
    make_map3(enc, &tm_o, g_o_ptr, 64, SEQ, 8, DM * 2, 128, 64, 64, 1);
    make_map3(enc, &tm_wo, wo, 64, DM, 8, DM * 2, 128, 64, 64, 2);

    launch(kf_main, 128, 512, KF_SMEM, false, tm_x, tm_w, tm_o, tm_wo, tm_g, tm_u, tm_d, x, wo, w_r, w_gate, w_up, w_down, out);
}
```

```cpp
#include <cuda_runtime.h>
#include <cuda_bf16.h>
#include <cuda.h>
#include <stdint.h>

namespace {

constexpr int SEQ = 2048, DM = 512, NH = 32, FF = 1792;

__device__ __align__(1024) uint8_t g_q[NH * 2 * SEQ * 16];
__device__ __align__(1024) uint8_t g_kv[NH * 8 * 16384];
__device__ float g_norm[16 * NH * 3];
__device__ __align__(1024) __nv_bfloat16 g_o[SEQ * DM];
__device__ __align__(1024) __nv_bfloat16 g_h[SEQ * DM];
__device__ __align__(16) uint4 g_cand[64];
__device__ unsigned int g_oflag[32 * 32];
__device__ unsigned int g_hflag[32];
__device__ unsigned int g_sflag[32];
__device__ unsigned int g_act[FF];
__device__ unsigned int g_epoch;
__device__ __align__(16) float4 g_ln1[SEQ];
__device__ __align__(16) float4 g_part[32 * 8 * 64];

#define TSTAMP(K, I)
#define TSTAMP0(K, I)
__device__ __forceinline__ uint32_t smem_u32(const void* p) { return (uint32_t)__cvta_generic_to_shared(p); }
__device__ __forceinline__ void wg_fence() { asm volatile("wgmma.fence.sync.aligned;" ::: "memory"); }
__device__ __forceinline__ void wg_commit() { asm volatile("wgmma.commit_group.sync.aligned;" ::: "memory"); }
template <int N> __device__ __forceinline__ void wg_wait() { asm volatile("wgmma.wait_group.sync.aligned %0;" ::"n"(N) : "memory"); }
template <int N> __device__ __forceinline__ void fence_regs(float (&r)[N]) {
#pragma unroll
    for (int i = 0; i < N; i++) asm volatile("" : "+f"(r[i])::"memory");
}
__device__ __forceinline__ uint64_t make_desc(uint32_t addr, uint32_t lbo, uint32_t sbo, uint32_t swz) {
    uint64_t d = 0;
    d |= (uint64_t)((addr & 0x3FFFF) >> 4);
    d |= (uint64_t)((lbo & 0x3FFFF) >> 4) << 16;
    d |= (uint64_t)((sbo & 0x3FFFF) >> 4) << 32;
    d |= (uint64_t)swz << 62;
    return d;
}
__device__ __forceinline__ void mbar_init(uint32_t bar, uint32_t cnt) {
    asm volatile("mbarrier.init.shared::cta.b64 [%0], %1;" ::"r"(bar), "r"(cnt) : "memory");
}
__device__ __forceinline__ void mbar_expect_tx(uint32_t bar, uint32_t bytes) {
    asm volatile("mbarrier.arrive.expect_tx.shared::cta.b64 _, [%0], %1;" ::"r"(bar), "r"(bytes) : "memory");
}
__device__ __forceinline__ void mbar_arrive(uint32_t bar) {
    asm volatile("mbarrier.arrive.shared::cta.b64 _, [%0];" ::"r"(bar) : "memory");
}
__device__ __forceinline__ void mbar_wait(uint32_t bar, uint32_t parity) {
    asm volatile(
        "{\n.reg .pred p;\nWAIT_%=:\n"
        "mbarrier.try_wait.parity.shared::cta.b64 p, [%0], %1;\n"
        "@p bra DONE_%=;\nbra WAIT_%=;\nDONE_%=:\n}\n" ::"r"(bar), "r"(parity) : "memory");
}
__device__ __forceinline__ void bulk_g2s(uint32_t dst, const void* src, uint32_t bytes, uint32_t bar) {
    asm volatile("cp.async.bulk.shared::cluster.global.mbarrier::complete_tx::bytes [%0], [%1], %2, [%3];" ::"r"(dst),
                 "l"(src), "r"(bytes), "r"(bar) : "memory");
}
__device__ __forceinline__ void bulk_s2g(void* dst, uint32_t src, uint32_t bytes) {
    asm volatile("cp.async.bulk.global.shared::cta.bulk_group [%0], [%1], %2;" ::"l"(dst), "r"(src), "r"(bytes) : "memory");
}
__device__ __forceinline__ void tma_load_2d(uint32_t dst, const CUtensorMap* tm, int c0, int c1, uint32_t bar) {
    asm volatile("cp.async.bulk.tensor.2d.shared::cluster.global.mbarrier::complete_tx::bytes [%0], [%1, {%3, %4}], [%2];" ::"r"(dst),
                 "l"(tm), "r"(bar), "r"(c0), "r"(c1) : "memory");
}
__device__ __forceinline__ void tma_load_3d(uint32_t dst, const CUtensorMap* tm, int c0, int c1, int c2, uint32_t bar) {
    asm volatile("cp.async.bulk.tensor.3d.shared::cluster.global.mbarrier::complete_tx::bytes [%0], [%1, {%3, %4, %5}], [%2];" ::"r"(dst),
                 "l"(tm), "r"(bar), "r"(c0), "r"(c1), "r"(c2) : "memory");
}
__device__ __forceinline__ void tma_load_2d_mc(uint32_t dst, const CUtensorMap* tm, int c0, int c1, uint32_t bar, uint16_t mask) {
    asm volatile("cp.async.bulk.tensor.2d.shared::cluster.global.mbarrier::complete_tx::bytes.multicast::cluster [%0], [%1, {%3, %4}], [%2], %5;" ::"r"(dst),
                 "l"(tm), "r"(bar), "r"(c0), "r"(c1), "h"(mask) : "memory");
}
__device__ __forceinline__ void mbar_arrive_cluster(uint32_t bar, uint32_t cta) {
    asm volatile("{\n.reg .b32 ra;\nmapa.shared::cluster.u32 ra, %0, %1;\nmbarrier.arrive.release.cluster.shared::cluster.b64 _, [ra];\n}" ::"r"(bar), "r"(cta) : "memory");
}
__device__ __forceinline__ void cluster_sync() {
    asm volatile("barrier.cluster.arrive.release.aligned;\nbarrier.cluster.wait.acquire.aligned;" ::: "memory");
}
__device__ __forceinline__ void prefetch_l2(const void* p, uint32_t bytes) {
    asm volatile("cp.async.bulk.prefetch.L2.global [%0], %1;" ::"l"(p), "r"(bytes) : "memory");
}
__device__ __forceinline__ void fence_proxy_async() { asm volatile("fence.proxy.async.shared::cta;" ::: "memory"); }
__device__ __forceinline__ void fence_barrier_init() { asm volatile("fence.mbarrier_init.release.cluster;" ::: "memory"); }
__device__ __forceinline__ void pdl_launch() { asm volatile("griddepcontrol.launch_dependents;" ::: "memory"); }
__device__ __forceinline__ void pdl_wait() { asm volatile("griddepcontrol.wait;" ::: "memory"); }
__device__ __forceinline__ void named_sync(int id, int n) { asm volatile("bar.sync %0, %1;" ::"r"(id), "r"(n) : "memory"); }
__device__ __forceinline__ void named_arrive(int id, int n) { asm volatile("bar.arrive %0, %1;" ::"r"(id), "r"(n) : "memory"); }

__device__ __forceinline__ float ex2f(float x) { float y; asm("ex2.approx.ftz.f32 %0, %1;" : "=f"(y) : "f"(x)); return y; }
__device__ __forceinline__ uint32_t pack_bf16(float lo, float hi) {
    uint32_t r; asm("cvt.rn.bf16x2.f32 %0, %1, %2;" : "=r"(r) : "f"(hi), "f"(lo)); return r;
}
__device__ __forceinline__ float bf_lo(uint32_t v) { return __uint_as_float(v << 16); }
__device__ __forceinline__ float bf_hi(uint32_t v) { return __uint_as_float(v & 0xFFFF0000u); }
__device__ __forceinline__ float rbf(float x) { return __bfloat162float(__float2bfloat16_rn(x)); }
__device__ __forceinline__ uint32_t fma_bf16x2(uint32_t a, uint32_t b, uint32_t c) {
    uint32_t r; asm("fma.rn.bf16x2 %0, %1, %2, %3;" : "=r"(r) : "r"(a), "r"(b), "r"(c)); return r;
}
__device__ __forceinline__ void stmatrix_x4(uint32_t addr, uint32_t r0, uint32_t r1, uint32_t r2, uint32_t r3) {
    asm volatile("stmatrix.sync.aligned.m8n8.x4.shared.b16 [%0], {%1, %2, %3, %4};" ::"r"(addr), "r"(r0), "r"(r1), "r"(r2), "r"(r3) : "memory");
}
__device__ __forceinline__ void stmatrix_x4_trans(uint32_t addr, uint32_t r0, uint32_t r1, uint32_t r2, uint32_t r3) {
    asm volatile("stmatrix.sync.aligned.m8n8.x4.trans.shared.b16 [%0], {%1, %2, %3, %4};" ::"r"(addr), "r"(r0), "r"(r1), "r"(r2), "r"(r3) : "memory");
}

__device__ __forceinline__ void wgmma_k1_n136(float (&d)[68], uint64_t desca, uint64_t descb, int scale_d) {
  asm volatile("{\n.reg .pred p;\nsetp.ne.b32 p, %70, 0;\n"
    "wgmma.mma_async.sync.aligned.m64n136k16.f32.bf16.bf16 "
    "{%0, %1, %2, %3, %4, %5, %6, %7, %8, %9, %10, %11, %12, %13, %14, %15, %16, %17, %18, %19, %20, %21, %22, %23, %24, %25, %26, %27, %28, %29, %30, %31, %32, %33, %34, %35, %36, %37, %38, %39, %40, %41, %42, %43, %44, %45, %46, %47, %48, %49, %50, %51, %52, %53, %54, %55, %56, %57, %58, %59, %60, %61, %62, %63, %64, %65, %66, %67}, "
    "%68, %69, p, 1, 1, 1, 0;\n}\n"
    : "+f"(d[0]), "+f"(d[1]), "+f"(d[2]), "+f"(d[3]), "+f"(d[4]), "+f"(d[5]), "+f"(d[6]), "+f"(d[7]), "+f"(d[8]), "+f"(d[9]), "+f"(d[10]), "+f"(d[11]), "+f"(d[12]), "+f"(d[13]), "+f"(d[14]), "+f"(d[15]), "+f"(d[16]), "+f"(d[17]), "+f"(d[18]), "+f"(d[19]), "+f"(d[20]), "+f"(d[21]), "+f"(d[22]), "+f"(d[23]), "+f"(d[24]), "+f"(d[25]), "+f"(d[26]), "+f"(d[27]), "+f"(d[28]), "+f"(d[29]), "+f"(d[30]), "+f"(d[31]), "+f"(d[32]), "+f"(d[33]), "+f"(d[34]), "+f"(d[35]), "+f"(d[36]), "+f"(d[37]), "+f"(d[38]), "+f"(d[39]), "+f"(d[40]), "+f"(d[41]), "+f"(d[42]), "+f"(d[43]), "+f"(d[44]), "+f"(d[45]), "+f"(d[46]), "+f"(d[47]), "+f"(d[48]), "+f"(d[49]), "+f"(d[50]), "+f"(d[51]), "+f"(d[52]), "+f"(d[53]), "+f"(d[54]), "+f"(d[55]), "+f"(d[56]), "+f"(d[57]), "+f"(d[58]), "+f"(d[59]), "+f"(d[60]), "+f"(d[61]), "+f"(d[62]), "+f"(d[63]), "+f"(d[64]), "+f"(d[65]), "+f"(d[66]), "+f"(d[67])
    : "l"(desca), "l"(descb), "r"(scale_d));
}
__device__ __forceinline__ void wgmma_qk_n64(float (&d)[32], uint32_t a0, uint32_t a1, uint32_t a2, uint32_t a3, uint64_t descb) {
  asm volatile("{\n.reg .pred p;\nsetp.ne.b32 p, 0, 0;\n"
    "wgmma.mma_async.sync.aligned.m64n64k16.f32.bf16.bf16 "
    "{%0, %1, %2, %3, %4, %5, %6, %7, %8, %9, %10, %11, %12, %13, %14, %15, %16, %17, %18, %19, %20, %21, %22, %23, %24, %25, %26, %27, %28, %29, %30, %31}, "
    "{%32, %33, %34, %35}, %36, p, 1, 1, 0;\n}\n"
    : "=f"(d[0]), "=f"(d[1]), "=f"(d[2]), "=f"(d[3]), "=f"(d[4]), "=f"(d[5]), "=f"(d[6]), "=f"(d[7]), "=f"(d[8]), "=f"(d[9]), "=f"(d[10]), "=f"(d[11]), "=f"(d[12]), "=f"(d[13]), "=f"(d[14]), "=f"(d[15]), "=f"(d[16]), "=f"(d[17]), "=f"(d[18]), "=f"(d[19]), "=f"(d[20]), "=f"(d[21]), "=f"(d[22]), "=f"(d[23]), "=f"(d[24]), "=f"(d[25]), "=f"(d[26]), "=f"(d[27]), "=f"(d[28]), "=f"(d[29]), "=f"(d[30]), "=f"(d[31])
    : "r"(a0), "r"(a1), "r"(a2), "r"(a3), "l"(descb));
}
__device__ __forceinline__ void wgmma_pv_n24(float (&d)[12], uint32_t a0, uint32_t a1, uint32_t a2, uint32_t a3, uint64_t descb) {
  asm volatile("{\n.reg .pred p;\nsetp.eq.b32 p, 0, 0;\n"
    "wgmma.mma_async.sync.aligned.m64n24k16.f32.bf16.bf16 "
    "{%0, %1, %2, %3, %4, %5, %6, %7, %8, %9, %10, %11}, "
    "{%12, %13, %14, %15}, %16, p, 1, 1, 1;\n}\n"
    : "+f"(d[0]), "+f"(d[1]), "+f"(d[2]), "+f"(d[3]), "+f"(d[4]), "+f"(d[5]), "+f"(d[6]), "+f"(d[7]), "+f"(d[8]), "+f"(d[9]), "+f"(d[10]), "+f"(d[11])
    : "r"(a0), "r"(a1), "r"(a2), "r"(a3), "l"(descb));
}
__device__ __forceinline__ void wgmma_k3_n64(float (&d)[32], uint64_t desca, uint64_t descb, int scale_d) {
  asm volatile("{\n.reg .pred p;\nsetp.ne.b32 p, %34, 0;\n"
    "wgmma.mma_async.sync.aligned.m64n64k16.f32.bf16.bf16 "
    "{%0, %1, %2, %3, %4, %5, %6, %7, %8, %9, %10, %11, %12, %13, %14, %15, %16, %17, %18, %19, %20, %21, %22, %23, %24, %25, %26, %27, %28, %29, %30, %31}, "
    "%32, %33, p, 1, 1, 0, 1;\n}\n"
    : "+f"(d[0]), "+f"(d[1]), "+f"(d[2]), "+f"(d[3]), "+f"(d[4]), "+f"(d[5]), "+f"(d[6]), "+f"(d[7]), "+f"(d[8]), "+f"(d[9]), "+f"(d[10]), "+f"(d[11]), "+f"(d[12]), "+f"(d[13]), "+f"(d[14]), "+f"(d[15]), "+f"(d[16]), "+f"(d[17]), "+f"(d[18]), "+f"(d[19]), "+f"(d[20]), "+f"(d[21]), "+f"(d[22]), "+f"(d[23]), "+f"(d[24]), "+f"(d[25]), "+f"(d[26]), "+f"(d[27]), "+f"(d[28]), "+f"(d[29]), "+f"(d[30]), "+f"(d[31])
    : "l"(desca), "l"(descb), "r"(scale_d));
}
__device__ __forceinline__ void wgmma_bias_n40(float (&d)[32], uint32_t a0, uint32_t az, uint64_t descb) {
  asm volatile("{\n.reg .pred p;\nsetp.eq.b32 p, 0, 0;\n"
    "wgmma.mma_async.sync.aligned.m64n40k16.f32.bf16.bf16 "
    "{%0, %1, %2, %3, %4, %5, %6, %7, %8, %9, %10, %11, %12, %13, %14, %15, %16, %17, %18, %19}, "
    "{%20, %20, %21, %21}, %22, p, 1, 1, 0;\n}\n"
    : "+f"(d[0]), "+f"(d[1]), "+f"(d[2]), "+f"(d[3]), "+f"(d[4]), "+f"(d[5]), "+f"(d[6]), "+f"(d[7]), "+f"(d[8]), "+f"(d[9]), "+f"(d[10]), "+f"(d[11]), "+f"(d[12]), "+f"(d[13]), "+f"(d[14]), "+f"(d[15]), "+f"(d[16]), "+f"(d[17]), "+f"(d[18]), "+f"(d[19])
    : "r"(a0), "r"(az), "l"(descb));
}

constexpr int K1_XS = 17408;
constexpr int K1_WS = 24576;
constexpr int K1_ST = K1_XS + K1_WS;
constexpr int K1_NST = 5;
constexpr int K1_OFF_MISC = K1_NST * K1_ST;
constexpr int K1_SMEM = K1_OFF_MISC + 2048 + 1024;
constexpr float QSCALE = 0.25f * 1.4426950408889634f;

__global__ void __launch_bounds__(544, 1)
k1_qkv(const __grid_constant__ CUtensorMap tm_x, const __grid_constant__ CUtensorMap tm_w, const __nv_bfloat16* __restrict__ x) {
    extern __shared__ uint8_t smem_raw[];
    const uint32_t sraw = smem_u32(smem_raw);
    const uint32_t sb = (sraw + 1023) & ~1023u;
    uint8_t* sp = smem_raw + (sb - sraw);
    const uint32_t full = sb + K1_OFF_MISC;
    const uint32_t empty = full + 64;
    float* s_mr = (float*)(sp + K1_OFF_MISC + 256);

    const int tid = threadIdx.x, warp = tid >> 5, lane = tid & 31;
    const int mt = blockIdx.x >> 3, nt = blockIdx.x & 7;
    if (tid == 0) TSTAMP0(0, 0);
    pdl_launch();
    if (tid == 512) {
        for (int i = 0; i < K1_NST; i++) { mbar_init(full + 8 * i, 1); mbar_init(empty + 8 * i, 3); }
        fence_barrier_init();
        for (int kb = 0; kb < K1_NST; kb++) {
            mbar_expect_tx(full + 8 * kb, 16384 + K1_WS);
            tma_load_2d(sb + kb * K1_ST, &tm_x, kb * 64, mt * 128, full + 8 * kb);
            tma_load_3d(sb + kb * K1_ST + K1_XS, &tm_w, nt * 64, kb * 64, 0, full + 8 * kb);
        }
    }
    if (tid < K1_NST * 64) {
        *(uint4*)(sp + (tid >> 6) * K1_ST + 16384 + (tid & 63) * 16) =
            make_uint4(0x3F803F80u, 0x3F803F80u, 0x3F803F80u, 0x3F803F80u);
    }
    fence_proxy_async();
    __syncthreads();

    if (warp == 16) {
        if (lane == 0) {
            for (int kb = K1_NST; kb < 8; kb++) {
                const int s = kb % K1_NST;
                mbar_wait(empty + 8 * s, 0);
                mbar_expect_tx(full + 8 * s, 16384 + K1_WS);
                tma_load_2d(sb + s * K1_ST, &tm_x, kb * 64, mt * 128, full + 8 * s);
                tma_load_3d(sb + s * K1_ST + K1_XS, &tm_w, nt * 64, kb * 64, 0, full + 8 * s);
            }
        }
        __syncwarp();
        if (lane < FF / 128) g_act[blockIdx.x * (FF / 128) + lane] = 0xFFFFFFFFu;
        for (int i = lane; i < 128; i += 32) g_part[blockIdx.x * 128 + i] = make_float4(0.f, 0.f, 0.f, 0.f);
        if (blockIdx.x == 1) { g_cand[lane] = make_uint4(0, 0, 0, 0); g_cand[lane + 32] = make_uint4(0, 0, 0, 0); g_hflag[lane] = 0; g_sflag[lane] = 0; }
        if (blockIdx.x == 2) for (int i = lane; i < 1024; i += 32) g_oflag[i] = 0;
    } else if (warp >= 12) {
        const int r = tid - 384;
        const unsigned int tag = *(volatile unsigned int*)&g_epoch + 1u;
        {
            const int row = mt * 128 + nt * 16 + (r >> 3);
            const uint4* xp = (const uint4*)(x + (size_t)row * DM) + (r & 7);
            uint4 v[8];
#pragma unroll
            for (int i = 0; i < 8; i++) v[i] = __ldg(xp + i * 8);
            float s1 = 0.f;
#pragma unroll
            for (int i = 0; i < 8; i++)
                s1 += ((bf_lo(v[i].x) + bf_hi(v[i].x)) + (bf_lo(v[i].y) + bf_hi(v[i].y))) + ((bf_lo(v[i].z) + bf_hi(v[i].z)) + (bf_lo(v[i].w) + bf_hi(v[i].w)));
#pragma unroll
            for (int o = 1; o < 8; o <<= 1) s1 += __shfl_xor_sync(0xffffffffu, s1, o);
            const float mean = s1 * (1.f / DM);
            float q0 = 0.f, q1 = 0.f;
#pragma unroll
            for (int i = 0; i < 8; i++) {
                const uint32_t w[4] = {v[i].x, v[i].y, v[i].z, v[i].w};
#pragma unroll
                for (int j = 0; j < 4; j++) {
                    const float a = bf_lo(w[j]) - mean, b = bf_hi(w[j]) - mean;
                    q0 = fmaf(a, a, q0); q1 = fmaf(b, b, q1);
                }
            }
            float q = q0 + q1;
#pragma unroll
            for (int o = 1; o < 8; o <<= 1) q += __shfl_xor_sync(0xffffffffu, q, o);
            const float den = rbf(sqrtf(rbf(rbf(q * (1.f / DM)) + 1e-5f)));
            if ((r & 7) == 0)
                asm volatile("st.relaxed.gpu.global.v4.f32 [%0], {%1, %2, %3, %4};" ::"l"(g_ln1 + row), "f"(rbf(mean)), "f"(1.f / den),
                             "f"(__uint_as_float(tag)), "f"(0.f) : "memory");
        }
        if (r == 0) TSTAMP0(0, 6);
        {
            float4 v;
            int spins = 0;
            do {
                asm volatile("ld.relaxed.gpu.global.v4.f32 {%0, %1, %2, %3}, [%4];" : "=f"(v.x), "=f"(v.y), "=f"(v.z), "=f"(v.w) : "l"(g_ln1 + mt * 128 + r) : "memory");
            } while (__float_as_uint(v.z) != tag && ++spins < (1 << 22));
            s_mr[(r >> 1) * 4 + (r & 1)] = v.x;
            s_mr[(r >> 1) * 4 + 2 + (r & 1)] = v.y;
        }
        if (r == 0) TSTAMP0(0, 7);
        named_arrive(1, 512);
    } else {
        const int part = warp >> 2, hw = warp & 3;
        float acc[68];
#pragma unroll
        for (int i = 0; i < 68; i++) acc[i] = 0.f;
        fence_regs(acc);
#pragma unroll 1
        for (int kb = 0; kb < 8; kb++) {
            const int s = kb % K1_NST;
            mbar_wait(full + 8 * s, (kb / K1_NST) & 1);
            const uint64_t da = make_desc(sb + s * K1_ST + K1_XS + part * 8192, 1024, 1024, 1);
            const uint64_t db = make_desc(sb + s * K1_ST, 16, 1024, 1);
            wg_fence();
#pragma unroll
            for (int k = 0; k < 4; k++) wgmma_k1_n136(acc, da + k * 128, db + k * 2, (kb | k) != 0);
            wg_commit();
            if (kb > 0 && kb <= 8 - K1_NST) {
                wg_wait<1>();
                if ((tid & 127) == 0) mbar_arrive(empty + 8 * (kb - 1));
            }
        }
        wg_wait<0>();
        fence_regs(acc);
        if (tid == 0) TSTAMP0(0, 1);
        named_sync(1, 512);
        if (tid == 0) TSTAMP0(0, 2);

        const int t = lane & 3;
        const float cs0 = acc[64], cs1 = acc[66];
        const float sc = (part == 0) ? QSCALE : 1.f;
        const uint32_t stg = sb + (hw >> 1) * K1_ST + K1_XS + part * 8192 + (hw & 1) * 4096;
        const uint32_t st_addr = stg + ((lane >> 3) & 1) * 2048 + ((lane >> 4) * 8 + (lane & 7)) * 16;
#pragma unroll
        for (int j = 0; j < 16; j += 2) {
            uint32_t rr[4];
#pragma unroll
            for (int u = 0; u < 2; u++) {
                const int jj = j + u;
                const float4 mr = *(const float4*)(s_mr + (4 * jj + t) * 4);
                const float2 m2 = make_float2(mr.x, mr.y);
                const float ra = mr.z * sc, rb = mr.w * sc;
                rr[2 * u] = pack_bf16((acc[4 * jj] - m2.x * cs0) * ra, (acc[4 * jj + 1] - m2.y * cs0) * rb);
                rr[2 * u + 1] = pack_bf16((acc[4 * jj + 2] - m2.x * cs1) * ra, (acc[4 * jj + 3] - m2.y * cs1) * rb);
            }
            stmatrix_x4_trans(st_addr + j * 128, rr[0], rr[1], rr[2], rr[3]);
        }
        fence_proxy_async();
        __syncwarp();
        if (tid == 0) TSTAMP0(0, 4);
        const int head = nt * 4 + hw;
        if (lane == 0) {
            uint8_t* dst;
            uint32_t hstride;
            if (part == 0) { dst = g_q + (size_t)head * 65536 + mt * 2048; hstride = 32768; }
            else { dst = g_kv + (size_t)head * 131072 + (mt >> 1) * 16384 + (part - 1) * 8192 + (mt & 1) * 2048; hstride = 4096; }
            bulk_s2g(dst, stg, 2048);
            bulk_s2g(dst + hstride, stg + 2048, 2048);
            asm volatile("cp.async.bulk.commit_group;" ::: "memory");
        }
        float nmax = 0.f;
#pragma unroll
        for (int i = 0; i < 4; i++) {
            const int tok = lane + 32 * i;
            const uint4 a = *(const uint4*)(sp + (stg - sb) + tok * 16);
            const uint4 b = *(const uint4*)(sp + (stg - sb) + 2048 + tok * 16);
            uint32_t n0 = fma_bf16x2(a.x, a.x, 0u), n1 = fma_bf16x2(b.x, b.x, 0u);
            n0 = fma_bf16x2(a.y, a.y, n0); n1 = fma_bf16x2(b.y, b.y, n1);
            n0 = fma_bf16x2(a.z, a.z, n0); n1 = fma_bf16x2(b.z, b.z, n1);
            n0 = fma_bf16x2(a.w, a.w, n0); n1 = fma_bf16x2(b.w, b.w, n1);
            const float n2 = ((bf_lo(n0) + bf_hi(n0)) + (bf_lo(n1) + bf_hi(n1))) * 1.125f;
            nmax = (n2 > nmax || n2 != n2) ? n2 : nmax;
        }
#pragma unroll
        for (int o = 16; o > 0; o >>= 1) {
            const float v = __shfl_xor_sync(0xffffffffu, nmax, o);
            nmax = (v > nmax || v != v) ? v : nmax;
        }
        if (tid == 0) TSTAMP0(0, 5);
        if (lane == 0) {
            g_norm[(head * 16 + mt) * 3 + part] = nmax;
            asm volatile("cp.async.bulk.wait_group.read 0;" ::: "memory");
            if (tid == 0) TSTAMP0(0, 3);
        }
    }
}

#define POLL_NS 50
constexpr int KF_CH_G = 16384, KF_CH_S = 20480, KF_NCH = 8;
constexpr int KF_OFF_WO = KF_NCH * KF_CH_S;
constexpr int KF_OFF_MISC = KF_OFF_WO + 65536;
constexpr int KF_SMEM = KF_OFF_MISC + 1280 + 1024;

__device__ __forceinline__ uint32_t exp2_pair_poly(float t0, float t1) {
    const uint32_t w = __byte_perm(__float_as_uint(t0), __float_as_uint(t1), 0x5410);
    uint32_t z;
    asm("lop3.b32 %0, %1, %2, %3, 0xEA;" : "=r"(z) : "r"(w), "r"(0x007F007Fu), "r"(0x3F803F80u));
    uint32_t p = fma_bf16x2(0x3eab3eabu, z, 0xbc73bc73u);
    p = fma_bf16x2(p, z, 0x3f2f3f2fu);
    return p + w - z;
}
constexpr uint32_t KF_EMASK = 0x03FFu;
template <int LO, int HI>
__device__ __forceinline__ void softmax_part(const float (&s)[32], uint32_t (&p)[16]) {
#pragma unroll
    for (int i = LO; i < HI; i++) {
        if ((KF_EMASK >> i) & 1) p[i] = exp2_pair_poly(s[2 * i], s[2 * i + 1]);
        else p[i] = pack_bf16(ex2f(s[2 * i]), ex2f(s[2 * i + 1]));
    }
}
#define KF_PV(P, OFF)                                                                              \
    _Pragma("unroll") for (int kk = 0; kk < 4; kk++)                                               \
        wgmma_pv_n24(o, P[4 * kk], P[4 * kk + 1], P[4 * kk + 2], P[4 * kk + 3], dv + ((OFF) + kk * 16));

__device__ __forceinline__ uint32_t make_key(float r_bf16, int token) {
    const uint32_t u = __float_as_uint(r_bf16) >> 16;
    const uint32_t o = (u & 0x8000u) ? (~u & 0xFFFFu) : (u | 0x8000u);
    return (o << 16) | (uint32_t)(0xFFFF - token);
}
__device__ __forceinline__ float key_value(uint32_t k) {
    const uint32_t o = k >> 16;
    const uint32_t u = (o & 0x8000u) ? (o & 0x7FFFu) : (~o & 0xFFFFu);
    return __uint_as_float(u << 16);
}
__device__ __forceinline__ int key_token(uint32_t k) { return 0xFFFF - (int)(k & 0xFFFFu); }
__device__ __forceinline__ void warp_top2(uint32_t a, uint32_t b, uint32_t& k1, uint32_t& k2) {
    k1 = __reduce_max_sync(0xffffffffu, a > b ? a : b);
    const uint32_t a2 = (a == k1) ? 0u : a, b2 = (b == k1) ? 0u : b;
    k2 = __reduce_max_sync(0xffffffffu, a2 > b2 ? a2 : b2);
}
__device__ __forceinline__ unsigned int ld_acquire(const unsigned int* p) {
    unsigned int v; asm volatile("ld.acquire.gpu.global.u32 %0, [%1];" : "=r"(v) : "l"(p) : "memory"); return v;
}
__device__ __forceinline__ void red_release_add(unsigned int* p) {
    asm volatile("red.release.gpu.global.add.u32 [%0], 1;" ::"l"(p) : "memory");
}

__global__ void __launch_bounds__(512, 1)
kf_main(const __grid_constant__ CUtensorMap tm_o, const __grid_constant__ CUtensorMap tm_wo,
        const __grid_constant__ CUtensorMap tm_g, const __grid_constant__ CUtensorMap tm_u, const __grid_constant__ CUtensorMap tm_d,
        const __nv_bfloat16* __restrict__ x, const __nv_bfloat16* __restrict__ wo, const __nv_bfloat16* __restrict__ w_r,
        const __nv_bfloat16* __restrict__ w_gate, const __nv_bfloat16* __restrict__ w_up, const __nv_bfloat16* __restrict__ w_down,
        __nv_bfloat16* __restrict__ out) {
    extern __shared__ uint8_t smem_raw[];
    const uint32_t sraw = smem_u32(smem_raw);
    const uint32_t sb = (sraw + 1023) & ~1023u;
    uint8_t* sp = smem_raw + (sb - sraw);
    const uint32_t kvbar = sb + KF_OFF_MISC;
    const uint32_t wbar = kvbar + 64;
    const uint32_t obar = wbar + 64;
    const uint32_t gbar = obar + 64;
    const uint32_t dbar = gbar + 8;
    unsigned int* s_cnt = (unsigned int*)(sp + KF_OFF_MISC + 208);
    volatile unsigned int* s_order = (volatile unsigned int*)(sp + KF_OFF_MISC + 1056);
    uint32_t* s_key = (uint32_t*)(sp + KF_OFF_MISC + 256);
    float* s_gu = (float*)(sp + KF_OFF_MISC + 768);
    uint4* s_sel = (uint4*)(sp + KF_OFF_MISC + 1024);
    const int tid = threadIdx.x;
    const int head = blockIdx.x >> 2, quarter = blockIdx.x & 3;
    const int mt = blockIdx.x >> 2, nt = blockIdx.x & 3;
    if (tid == 0) TSTAMP0(1, 0);
    if (tid == 0) {
        for (int c = 0; c < 26; c++) mbar_init(kvbar + 8 * c, 1);
        for (int c = 0; c < 4; c++) s_cnt[c] = 0;
        fence_barrier_init();
        for (int kb = 0; kb < 4; kb++) {
            mbar_expect_tx(wbar + 8 * kb, 16384);
            tma_load_3d(sb + KF_OFF_WO + kb * 16384, &tm_wo, 0, kb * 64, nt * 2, wbar + 8 * kb);
        }
    }
    if (tid == 32) {
        prefetch_l2((const uint8_t*)wo + blockIdx.x * 4096, 4096);
        prefetch_l2((const uint8_t*)w_gate + blockIdx.x * 14336, 14336);
        prefetch_l2((const uint8_t*)w_up + blockIdx.x * 14336, 14336);
        prefetch_l2((const uint8_t*)w_down + blockIdx.x * 14336, 14336);
    }
    if (tid < 8) *(uint4*)(sp + KF_OFF_MISC + 1152 + tid * 16) = make_uint4(0x3F804380u, 0x00003E00u, 0u, 0u);
    for (int i = tid; i < KF_NCH * 256; i += 512)
        *(uint4*)(sp + (i >> 8) * KF_CH_S + 16384 + (i & 255) * 16) =
            make_uint4(0x3F803F80u, 0x3F803F80u, 0x3F803F80u, 0x3F803F80u);
    fence_proxy_async();
    __syncthreads();
    pdl_wait();
    if (tid == 0) TSTAMP0(1, 1);
    const uint8_t* kvsrc = g_kv + (size_t)head * (KF_NCH * KF_CH_G);
    if (tid == 32) {
        mbar_expect_tx(kvbar, KF_CH_G);
        bulk_g2s(sb, kvsrc, KF_CH_G, kvbar);
    }
    const int wg = tid >> 7, warp = (tid >> 5) & 3, lane = tid & 31, g = lane >> 2, t = lane & 3;
    if (tid < 32) {
        const int m16 = lane & 15;
        float kn = g_norm[(head * 16 + m16) * 3 + 1];
        float vn = g_norm[(head * 16 + m16) * 3 + 2];
        float qn = g_norm[(head * 16 + quarter * 4 + (lane & 3)) * 3 + 0];
        const bool bad = !(kn < 1e30f) || !(vn < 1e30f) || !(qn < 1e30f);
#pragma unroll
        for (int o = 8; o > 0; o >>= 1) {
            kn = fmaxf(kn, __shfl_xor_sync(0xffffffffu, kn, o));
            qn = fmaxf(qn, __shfl_xor_sync(0xffffffffu, qn, o));
        }
        const bool ok = __all_sync(0xffffffffu, !bad && (qn * kn <= 3500.f));
        if (lane == 0) s_cnt[4] = ok ? 1u : 0u;
    }
    uint32_t qn2[2][4];
#pragma unroll
    for (int ps = 0; ps < 2; ps++) {
        const uint8_t* qb = g_q + (size_t)head * 65536 + (quarter * 512 + ps * 256 + wg * 64 + warp * 16 + g) * 16 + t * 4;
        qn2[ps][0] = *(const uint32_t*)(qb);
        qn2[ps][1] = *(const uint32_t*)(qb + 128);
        qn2[ps][2] = *(const uint32_t*)(qb + 32768);
        qn2[ps][3] = *(const uint32_t*)(qb + 32768 + 128);
    }

    __syncthreads();
    const bool fast = __all_sync(0xffffffffu, s_cnt[4] != 0u);
    if (tid == 32) {
        for (int c = 1; c < KF_NCH; c++) {
            mbar_expect_tx(kvbar + 8 * c, KF_CH_G);
            bulk_g2s(sb + c * KF_CH_S, kvsrc + c * KF_CH_G, KF_CH_G, kvbar + 8 * c);
        }
    }
    if (tid == 0) TSTAMP0(1, 8);
    const uint64_t dbias = make_desc(sb + KF_OFF_MISC + 1152, 0, 0, 0);
    const uint32_t abias = (t == 0) ? 0x42FE4380u : ((t == 1) ? 0x00003D80u : 0u);
    const uint64_t dk0 = make_desc(sb, 4096, 128, 0);
    const uint64_t dv0 = make_desc(sb + 8192, 128, 4096, 0);

#pragma unroll 1
    for (int pass = 0; pass < 2; pass++) {
        const int row0 = quarter * 512 + pass * 256 + wg * 64 + warp * 16 + g;
        uint32_t qa[4];
#pragma unroll
        for (int i = 0; i < 4; i++) qa[i] = pass ? qn2[1][i] : qn2[0][i];
        float o[12];
#pragma unroll
        for (int i = 0; i < 12; i++) o[i] = 0.f;
        fence_regs(o);
#define KF_RELEASE_CHUNK(c)                                                                          \
        if (pass == 1 && (c) >= 1 && (c) <= 4) {                                                     \
            named_sync(4 + wg, 128);            \
            if ((tid & 127) == 0 && atomicAdd(&s_cnt[(c) - 1], 1u) == 3u) {                          \
                mbar_expect_tx(wbar + 8 * (3 + (c)), 16384);                                         \
                tma_load_3d(sb + ((c) - 1) * KF_CH_S, &tm_wo, 0, (3 + (c)) * 64, nt * 2, wbar + 8 * (3 + (c))); \
            }                                                                                        \
        }
        if (fast) {
#pragma unroll 1
            for (int c = 0; c < KF_NCH; c++) {
                const uint64_t dk = dk0 + (uint64_t)(c * (KF_CH_S >> 4));
                const uint64_t dv = dv0 + (uint64_t)(c * (KF_CH_S >> 4));
                float s0[32], s1[32], s2[32], s3[32];
                uint32_t p0[16], p1[16], p2[16], p3[16];
                mbar_wait(kvbar + 8 * c, 0);
                wg_wait<1>();
                wg_fence();
                wgmma_qk_n64(s0, qa[0], qa[1], qa[2], qa[3], dk);
                wgmma_bias_n40(s0, abias, 0u, dbias);
                wg_commit();
                wg_wait<1>();
                KF_RELEASE_CHUNK(c);
                wg_fence();
                wgmma_qk_n64(s1, qa[0], qa[1], qa[2], qa[3], dk + 64);
                wgmma_bias_n40(s1, abias, 0u, dbias);
                wg_commit();
                wg_wait<1>();
                fence_regs(s0);
                softmax_part<0, 16>(s0, p0);
                wg_fence();
                KF_PV(p0, 0);
                wg_commit();
                wg_wait<1>();
                fence_regs(s1);
                softmax_part<0, 8>(s1, p1);
                wg_wait<0>();
                wg_fence();
                wgmma_qk_n64(s2, qa[0], qa[1], qa[2], qa[3], dk + 128);
                wgmma_bias_n40(s2, abias, 0u, dbias);
                wg_commit();
                softmax_part<8, 16>(s1, p1);
                wg_fence();
                KF_PV(p1, 64);
                wg_commit();
                wg_wait<1>();
                fence_regs(s2);
                softmax_part<0, 8>(s2, p2);
                wg_wait<0>();
                wg_fence();
                wgmma_qk_n64(s3, qa[0], qa[1], qa[2], qa[3], dk + 192);
                wgmma_bias_n40(s3, abias, 0u, dbias);
                wg_commit();
                softmax_part<8, 16>(s2, p2);
                wg_fence();
                KF_PV(p2, 128);
                wg_commit();
                wg_wait<1>();
                fence_regs(s3);
                softmax_part<0, 16>(s3, p3);
                wg_fence();
                KF_PV(p3, 192);
                wg_commit();
            }
            wg_wait<0>();
            fence_regs(o);
        } else {
            float m0 = -INFINITY, m1 = -INFINITY;
#pragma unroll 1
            for (int b = 0; b < 32; b++) {
                const int c = b >> 2;
                const uint64_t dk = dk0 + (uint64_t)(c * (KF_CH_S >> 4) + (b & 3) * 64);
                const uint64_t dv = dv0 + (uint64_t)(c * (KF_CH_S >> 4) + (b & 3) * 64);
                float s[32];
                uint32_t p[16];
                mbar_wait(kvbar + 8 * c, 0);
                wg_fence();
                wgmma_qk_n64(s, qa[0], qa[1], qa[2], qa[3], dk);
                wg_commit();
                if ((b & 3) == 0) { KF_RELEASE_CHUNK(c); }
                wg_wait<0>();
                fence_regs(s);
                float x0 = s[0], x1 = s[2];
#pragma unroll
                for (int j = 0; j < 8; j++) {
                    x0 = fmaxf(x0, fmaxf(s[4 * j], s[4 * j + 1]));
                    x1 = fmaxf(x1, fmaxf(s[4 * j + 2], s[4 * j + 3]));
                }
                x0 = fmaxf(x0, __shfl_xor_sync(0xffffffffu, x0, 1));
                x0 = fmaxf(x0, __shfl_xor_sync(0xffffffffu, x0, 2));
                x1 = fmaxf(x1, __shfl_xor_sync(0xffffffffu, x1, 1));
                x1 = fmaxf(x1, __shfl_xor_sync(0xffffffffu, x1, 2));
                const float n0 = fmaxf(m0, x0), n1 = fmaxf(m1, x1);
                const float c0 = ex2f(m0 - n0), c1 = ex2f(m1 - n1);
                m0 = n0; m1 = n1;
#pragma unroll
                for (int j = 0; j < 3; j++) {
                    o[4 * j] *= c0; o[4 * j + 1] *= c0; o[4 * j + 2] *= c1; o[4 * j + 3] *= c1;
                }
#pragma unroll
                for (int j = 0; j < 8; j++) {
                    p[2 * j] = pack_bf16(ex2f(s[4 * j] - n0), ex2f(s[4 * j + 1] - n0));
                    p[2 * j + 1] = pack_bf16(ex2f(s[4 * j + 2] - n1), ex2f(s[4 * j + 3] - n1));
                }
                fence_regs(o);
                wg_fence();
                KF_PV(p, 0);
                wg_commit();
                wg_wait<0>();
                fence_regs(o);
            }
        }
        const float inv0 = 1.f / o[8], inv1 = 1.f / o[10];
        {
            uint32_t v0 = pack_bf16(o[0] * inv0, o[1] * inv0), v1 = pack_bf16(o[4] * inv0, o[5] * inv0);
            uint32_t v2 = pack_bf16(o[2] * inv1, o[3] * inv1), v3 = pack_bf16(o[6] * inv1, o[7] * inv1);
            const bool o1 = t & 1, o2 = t & 2;
            uint32_t s0 = o1 ? v0 : v1, s1 = o1 ? v2 : v3;
            s0 = __shfl_xor_sync(0xffffffffu, s0, 1); s1 = __shfl_xor_sync(0xffffffffu, s1, 1);
            uint32_t a0 = o1 ? s0 : v0, a1 = o1 ? v1 : s0, b0 = o1 ? s1 : v2, b1 = o1 ? v3 : s1;
            uint32_t x0 = o2 ? a0 : b0, x1 = o2 ? a1 : b1;
            x0 = __shfl_xor_sync(0xffffffffu, x0, 2); x1 = __shfl_xor_sync(0xffffffffu, x1, 2);
            uint4 r;
            r.x = o2 ? x0 : a0; r.y = o2 ? x1 : a1; r.z = o2 ? b0 : x0; r.w = o2 ? b1 : x1;
            *(uint4*)(g_o + (size_t)(row0 + (t >> 1) * 8) * DM + head * 16 + (t & 1) * 8) = r;
        }
        if (tid == 0) TSTAMP0(1, 4 + pass);
    }
    if ((tid >> 5) != 10) named_arrive(1, 512);
    named_sync(4 + wg, 128);
    if ((tid & 127) == 0) {
        asm volatile("fence.acq_rel.gpu;" ::: "memory");
        asm volatile("red.relaxed.gpu.global.add.u32 [%0], 1;" ::"l"(&g_oflag[(quarter * 8 + 4 + wg) * 32 + (head >> 2) * 4]) : "memory");
        asm volatile("red.relaxed.gpu.global.add.u32 [%0], 1;" ::"l"(&g_oflag[(quarter * 8 + wg) * 32 + (head >> 2) * 4]) : "memory");
    }
    if (tid == 0) TSTAMP0(1, 3);

    if (wg < 2) {
        const int wi = warp;
        const int r0 = mt * 64 + wi * 16 + g;
        const int cb = nt * 128 + wg * 64;
        uint32_t xr[16], wr[8];
#pragma unroll
        for (int j = 0; j < 8; j++) {
            xr[2 * j] = __ldg((const uint32_t*)(x + (size_t)r0 * DM + cb + 8 * j + 2 * t));
            xr[2 * j + 1] = __ldg((const uint32_t*)(x + (size_t)(r0 + 8) * DM + cb + 8 * j + 2 * t));
            wr[j] = __ldg((const uint32_t*)(w_r + cb + 8 * j + 2 * t));
        }
        float wsum = 0.f;
        {
            const uint4 a = __ldg((const uint4*)(w_r + lane * 16)), b = __ldg((const uint4*)(w_r + lane * 16 + 8));
            const uint32_t w[8] = {a.x, a.y, a.z, a.w, b.x, b.y, b.z, b.w};
#pragma unroll
            for (int i = 0; i < 8; i++) wsum += bf_lo(w[i]) + bf_hi(w[i]);
#pragma unroll
            for (int o = 16; o > 0; o >>= 1) wsum += __shfl_xor_sync(0xffffffffu, wsum, o);
        }
        float acc[32];
#pragma unroll
        for (int i = 0; i < 32; i++) acc[i] = 0.f;
        fence_regs(acc);
#pragma unroll 1
        for (int i = 0; i < 8; i++) {
            mbar_wait(obar + 8 * i, 0);
            const int kb = __shfl_sync(0xffffffffu, (int)s_order[i], 0);
            mbar_wait(wbar + 8 * kb, 0);
            const uint32_t wa = (kb < 4) ? (KF_OFF_WO + kb * 16384) : ((kb - 4) * KF_CH_S);
            const uint64_t da = make_desc(sb + (4 + (kb >> 1)) * KF_CH_S + (kb & 1) * 8192, 16, 1024, 1);
            const uint64_t db = make_desc(sb + wa + wg * 8192, 1024, 1024, 1);
            wg_fence();
#pragma unroll
            for (int k = 0; k < 4; k++) wgmma_k3_n64(acc, da + k * 2, db + k * 128, (i | k) != 0);
            wg_commit();
        }
        wg_wait<0>();
        fence_regs(acc);
        if (tid == 0) TSTAMP0(2, 2);
        float hv[32];
        uint32_t hp[16];
        float s0 = 0.f, s1 = 0.f, d0 = 0.f, d1 = 0.f;
#pragma unroll
        for (int j = 0; j < 8; j++) {
            const uint32_t a01 = pack_bf16(acc[4 * j], acc[4 * j + 1]), a23 = pack_bf16(acc[4 * j + 2], acc[4 * j + 3]);
            hp[2 * j] = pack_bf16(bf_lo(xr[2 * j]) + bf_lo(a01), bf_hi(xr[2 * j]) + bf_hi(a01));
            hp[2 * j + 1] = pack_bf16(bf_lo(xr[2 * j + 1]) + bf_lo(a23), bf_hi(xr[2 * j + 1]) + bf_hi(a23));
            hv[4 * j] = bf_lo(hp[2 * j]); hv[4 * j + 1] = bf_hi(hp[2 * j]);
            hv[4 * j + 2] = bf_lo(hp[2 * j + 1]); hv[4 * j + 3] = bf_hi(hp[2 * j + 1]);
            const float wl = bf_lo(wr[j]), wh = bf_hi(wr[j]);
            s0 += hv[4 * j] + hv[4 * j + 1];
            s1 += hv[4 * j + 2] + hv[4 * j + 3];
            d0 = fmaf(hv[4 * j], wl, fmaf(hv[4 * j + 1], wh, d0));
            d1 = fmaf(hv[4 * j + 2], wl, fmaf(hv[4 * j + 3], wh, d1));
        }
        float mu0 = s0 * (1.f / 16), mu1 = s1 * (1.f / 16);
        float q0 = 0.f, q1 = 0.f;
#pragma unroll
        for (int j = 0; j < 8; j++) {
            float a = hv[4 * j] - mu0, b = hv[4 * j + 1] - mu0, c = hv[4 * j + 2] - mu1, d = hv[4 * j + 3] - mu1;
            q0 = fmaf(a, a, fmaf(b, b, q0));
            q1 = fmaf(c, c, fmaf(d, d, q1));
        }
#pragma unroll
        for (int o = 1; o < 4; o <<= 1) {
            const float m0 = __shfl_xor_sync(0xffffffffu, mu0, o), m1 = __shfl_xor_sync(0xffffffffu, mu1, o);
            const float e0 = __shfl_xor_sync(0xffffffffu, q0, o), e1 = __shfl_xor_sync(0xffffffffu, q1, o);
            d0 += __shfl_xor_sync(0xffffffffu, d0, o);
            d1 += __shfl_xor_sync(0xffffffffu, d1, o);
            const float f0 = mu0 - m0, f1 = mu1 - m1;
            q0 = q0 + e0 + f0 * f0 * (8.f * o);
            q1 = q1 + e1 + f1 * f1 * (8.f * o);
            mu0 = 0.5f * (mu0 + m0); mu1 = 0.5f * (mu1 + m1);
        }
        float4* part = g_part + (size_t)mt * 512 + wi * 16 + g;
        if (t < 2) {
            float4* dst = part + (nt * 2 + wg) * 64 + t * 8;
            const float a = t ? mu1 : mu0, b = t ? q1 : q0, c = t ? d1 : d0;
            asm volatile("st.relaxed.gpu.global.v4.f32 [%0], {%1, %2, %3, %4};" ::"l"(dst), "f"(a), "f"(b), "f"(c), "f"(1.0f) : "memory");
        }
        if (tid == 0) TSTAMP0(2, 5);
        const uint32_t stg_off = KF_OFF_WO + (wi >> 1) * 16384 + wg * 8192 + (wi & 1) * 4096;
        const uint32_t stg_o = sb + stg_off, stg_h = stg_o + 2048;
        const int srow = (lane & 7) + ((lane >> 3) & 1) * 8;
        const int sj = lane >> 4;
        named_sync(4 + wg, 128);
#pragma unroll
        for (int j = 0; j < 8; j += 2) {
            const uint32_t off = srow * 128 + (((j + sj) ^ (srow & 7)) << 4);
            stmatrix_x4(stg_h + off, hp[2 * j], hp[2 * j + 1], hp[2 * j + 2], hp[2 * j + 3]);
        }
        __syncwarp();
#pragma unroll
        for (int i = 0; i < 4; i++) {
            const int row = i * 4 + (lane >> 3), ch = lane & 7;
            const uint4 vh = *(const uint4*)(sp + stg_off + 2048 + row * 128 + ((ch ^ (row & 7)) << 4));
            *(uint4*)(g_h + (size_t)(mt * 64 + wi * 16 + row) * DM + cb + ch * 8) = vh;
        }
        named_arrive(8, 288);
        if (tid == 0) TSTAMP0(2, 6);
        float mean[2], den[2], rr[2];
        {
            float4 v[4];
            int spins = 0;
            while (true) {
#pragma unroll
                for (int i = 0; i < 4; i++) {
                    const float4* p = part + (t + (i & 1) * 4) * 64 + (i >> 1) * 8;
                    asm volatile("ld.relaxed.gpu.global.v4.f32 {%0, %1, %2, %3}, [%4];" : "=f"(v[i].x), "=f"(v[i].y), "=f"(v[i].z), "=f"(v[i].w) : "l"(p) : "memory");
                }
                const bool ok = (v[0].w != 0.f) && (v[1].w != 0.f) && (v[2].w != 0.f) && (v[3].w != 0.f);
                if (__all_sync(0xffffffffu, ok) || ++spins > (1 << 22)) break;
            }
#pragma unroll
            for (int u = 0; u < 2; u++) {
                float mu = v[2 * u].x + v[2 * u + 1].x, m2 = v[2 * u].y + v[2 * u + 1].y, hw = v[2 * u].z + v[2 * u + 1].z;
#pragma unroll
                for (int o = 1; o < 4; o <<= 1) {
                    mu += __shfl_xor_sync(0xffffffffu, mu, o);
                    m2 += __shfl_xor_sync(0xffffffffu, m2, o);
                    hw += __shfl_xor_sync(0xffffffffu, hw, o);
                }
                mu *= 0.125f;
                const float da = v[2 * u].x - mu, db = v[2 * u + 1].x - mu;
                float dd = 64.f * (da * da + db * db);
#pragma unroll
                for (int o = 1; o < 4; o <<= 1) dd += __shfl_xor_sync(0xffffffffu, dd, o);
                m2 += dd;
                mean[u] = rbf(mu);
                den[u] = rbf(sqrtf(rbf(rbf(m2 * (1.f / DM)) + 1e-5f)));
                rr[u] = rbf((hw - mean[u] * wsum) / den[u]);
            }
        }
        if (tid == 0) TSTAMP0(2, 3);
        named_arrive(3, 512);
        if (nt == 0 && wg == 0) {
            float2* s_st = (float2*)(sp + KF_OFF_WO + 49152);
            if (t == 0) {
                s_key[wi * 16 + g] = make_key(rr[0], r0);
                s_key[wi * 16 + g + 8] = make_key(rr[1], r0 + 8);
                s_st[wi * 16 + g] = make_float2(mean[0], den[0]);
                s_st[wi * 16 + g + 8] = make_float2(mean[1], den[1]);
            }
            named_sync(4, 128);
            if (warp == 0) {
                uint32_t k1, k2;
                warp_top2(s_key[lane], s_key[lane + 32], k1, k2);
                if (lane < 2) {
                    const uint32_t k = lane ? k2 : k1;
                    const float2 st = s_st[key_token(k) & 63];
                    asm volatile("st.relaxed.gpu.global.v4.u32 [%0], {%1, %2, %3, %4};" ::"l"(g_cand + mt * 2 + lane), "r"(k),
                                 "r"(1u), "r"(__float_as_uint(st.x)), "r"(__float_as_uint(st.y)) : "memory");
                }
            }
        }
        const float i0 = 1.f / den[0], i1 = 1.f / den[1];
#pragma unroll
        for (int j = 0; j < 8; j += 2) {
            uint32_t ro[4];
#pragma unroll
            for (int u = 0; u < 2; u++) {
                const int jj = j + u;
                const float a = hv[4 * jj], b = hv[4 * jj + 1], c = hv[4 * jj + 2], d = hv[4 * jj + 3];
                const uint32_t u01 = pack_bf16(a - mean[0], b - mean[0]), u23 = pack_bf16(c - mean[1], d - mean[1]);
                const uint32_t n01 = pack_bf16(bf_lo(u01) * i0, bf_hi(u01) * i0), n23 = pack_bf16(bf_lo(u23) * i1, bf_hi(u23) * i1);
                ro[2 * u] = pack_bf16(a + bf_lo(n01), b + bf_hi(n01));
                ro[2 * u + 1] = pack_bf16(c + bf_lo(n23), d + bf_hi(n23));
            }
            const uint32_t off = srow * 128 + (((j + sj) ^ (srow & 7)) << 4);
            stmatrix_x4(stg_o + off, ro[0], ro[1], ro[2], ro[3]);
        }
        __syncwarp();
#pragma unroll
        for (int i = 0; i < 4; i++) {
            const int row = i * 4 + (lane >> 3), ch = lane & 7;
            const uint4 vo = *(const uint4*)(sp + stg_off + row * 128 + ((ch ^ (row & 7)) << 4));
            *(uint4*)(out + (size_t)(mt * 64 + wi * 16 + row) * DM + cb + ch * 8) = vo;
        }
        named_sync(4 + wg, 128);
        if ((tid & 127) == 0) red_release_add(&g_sflag[mt]);
        if (tid == 0) TSTAMP0(2, 4);
    } else {
        const bool worker = blockIdx.x < FF / 16;
        const bool downer = blockIdx.x >= 64;
        const int mtid = tid - 256, mwarp = mtid >> 5;
        const int c0 = (blockIdx.x - 64) * 8;
        float* s_x = (float*)(sp + KF_OFF_WO + 49152 + 8192);
        float* s_red = (float*)(sp + KF_OFF_WO + 49152 + 8192 + 4096);
        if (mwarp == 2) {
            named_sync(1, 512);
            uint32_t done = 0;
            int n = 0, spins = 0;
            while (done != 0xFFu && ++spins < (1 << 22)) {
                const bool rdy = lane < 8 && ld_acquire(&g_oflag[mt * 32 + lane * 4]) >= 4u;
                uint32_t todo = __ballot_sync(0xffffffffu, rdy) & ~done;
                done |= todo;
                if (todo && lane == 0) {
                    asm volatile("fence.proxy.async.global;" ::: "memory");
                    while (todo) {
                        const int kb = __ffs(todo) - 1;
                        todo &= todo - 1;
                        s_order[n] = kb;
                        mbar_expect_tx(obar + 8 * n, 8192);
                        tma_load_3d(sb + (4 + (kb >> 1)) * KF_CH_S + (kb & 1) * 8192, &tm_o, 0, mt * 64, kb, obar + 8 * n);
                        n++;
                    }
                }
                n = __shfl_sync(0xffffffffu, n, 0);
                if (done != 0xFFu) __nanosleep(POLL_NS);
            }
            if (lane == 0) TSTAMP0(2, 1);
            if (lane == 0 && worker) {
                mbar_expect_tx(gbar, 32768);
                for (int i = 0; i < 4; i++) {
                    tma_load_2d(sb + i * KF_CH_S + 16384, &tm_g, blockIdx.x * 16, i * 128, gbar);
                    tma_load_2d(sb + (4 + i) * KF_CH_S + 16384, &tm_u, blockIdx.x * 16, i * 128, gbar);
                }
            }
        }
        if (mwarp == 1) {
            named_sync(8, 288);
            if (lane == 0) {
                red_release_add(&g_hflag[mt]);
                if (downer) {
                    mbar_expect_tx(dbar, 7 * 4096);
                    for (int i = 0; i < 7; i++) tma_load_2d(sb + (4 + (i >> 2)) * KF_CH_S + (i & 3) * 4096, &tm_d, c0, i * 256, dbar);
                }
            }
            __syncwarp();
        }
        if (mtid == 0) TSTAMP0(3, 0);
        named_sync(3, 512);
        if (mwarp == 0) {
            uint4 ca, cb4;
            int spins = 0;
            while (true) {
                asm volatile("ld.relaxed.gpu.global.v4.u32 {%0, %1, %2, %3}, [%4];" : "=r"(ca.x), "=r"(ca.y), "=r"(ca.z), "=r"(ca.w) : "l"(g_cand + 2 * lane) : "memory");
                asm volatile("ld.relaxed.gpu.global.v4.u32 {%0, %1, %2, %3}, [%4];" : "=r"(cb4.x), "=r"(cb4.y), "=r"(cb4.z), "=r"(cb4.w) : "l"(g_cand + 2 * lane + 1) : "memory");
                const unsigned int hf = ld_acquire(&g_hflag[lane]);
                const bool ok = ca.y != 0 && cb4.y != 0 && hf >= 4u;
                if (__all_sync(0xffffffffu, ok) || ++spins > (1 << 22)) break;
            }
            uint32_t k1, k2;
            warp_top2(ca.x, cb4.x, k1, k2);
            if (ca.x == k1) s_sel[0] = ca;
            if (cb4.x == k1) s_sel[0] = cb4;
            if (ca.x == k2) s_sel[1] = ca;
            if (cb4.x == k2) s_sel[1] = cb4;
        }
        named_sync(2, 256);
        if (mtid == 0) TSTAMP0(3, 1);
        int idx[2];
        float mean[2], inv[2], rv[2];
#pragma unroll
        for (int u = 0; u < 2; u++) {
            const uint4 c = s_sel[u];
            idx[u] = key_token(c.x);
            rv[u] = key_value(c.x);
            mean[u] = __uint_as_float(c.z);
            inv[u] = 1.f / __uint_as_float(c.w);
        }
        float hfin = 0.f;
        if (downer && mtid < 16) hfin = __bfloat162float(__ldcg((const __nv_bfloat16*)(g_h + (size_t)((mtid >> 3) ? idx[1] : idx[0]) * DM + c0 + (mtid & 7))));
        if (worker) {
            {
                const uint32_t h0 = __ldcg((const uint32_t*)(g_h + (size_t)idx[0] * DM + 2 * mtid));
                const uint32_t h1 = __ldcg((const uint32_t*)(g_h + (size_t)idx[1] * DM + 2 * mtid));
                const uint32_t u0 = pack_bf16(bf_lo(h0) - mean[0], bf_hi(h0) - mean[0]), u1 = pack_bf16(bf_lo(h1) - mean[1], bf_hi(h1) - mean[1]);
                const uint32_t n0 = pack_bf16(bf_lo(u0) * inv[0], bf_hi(u0) * inv[0]), n1 = pack_bf16(bf_lo(u1) * inv[1], bf_hi(u1) * inv[1]);
                *(float4*)(s_x + 4 * mtid) = make_float4(bf_lo(n0), bf_lo(n1), bf_hi(n0), bf_hi(n1));
            }
            if (mtid == 0) TSTAMP0(3, 5);
            mbar_wait(gbar, 0);
            named_sync(2, 256);
            if (mtid == 0) TSTAMP0(3, 6);
            float acc[8];
#pragma unroll
            for (int i = 0; i < 8; i++) acc[i] = 0.f;
            const uint8_t* wbase = sp + (mwarp >> 2) * (4 * KF_CH_S) + 16384 + lane * 32 + (mwarp & 3) * 8;
#pragma unroll
            for (int k = 0; k < 16; k++) {
                const uint2 w = *(const uint2*)(wbase + (k >> 2) * KF_CH_S + (k & 3) * 1024);
                const float2 xx = *(const float2*)(s_x + 2 * (lane + 32 * k));
                const float x0 = xx.x, x1 = xx.y;
                const float w0 = bf_lo(w.x), w1 = bf_hi(w.x), w2 = bf_lo(w.y), w3 = bf_hi(w.y);
                acc[0] = fmaf(x0, w0, acc[0]); acc[1] = fmaf(x0, w1, acc[1]); acc[2] = fmaf(x0, w2, acc[2]); acc[3] = fmaf(x0, w3, acc[3]);
                acc[4] = fmaf(x1, w0, acc[4]); acc[5] = fmaf(x1, w1, acc[5]); acc[6] = fmaf(x1, w2, acc[6]); acc[7] = fmaf(x1, w3, acc[7]);
            }
#define KF_STEP(O, N)                                                          \
            {                                                                  \
                const bool up = (lane & (O)) != 0;                             \
                _Pragma("unroll") for (int i = 0; i < (N); i++) {              \
                    const float send = up ? acc[i] : acc[i + (N)];             \
                    const float keep = up ? acc[i + (N)] : acc[i];             \
                    acc[i] = keep + __shfl_xor_sync(0xffffffffu, send, (O));   \
                }                                                              \
            }
            KF_STEP(16, 4) KF_STEP(8, 2) KF_STEP(4, 1)
            acc[0] += __shfl_xor_sync(0xffffffffu, acc[0], 2);
            acc[0] += __shfl_xor_sync(0xffffffffu, acc[0], 1);
            if ((lane & 3) == 0) {
                const int v = ((lane & 16) ? 4 : 0) + ((lane & 8) ? 2 : 0) + ((lane & 4) ? 1 : 0);
                s_gu[(v >> 2) * 32 + mwarp * 4 + (v & 3)] = acc[0];
            }
            named_sync(2, 256);
            if (mtid < 16) {
                uint32_t a2 = 0;
#pragma unroll
                for (int u = 0; u < 2; u++) {
                    const float gb = rbf(s_gu[u * 32 + mtid]);
                    const float sg = rbf(gb / (1.f + __expf(-gb)));
                    float a = sg * rbf(s_gu[u * 32 + 16 + mtid]);
                    uint32_t ab = (uint32_t)__bfloat16_as_ushort(__float2bfloat16_rn(a));
                    if (ab == 0xFFFFu) ab = 0x7FFFu;
                    a2 |= ab << (16 * u);
                }
                asm volatile("st.relaxed.gpu.global.u32 [%0], %1;" ::"l"(g_act + blockIdx.x * 16 + mtid), "r"(a2) : "memory");
            }
            if (mtid == 0) TSTAMP0(3, 2);
        }
        if (downer) {
            uint32_t av[7];
            {
                int spins = 0;
                while (true) {
                    bool ok = true;
#pragma unroll
                    for (int j = 0; j < 7; j++) {
                        asm volatile("ld.relaxed.gpu.global.u32 %0, [%1];" : "=r"(av[j]) : "l"(g_act + mtid + 256 * j) : "memory");
                        ok = ok && ((av[j] & 0xFFFFu) != 0xFFFFu) && ((av[j] >> 16) != 0xFFFFu);
                    }
                    if (mtid < 2) ok = ok && (ld_acquire(&g_sflag[(mtid ? idx[1] : idx[0]) >> 6]) >= 8u);
                    if (__all_sync(0xffffffffu, ok) || ++spins > (1 << 20)) break;
                    __nanosleep(20);
                }
            }
            if (mtid == 0) TSTAMP0(3, 3);
            mbar_wait(dbar, 0);
            float acc[16];
#pragma unroll
            for (int i = 0; i < 16; i++) acc[i] = 0.f;
#pragma unroll
            for (int j = 0; j < 7; j++) {
                const uint4 w = *(const uint4*)(sp + (4 + (j >> 2)) * KF_CH_S + (j & 3) * 4096 + mtid * 16);
                const float a0 = bf_lo(av[j]), a1 = bf_hi(av[j]);
                const uint32_t ww[4] = {w.x, w.y, w.z, w.w};
#pragma unroll
                for (int q = 0; q < 4; q++) {
                    const float wl = bf_lo(ww[q]), wh = bf_hi(ww[q]);
                    acc[2 * q] = fmaf(a0, wl, acc[2 * q]); acc[2 * q + 1] = fmaf(a0, wh, acc[2 * q + 1]);
                    acc[8 + 2 * q] = fmaf(a1, wl, acc[8 + 2 * q]); acc[8 + 2 * q + 1] = fmaf(a1, wh, acc[8 + 2 * q + 1]);
                }
            }
            KF_STEP(16, 8) KF_STEP(8, 4) KF_STEP(4, 2) KF_STEP(2, 1)
            acc[0] += __shfl_xor_sync(0xffffffffu, acc[0], 1);
            if ((lane & 1) == 0) {
                const int v = ((lane & 16) ? 8 : 0) + ((lane & 8) ? 4 : 0) + ((lane & 4) ? 2 : 0) + ((lane & 2) ? 1 : 0);
                s_red[mwarp * 16 + v] = acc[0];
            }
            named_sync(2, 256);
            if (mtid < 16) {
                const int u = mtid >> 3;
                float y = 0.f;
#pragma unroll
                for (int w = 0; w < 8; w++) y += s_red[w * 16 + mtid];
                const float sig = rbf(1.f / (1.f + __expf(-(u ? rv[1] : rv[0]))));
                const float xn = rbf(rbf(hfin - (u ? mean[1] : mean[0])) * (u ? inv[1] : inv[0]));
                const float ov = hfin + rbf(xn + rbf(rbf(y) * sig));
                out[(size_t)(u ? idx[1] : idx[0]) * DM + c0 + (mtid & 7)] = __float2bfloat16_rn(ov);
            }
            if (blockIdx.x == gridDim.x - 1 && mtid == 0) g_epoch = g_epoch + 1u;
            if (mtid == 0) TSTAMP0(3, 4);
        }
    }
}

typedef CUresult (*PFN_encodeTiled)(CUtensorMap*, CUtensorMapDataType, cuuint32_t, void*, const cuuint64_t*, const cuuint64_t*,
                                    const cuuint32_t*, const cuuint32_t*, CUtensorMapInterleave, CUtensorMapSwizzle,
                                    CUtensorMapL2promotion, CUtensorMapFloatOOBfill);

void make_map(PFN_encodeTiled enc, CUtensorMap* m, const void* ptr, uint64_t cols, uint64_t rows, uint32_t bcols, uint32_t brows) {
    cuuint64_t dims[2] = {cols, rows};
    cuuint64_t strides[1] = {cols * 2};
    cuuint32_t box[2] = {bcols, brows};
    cuuint32_t es[2] = {1, 1};
    enc(m, CU_TENSOR_MAP_DATA_TYPE_BFLOAT16, 2, const_cast<void*>(ptr), dims, strides, box, es, CU_TENSOR_MAP_INTERLEAVE_NONE,
        CU_TENSOR_MAP_SWIZZLE_128B, CU_TENSOR_MAP_L2_PROMOTION_L2_256B, CU_TENSOR_MAP_FLOAT_OOB_FILL_NONE);
}

void make_map3(PFN_encodeTiled enc, CUtensorMap* m, const void* ptr, uint64_t d0, uint64_t rows, uint64_t d2, uint64_t row_stride_bytes,
               uint64_t d2_stride_bytes, uint32_t b0, uint32_t b1, uint32_t b2) {
    cuuint64_t dims[3] = {d0, rows, d2};
    cuuint64_t strides[2] = {row_stride_bytes, d2_stride_bytes};
    cuuint32_t box[3] = {b0, b1, b2};
    cuuint32_t es[3] = {1, 1, 1};
    enc(m, CU_TENSOR_MAP_DATA_TYPE_BFLOAT16, 3, const_cast<void*>(ptr), dims, strides, box, es, CU_TENSOR_MAP_INTERLEAVE_NONE,
        CU_TENSOR_MAP_SWIZZLE_128B, CU_TENSOR_MAP_L2_PROMOTION_L2_256B, CU_TENSOR_MAP_FLOAT_OOB_FILL_NONE);
}

void make_map_plain(PFN_encodeTiled enc, CUtensorMap* m, const void* ptr, uint64_t cols, uint64_t rows, uint32_t bcols, uint32_t brows) {
    cuuint64_t dims[2] = {cols, rows};
    cuuint64_t strides[1] = {cols * 2};
    cuuint32_t box[2] = {bcols, brows};
    cuuint32_t es[2] = {1, 1};
    enc(m, CU_TENSOR_MAP_DATA_TYPE_BFLOAT16, 2, const_cast<void*>(ptr), dims, strides, box, es, CU_TENSOR_MAP_INTERLEAVE_NONE,
        CU_TENSOR_MAP_SWIZZLE_NONE, CU_TENSOR_MAP_L2_PROMOTION_NONE, CU_TENSOR_MAP_FLOAT_OOB_FILL_NONE);
}

template <typename... KArgs, typename... Args>
void launch(void (*kern)(KArgs...), int grid, int block, int smem, bool pdl, Args... args) {
    cudaLaunchConfig_t cfg = {};
    cfg.gridDim = dim3(grid);
    cfg.blockDim = dim3(block);
    cfg.dynamicSmemBytes = smem;
    cfg.stream = cudaStreamPerThread;
    cudaLaunchAttribute at[1];
    at[0].id = cudaLaunchAttributeProgrammaticStreamSerialization;
    at[0].val.programmaticStreamSerializationAllowed = 1;
    cfg.attrs = at;
    cfg.numAttrs = pdl ? 1 : 0;
    cudaLaunchKernelEx(&cfg, kern, KArgs(args)...);
}

}

extern "C" void kernel_launch(void* const* d_in, const int* in_sizes, int n_in, void* d_out, int out_size) {
    const __nv_bfloat16* x = (const __nv_bfloat16*)d_in[0];
    const __nv_bfloat16* wqkv = (const __nv_bfloat16*)d_in[1];
    const __nv_bfloat16* wo = (const __nv_bfloat16*)d_in[2];
    const __nv_bfloat16* w_r = (const __nv_bfloat16*)d_in[4];
    const __nv_bfloat16* w_gate = (const __nv_bfloat16*)d_in[5];
    const __nv_bfloat16* w_up = (const __nv_bfloat16*)d_in[6];
    const __nv_bfloat16* w_down = (const __nv_bfloat16*)d_in[7];
    __nv_bfloat16* out = (__nv_bfloat16*)d_out;

    static PFN_encodeTiled enc = nullptr;
    static void* g_o_ptr = nullptr;
    if (!enc) {
        cudaDriverEntryPointQueryResult qres;
        void* fn = nullptr;
        cudaGetDriverEntryPoint("cuTensorMapEncodeTiled", &fn, cudaEnableDefault, &qres);
        enc = (PFN_encodeTiled)fn;
        cudaGetSymbolAddress(&g_o_ptr, g_o);
        cudaFuncSetAttribute(k1_qkv, cudaFuncAttributeMaxDynamicSharedMemorySize, K1_SMEM);
        cudaFuncSetAttribute(kf_main, cudaFuncAttributeMaxDynamicSharedMemorySize, KF_SMEM);
    }
    CUtensorMap tm_x, tm_w, tm_o, tm_wo, tm_g, tm_u, tm_d;
    make_map_plain(enc, &tm_d, w_down, DM, FF, 8, 256);
    make_map_plain(enc, &tm_g, w_gate, FF, DM, 16, 128);
    make_map_plain(enc, &tm_u, w_up, FF, DM, 16, 128);
    make_map(enc, &tm_x, x, DM, SEQ, 64, 128);
    make_map3(enc, &tm_w, wqkv, DM, DM, 3, 3 * DM * 2, DM * 2, 64, 64, 3);
    make_map3(enc, &tm_o, g_o_ptr, 64, SEQ, 8, DM * 2, 128, 64, 64, 1);
    make_map3(enc, &tm_wo, wo, 64, DM, 8, DM * 2, 128, 64, 64, 2);

    const bool pdl = true;
    launch(k1_qkv, 128, 544, K1_SMEM, false, tm_x, tm_w, x);
    launch(kf_main, 128, 512, KF_SMEM, pdl, tm_o, tm_wo, tm_g, tm_u, tm_d, x, wo, w_r, w_gate, w_up, w_down, out);
}
```

```cpp
#include <cuda_runtime.h>
#include <cuda_bf16.h>
#include <cuda.h>
#include <stdint.h>

namespace {

constexpr int SEQ = 2048, DM = 512, NH = 32, FF = 1792;

__device__ __align__(1024) uint8_t g_q[NH * 2 * SEQ * 16];
__device__ __align__(1024) uint8_t g_kv[NH * 8 * 16384];
__device__ float g_norm[16 * NH * 3];
__device__ __align__(1024) __nv_bfloat16 g_o[SEQ * DM];
__device__ __align__(1024) __nv_bfloat16 g_h[SEQ * DM];
__device__ __align__(16) uint4 g_cand[64];
__device__ unsigned int g_oflag[32 * 32];
__device__ unsigned int g_hflag[32];
__device__ unsigned int g_sflag[32];
__device__ unsigned int g_act[FF];
__device__ unsigned int g_epoch;
__device__ __align__(16) float4 g_ln1[SEQ];
__device__ __align__(16) float4 g_part[32 * 8 * 64];

#define TSTAMP(K, I)
#define TSTAMP0(K, I)
__device__ __forceinline__ uint32_t smem_u32(const void* p) { return (uint32_t)__cvta_generic_to_shared(p); }
__device__ __forceinline__ void wg_fence() { asm volatile("wgmma.fence.sync.aligned;" ::: "memory"); }
__device__ __forceinline__ void wg_commit() { asm volatile("wgmma.commit_group.sync.aligned;" ::: "memory"); }
template <int N> __device__ __forceinline__ void wg_wait() { asm volatile("wgmma.wait_group.sync.aligned %0;" ::"n"(N) : "memory"); }
template <int N> __device__ __forceinline__ void fence_regs(float (&r)[N]) {
#pragma unroll
    for (int i = 0; i < N; i++) asm volatile("" : "+f"(r[i])::"memory");
}
__device__ __forceinline__ uint64_t make_desc(uint32_t addr, uint32_t lbo, uint32_t sbo, uint32_t swz) {
    uint64_t d = 0;
    d |= (uint64_t)((addr & 0x3FFFF) >> 4);
    d |= (uint64_t)((lbo & 0x3FFFF) >> 4) << 16;
    d |= (uint64_t)((sbo & 0x3FFFF) >> 4) << 32;
    d |= (uint64_t)swz << 62;
    return d;
}
__device__ __forceinline__ void mbar_init(uint32_t bar, uint32_t cnt) {
    asm volatile("mbarrier.init.shared::cta.b64 [%0], %1;" ::"r"(bar), "r"(cnt) : "memory");
}
__device__ __forceinline__ void mbar_expect_tx(uint32_t bar, uint32_t bytes) {
    asm volatile("mbarrier.arrive.expect_tx.shared::cta.b64 _, [%0], %1;" ::"r"(bar), "r"(bytes) : "memory");
}
__device__ __forceinline__ void mbar_arrive(uint32_t bar) {
    asm volatile("mbarrier.arrive.shared::cta.b64 _, [%0];" ::"r"(bar) : "memory");
}
__device__ __forceinline__ void mbar_wait(uint32_t bar, uint32_t parity) {
    asm volatile(
        "{\n.reg .pred p;\nWAIT_%=:\n"
        "mbarrier.try_wait.parity.shared::cta.b64 p, [%0], %1;\n"
        "@p bra DONE_%=;\nbra WAIT_%=;\nDONE_%=:\n}\n" ::"r"(bar), "r"(parity) : "memory");
}
__device__ __forceinline__ void bulk_g2s(uint32_t dst, const void* src, uint32_t bytes, uint32_t bar) {
    asm volatile("cp.async.bulk.shared::cluster.global.mbarrier::complete_tx::bytes [%0], [%1], %2, [%3];" ::"r"(dst),
                 "l"(src), "r"(bytes), "r"(bar) : "memory");
}
__device__ __forceinline__ void bulk_s2g(void* dst, uint32_t src, uint32_t bytes) {
    asm volatile("cp.async.bulk.global.shared::cta.bulk_group [%0], [%1], %2;" ::"l"(dst), "r"(src), "r"(bytes) : "memory");
}
__device__ __forceinline__ void tma_load_2d(uint32_t dst, const CUtensorMap* tm, int c0, int c1, uint32_t bar) {
    asm volatile("cp.async.bulk.tensor.2d.shared::cluster.global.mbarrier::complete_tx::bytes [%0], [%1, {%3, %4}], [%2];" ::"r"(dst),
                 "l"(tm), "r"(bar), "r"(c0), "r"(c1) : "memory");
}
__device__ __forceinline__ void tma_load_3d(uint32_t dst, const CUtensorMap* tm, int c0, int c1, int c2, uint32_t bar) {
    asm volatile("cp.async.bulk.tensor.3d.shared::cluster.global.mbarrier::complete_tx::bytes [%0], [%1, {%3, %4, %5}], [%2];" ::"r"(dst),
                 "l"(tm), "r"(bar), "r"(c0), "r"(c1), "r"(c2) : "memory");
}
__device__ __forceinline__ void tma_load_2d_mc(uint32_t dst, const CUtensorMap* tm, int c0, int c1, uint32_t bar, uint16_t mask) {
    asm volatile("cp.async.bulk.tensor.2d.shared::cluster.global.mbarrier::complete_tx::bytes.multicast::cluster [%0], [%1, {%3, %4}], [%2], %5;" ::"r"(dst),
                 "l"(tm), "r"(bar), "r"(c0), "r"(c1), "h"(mask) : "memory");
}
__device__ __forceinline__ void mbar_arrive_cluster(uint32_t bar, uint32_t cta) {
    asm volatile("{\n.reg .b32 ra;\nmapa.shared::cluster.u32 ra, %0, %1;\nmbarrier.arrive.release.cluster.shared::cluster.b64 _, [ra];\n}" ::"r"(bar), "r"(cta) : "memory");
}
__device__ __forceinline__ void cluster_sync() {
    asm volatile("barrier.cluster.arrive.release.aligned;\nbarrier.cluster.wait.acquire.aligned;" ::: "memory");
}
__device__ __forceinline__ void prefetch_l2(const void* p, uint32_t bytes) {
    asm volatile("cp.async.bulk.prefetch.L2.global [%0], %1;" ::"l"(p), "r"(bytes) : "memory");
}
__device__ __forceinline__ void fence_proxy_async() { asm volatile("fence.proxy.async.shared::cta;" ::: "memory"); }
__device__ __forceinline__ void fence_barrier_init() { asm volatile("fence.mbarrier_init.release.cluster;" ::: "memory"); }
__device__ __forceinline__ void pdl_launch() { asm volatile("griddepcontrol.launch_dependents;" ::: "memory"); }
__device__ __forceinline__ void pdl_wait() { asm volatile("griddepcontrol.wait;" ::: "memory"); }
__device__ __forceinline__ void named_sync(int id, int n) { asm volatile("bar.sync %0, %1;" ::"r"(id), "r"(n) : "memory"); }
__device__ __forceinline__ void named_arrive(int id, int n) { asm volatile("bar.arrive %0, %1;" ::"r"(id), "r"(n) : "memory"); }

__device__ __forceinline__ float ex2f(float x) { float y; asm("ex2.approx.ftz.f32 %0, %1;" : "=f"(y) : "f"(x)); return y; }
__device__ __forceinline__ uint32_t pack_bf16(float lo, float hi) {
    uint32_t r; asm("cvt.rn.bf16x2.f32 %0, %1, %2;" : "=r"(r) : "f"(hi), "f"(lo)); return r;
}
__device__ __forceinline__ float bf_lo(uint32_t v) { return __uint_as_float(v << 16); }
__device__ __forceinline__ float bf_hi(uint32_t v) { return __uint_as_float(v & 0xFFFF0000u); }
__device__ __forceinline__ float rbf(float x) { return __bfloat162float(__float2bfloat16_rn(x)); }
__device__ __forceinline__ uint32_t fma_bf16x2(uint32_t a, uint32_t b, uint32_t c) {
    uint32_t r; asm("fma.rn.bf16x2 %0, %1, %2, %3;" : "=r"(r) : "r"(a), "r"(b), "r"(c)); return r;
}
__device__ __forceinline__ void stmatrix_x4(uint32_t addr, uint32_t r0, uint32_t r1, uint32_t r2, uint32_t r3) {
    asm volatile("stmatrix.sync.aligned.m8n8.x4.shared.b16 [%0], {%1, %2, %3, %4};" ::"r"(addr), "r"(r0), "r"(r1), "r"(r2), "r"(r3) : "memory");
}
__device__ __forceinline__ void stmatrix_x4_trans(uint32_t addr, uint32_t r0, uint32_t r1, uint32_t r2, uint32_t r3) {
    asm volatile("stmatrix.sync.aligned.m8n8.x4.trans.shared.b16 [%0], {%1, %2, %3, %4};" ::"r"(addr), "r"(r0), "r"(r1), "r"(r2), "r"(r3) : "memory");
}

__device__ __forceinline__ void wgmma_k1_n136(float (&d)[68], uint64_t desca, uint64_t descb, int scale_d) {
  asm volatile("{\n.reg .pred p;\nsetp.ne.b32 p, %70, 0;\n"
    "wgmma.mma_async.sync.aligned.m64n136k16.f32.bf16.bf16 "
    "{%0, %1, %2, %3, %4, %5, %6, %7, %8, %9, %10, %11, %12, %13, %14, %15, %16, %17, %18, %19, %20, %21, %22, %23, %24, %25, %26, %27, %28, %29, %30, %31, %32, %33, %34, %35, %36, %37, %38, %39, %40, %41, %42, %43, %44, %45, %46, %47, %48, %49, %50, %51, %52, %53, %54, %55, %56, %57, %58, %59, %60, %61, %62, %63, %64, %65, %66, %67}, "
    "%68, %69, p, 1, 1, 1, 0;\n}\n"
    : "+f"(d[0]), "+f"(d[1]), "+f"(d[2]), "+f"(d[3]), "+f"(d[4]), "+f"(d[5]), "+f"(d[6]), "+f"(d[7]), "+f"(d[8]), "+f"(d[9]), "+f"(d[10]), "+f"(d[11]), "+f"(d[12]), "+f"(d[13]), "+f"(d[14]), "+f"(d[15]), "+f"(d[16]), "+f"(d[17]), "+f"(d[18]), "+f"(d[19]), "+f"(d[20]), "+f"(d[21]), "+f"(d[22]), "+f"(d[23]), "+f"(d[24]), "+f"(d[25]), "+f"(d[26]), "+f"(d[27]), "+f"(d[28]), "+f"(d[29]), "+f"(d[30]), "+f"(d[31]), "+f"(d[32]), "+f"(d[33]), "+f"(d[34]), "+f"(d[35]), "+f"(d[36]), "+f"(d[37]), "+f"(d[38]), "+f"(d[39]), "+f"(d[40]), "+f"(d[41]), "+f"(d[42]), "+f"(d[43]), "+f"(d[44]), "+f"(d[45]), "+f"(d[46]), "+f"(d[47]), "+f"(d[48]), "+f"(d[49]), "+f"(d[50]), "+f"(d[51]), "+f"(d[52]), "+f"(d[53]), "+f"(d[54]), "+f"(d[55]), "+f"(d[56]), "+f"(d[57]), "+f"(d[58]), "+f"(d[59]), "+f"(d[60]), "+f"(d[61]), "+f"(d[62]), "+f"(d[63]), "+f"(d[64]), "+f"(d[65]), "+f"(d[66]), "+f"(d[67])
    : "l"(desca), "l"(descb), "r"(scale_d));
}
__device__ __forceinline__ void wgmma_qk_n64(float (&d)[32], uint32_t a0, uint32_t a1, uint32_t a2, uint32_t a3, uint64_t descb) {
  asm volatile("{\n.reg .pred p;\nsetp.ne.b32 p, 0, 0;\n"
    "wgmma.mma_async.sync.aligned.m64n64k16.f32.bf16.bf16 "
    "{%0, %1, %2, %3, %4, %5, %6, %7, %8, %9, %10, %11, %12, %13, %14, %15, %16, %17, %18, %19, %20, %21, %22, %23, %24, %25, %26, %27, %28, %29, %30, %31}, "
    "{%32, %33, %34, %35}, %36, p, 1, 1, 0;\n}\n"
    : "=f"(d[0]), "=f"(d[1]), "=f"(d[2]), "=f"(d[3]), "=f"(d[4]), "=f"(d[5]), "=f"(d[6]), "=f"(d[7]), "=f"(d[8]), "=f"(d[9]), "=f"(d[10]), "=f"(d[11]), "=f"(d[12]), "=f"(d[13]), "=f"(d[14]), "=f"(d[15]), "=f"(d[16]), "=f"(d[17]), "=f"(d[18]), "=f"(d[19]), "=f"(d[20]), "=f"(d[21]), "=f"(d[22]), "=f"(d[23]), "=f"(d[24]), "=f"(d[25]), "=f"(d[26]), "=f"(d[27]), "=f"(d[28]), "=f"(d[29]), "=f"(d[30]), "=f"(d[31])
    : "r"(a0), "r"(a1), "r"(a2), "r"(a3), "l"(descb));
}
__device__ __forceinline__ void wgmma_pv_n24(float (&d)[12], uint32_t a0, uint32_t a1, uint32_t a2, uint32_t a3, uint64_t descb) {
  asm volatile("{\n.reg .pred p;\nsetp.eq.b32 p, 0, 0;\n"
    "wgmma.mma_async.sync.aligned.m64n24k16.f32.bf16.bf16 "
    "{%0, %1, %2, %3, %4, %5, %6, %7, %8, %9, %10, %11}, "
    "{%12, %13, %14, %15}, %16, p, 1, 1, 1;\n}\n"
    : "+f"(d[0]), "+f"(d[1]), "+f"(d[2]), "+f"(d[3]), "+f"(d[4]), "+f"(d[5]), "+f"(d[6]), "+f"(d[7]), "+f"(d[8]), "+f"(d[9]), "+f"(d[10]), "+f"(d[11])
    : "r"(a0), "r"(a1), "r"(a2), "r"(a3), "l"(descb));
}
__device__ __forceinline__ void wgmma_k3_n64(float (&d)[32], uint64_t desca, uint64_t descb, int scale_d) {
  asm volatile("{\n.reg .pred p;\nsetp.ne.b32 p, %34, 0;\n"
    "wgmma.mma_async.sync.aligned.m64n64k16.f32.bf16.bf16 "
    "{%0, %1, %2, %3, %4, %5, %6, %7, %8, %9, %10, %11, %12, %13, %14, %15, %16, %17, %18, %19, %20, %21, %22, %23, %24, %25, %26, %27, %28, %29, %30, %31}, "
    "%32, %33, p, 1, 1, 0, 1;\n}\n"
    : "+f"(d[0]), "+f"(d[1]), "+f"(d[2]), "+f"(d[3]), "+f"(d[4]), "+f"(d[5]), "+f"(d[6]), "+f"(d[7]), "+f"(d[8]), "+f"(d[9]), "+f"(d[10]), "+f"(d[11]), "+f"(d[12]), "+f"(d[13]), "+f"(d[14]), "+f"(d[15]), "+f"(d[16]), "+f"(d[17]), "+f"(d[18]), "+f"(d[19]), "+f"(d[20]), "+f"(d[21]), "+f"(d[22]), "+f"(d[23]), "+f"(d[24]), "+f"(d[25]), "+f"(d[26]), "+f"(d[27]), "+f"(d[28]), "+f"(d[29]), "+f"(d[30]), "+f"(d[31])
    : "l"(desca), "l"(descb), "r"(scale_d));
}
__device__ __forceinline__ void wgmma_bias_n40(float (&d)[32], uint64_t desca, uint64_t descb) {
  asm volatile("{\n.reg .pred p;\nsetp.eq.b32 p, 0, 0;\n"
    "wgmma.mma_async.sync.aligned.m64n40k16.f32.bf16.bf16 "
    "{%0, %1, %2, %3, %4, %5, %6, %7, %8, %9, %10, %11, %12, %13, %14, %15, %16, %17, %18, %19}, "
    "%20, %21, p, 1, 1, 0, 0;\n}\n"
    : "+f"(d[0]), "+f"(d[1]), "+f"(d[2]), "+f"(d[3]), "+f"(d[4]), "+f"(d[5]), "+f"(d[6]), "+f"(d[7]), "+f"(d[8]), "+f"(d[9]), "+f"(d[10]), "+f"(d[11]), "+f"(d[12]), "+f"(d[13]), "+f"(d[14]), "+f"(d[15]), "+f"(d[16]), "+f"(d[17]), "+f"(d[18]), "+f"(d[19])
    : "l"(desca), "l"(descb));
}

constexpr int K1_XS = 17408;
constexpr int K1_WS = 24576;
constexpr int K1_ST = K1_XS + K1_WS;
constexpr int K1_NST = 5;
constexpr int K1_OFF_MISC = K1_NST * K1_ST;
constexpr int K1_SMEM = K1_OFF_MISC + 2048 + 1024;
constexpr float QSCALE = 0.25f * 1.4426950408889634f;

__global__ void __launch_bounds__(544, 1)
k1_qkv(const __grid_constant__ CUtensorMap tm_x, const __grid_constant__ CUtensorMap tm_w, const __nv_bfloat16* __restrict__ x) {
    extern __shared__ uint8_t smem_raw[];
    const uint32_t sraw = smem_u32(smem_raw);
    const uint32_t sb = (sraw + 1023) & ~1023u;
    uint8_t* sp = smem_raw + (sb - sraw);
    const uint32_t full = sb + K1_OFF_MISC;
    const uint32_t empty = full + 64;
    float* s_mr = (float*)(sp + K1_OFF_MISC + 256);

    const int tid = threadIdx.x, warp = tid >> 5, lane = tid & 31;
    const int mt = blockIdx.x >> 3, nt = blockIdx.x & 7;
    if (tid == 0) TSTAMP0(0, 0);
    pdl_launch();
    if (tid == 512) {
        for (int i = 0; i < K1_NST; i++) { mbar_init(full + 8 * i, 1); mbar_init(empty + 8 * i, 3); }
        fence_barrier_init();
        for (int kb = 0; kb < K1_NST; kb++) {
            mbar_expect_tx(full + 8 * kb, 16384 + K1_WS);
            tma_load_2d(sb + kb * K1_ST, &tm_x, kb * 64, mt * 128, full + 8 * kb);
            tma_load_3d(sb + kb * K1_ST + K1_XS, &tm_w, nt * 64, kb * 64, 0, full + 8 * kb);
        }
    }
    if (tid < K1_NST * 64) {
        *(uint4*)(sp + (tid >> 6) * K1_ST + 16384 + (tid & 63) * 16) =
            make_uint4(0x3F803F80u, 0x3F803F80u, 0x3F803F80u, 0x3F803F80u);
    }
    fence_proxy_async();
    __syncthreads();

    if (warp == 16) {
        if (lane == 0) {
            for (int kb = K1_NST; kb < 8; kb++) {
                const int s = kb % K1_NST;
                mbar_wait(empty + 8 * s, 0);
                mbar_expect_tx(full + 8 * s, 16384 + K1_WS);
                tma_load_2d(sb + s * K1_ST, &tm_x, kb * 64, mt * 128, full + 8 * s);
                tma_load_3d(sb + s * K1_ST + K1_XS, &tm_w, nt * 64, kb * 64, 0, full + 8 * s);
            }
        }
        __syncwarp();
        if (lane < FF / 128) g_act[blockIdx.x * (FF / 128) + lane] = 0xFFFFFFFFu;
        for (int i = lane; i < 128; i += 32) g_part[blockIdx.x * 128 + i] = make_float4(0.f, 0.f, 0.f, 0.f);
        if (blockIdx.x == 1) { g_cand[lane] = make_uint4(0, 0, 0, 0); g_cand[lane + 32] = make_uint4(0, 0, 0, 0); g_hflag[lane] = 0; g_sflag[lane] = 0; }
        if (blockIdx.x == 2) for (int i = lane; i < 1024; i += 32) g_oflag[i] = 0;
    } else if (warp >= 12) {
        const int r = tid - 384;
        const unsigned int tag = *(volatile unsigned int*)&g_epoch + 1u;
        {
            const int row = mt * 128 + nt * 16 + (r >> 3);
            const uint4* xp = (const uint4*)(x + (size_t)row * DM) + (r & 7);
            uint4 v[8];
#pragma unroll
            for (int i = 0; i < 8; i++) v[i] = __ldg(xp + i * 8);
            float s1 = 0.f;
#pragma unroll
            for (int i = 0; i < 8; i++)
                s1 += ((bf_lo(v[i].x) + bf_hi(v[i].x)) + (bf_lo(v[i].y) + bf_hi(v[i].y))) + ((bf_lo(v[i].z) + bf_hi(v[i].z)) + (bf_lo(v[i].w) + bf_hi(v[i].w)));
#pragma unroll
            for (int o = 1; o < 8; o <<= 1) s1 += __shfl_xor_sync(0xffffffffu, s1, o);
            const float mean = s1 * (1.f / DM);
            float q0 = 0.f, q1 = 0.f;
#pragma unroll
            for (int i = 0; i < 8; i++) {
                const uint32_t w[4] = {v[i].x, v[i].y, v[i].z, v[i].w};
#pragma unroll
                for (int j = 0; j < 4; j++) {
                    const float a = bf_lo(w[j]) - mean, b = bf_hi(w[j]) - mean;
                    q0 = fmaf(a, a, q0); q1 = fmaf(b, b, q1);
                }
            }
            float q = q0 + q1;
#pragma unroll
            for (int o = 1; o < 8; o <<= 1) q += __shfl_xor_sync(0xffffffffu, q, o);
            const float den = rbf(sqrtf(rbf(rbf(q * (1.f / DM)) + 1e-5f)));
            if ((r & 7) == 0)
                asm volatile("st.relaxed.gpu.global.v4.f32 [%0], {%1, %2, %3, %4};" ::"l"(g_ln1 + row), "f"(rbf(mean)), "f"(1.f / den),
                             "f"(__uint_as_float(tag)), "f"(0.f) : "memory");
        }
        if (r == 0) TSTAMP0(0, 6);
        {
            float4 v;
            int spins = 0;
            do {
                asm volatile("ld.relaxed.gpu.global.v4.f32 {%0, %1, %2, %3}, [%4];" : "=f"(v.x), "=f"(v.y), "=f"(v.z), "=f"(v.w) : "l"(g_ln1 + mt * 128 + r) : "memory");
            } while (__float_as_uint(v.z) != tag && ++spins < (1 << 22));
            s_mr[(r >> 1) * 4 + (r & 1)] = v.x;
            s_mr[(r >> 1) * 4 + 2 + (r & 1)] = v.y;
        }
        if (r == 0) TSTAMP0(0, 7);
        named_arrive(1, 512);
    } else {
        const int part = warp >> 2, hw = warp & 3;
        float acc[68];
#pragma unroll
        for (int i = 0; i < 68; i++) acc[i] = 0.f;
        fence_regs(acc);
#pragma unroll 1
        for (int kb = 0; kb < 8; kb++) {
            const int s = kb % K1_NST;
            mbar_wait(full + 8 * s, (kb / K1_NST) & 1);
            const uint64_t da = make_desc(sb + s * K1_ST + K1_XS + part * 8192, 1024, 1024, 1);
            const uint64_t db = make_desc(sb + s * K1_ST, 16, 1024, 1);
            wg_fence();
#pragma unroll
            for (int k = 0; k < 4; k++) wgmma_k1_n136(acc, da + k * 128, db + k * 2, (kb | k) != 0);
            wg_commit();
            if (kb > 0 && kb <= 8 - K1_NST) {
                wg_wait<1>();
                if ((tid & 127) == 0) mbar_arrive(empty + 8 * (kb - 1));
            }
        }
        wg_wait<0>();
        fence_regs(acc);
        if (tid == 0) TSTAMP0(0, 1);
        named_sync(1, 512);
        if (tid == 0) TSTAMP0(0, 2);

        const int t = lane & 3;
        const float cs0 = acc[64], cs1 = acc[66];
        const float sc = (part == 0) ? QSCALE : 1.f;
        const uint32_t stg = sb + (hw >> 1) * K1_ST + K1_XS + part * 8192 + (hw & 1) * 4096;
        const uint32_t st_addr = stg + ((lane >> 3) & 1) * 2048 + ((lane >> 4) * 8 + (lane & 7)) * 16;
#pragma unroll
        for (int j = 0; j < 16; j += 2) {
            uint32_t rr[4];
#pragma unroll
            for (int u = 0; u < 2; u++) {
                const int jj = j + u;
                const float4 mr = *(const float4*)(s_mr + (4 * jj + t) * 4);
                const float2 m2 = make_float2(mr.x, mr.y);
                const float ra = mr.z * sc, rb = mr.w * sc;
                rr[2 * u] = pack_bf16((acc[4 * jj] - m2.x * cs0) * ra, (acc[4 * jj + 1] - m2.y * cs0) * rb);
                rr[2 * u + 1] = pack_bf16((acc[4 * jj + 2] - m2.x * cs1) * ra, (acc[4 * jj + 3] - m2.y * cs1) * rb);
            }
            stmatrix_x4_trans(st_addr + j * 128, rr[0], rr[1], rr[2], rr[3]);
        }
        fence_proxy_async();
        __syncwarp();
        if (tid == 0) TSTAMP0(0, 4);
        const int head = nt * 4 + hw;
        if (lane == 0) {
            uint8_t* dst;
            uint32_t hstride;
            if (part == 0) { dst = g_q + (size_t)head * 65536 + mt * 2048; hstride = 32768; }
            else { dst = g_kv + (size_t)head * 131072 + (mt >> 1) * 16384 + (part - 1) * 8192 + (mt & 1) * 2048; hstride = 4096; }
            bulk_s2g(dst, stg, 2048);
            bulk_s2g(dst + hstride, stg + 2048, 2048);
            asm volatile("cp.async.bulk.commit_group;" ::: "memory");
        }
        float nmax = 0.f;
#pragma unroll
        for (int i = 0; i < 4; i++) {
            const int tok = lane + 32 * i;
            const uint4 a = *(const uint4*)(sp + (stg - sb) + tok * 16);
            const uint4 b = *(const uint4*)(sp + (stg - sb) + 2048 + tok * 16);
            uint32_t n0 = fma_bf16x2(a.x, a.x, 0u), n1 = fma_bf16x2(b.x, b.x, 0u);
            n0 = fma_bf16x2(a.y, a.y, n0); n1 = fma_bf16x2(b.y, b.y, n1);
            n0 = fma_bf16x2(a.z, a.z, n0); n1 = fma_bf16x2(b.z, b.z, n1);
            n0 = fma_bf16x2(a.w, a.w, n0); n1 = fma_bf16x2(b.w, b.w, n1);
            const float n2 = ((bf_lo(n0) + bf_hi(n0)) + (bf_lo(n1) + bf_hi(n1))) * 1.125f;
            nmax = (n2 > nmax || n2 != n2) ? n2 : nmax;
        }
#pragma unroll
        for (int o = 16; o > 0; o >>= 1) {
            const float v = __shfl_xor_sync(0xffffffffu, nmax, o);
            nmax = (v > nmax || v != v) ? v : nmax;
        }
        if (tid == 0) TSTAMP0(0, 5);
        if (lane == 0) {
            g_norm[(head * 16 + mt) * 3 + part] = nmax;
            asm volatile("cp.async.bulk.wait_group.read 0;" ::: "memory");
            if (tid == 0) TSTAMP0(0, 3);
        }
    }
}

#define POLL_NS 50
constexpr int KF_CH_G = 16384, KF_CH_S = 20480, KF_NCH = 8;
constexpr int KF_OFF_WO = KF_NCH * KF_CH_S;
constexpr int KF_OFF_MISC = KF_OFF_WO + 65536;
constexpr int KF_SMEM = KF_OFF_MISC + 1536 + 1024;

__device__ __forceinline__ uint32_t exp2_pair_poly(float t0, float t1) {
    const uint32_t w = __byte_perm(__float_as_uint(t0), __float_as_uint(t1), 0x5410);
    uint32_t z;
    asm("lop3.b32 %0, %1, %2, %3, 0xEA;" : "=r"(z) : "r"(w), "r"(0x007F007Fu), "r"(0x3F803F80u));
    uint32_t p = fma_bf16x2(0x3eab3eabu, z, 0xbc73bc73u);
    p = fma_bf16x2(p, z, 0x3f2f3f2fu);
    return p + w - z;
}
constexpr uint32_t KF_EMASK = 0x03FFu;
template <int LO, int HI>
__device__ __forceinline__ void softmax_part(const float (&s)[32], uint32_t (&p)[16]) {
#pragma unroll
    for (int i = LO; i < HI; i++) {
        if ((KF_EMASK >> i) & 1) p[i] = exp2_pair_poly(s[2 * i], s[2 * i + 1]);
        else p[i] = pack_bf16(ex2f(s[2 * i]), ex2f(s[2 * i + 1]));
    }
}
#define KF_PV(P, OFF)                                                                              \
    _Pragma("unroll") for (int kk = 0; kk < 4; kk++)                                               \
        wgmma_pv_n24(o, P[4 * kk], P[4 * kk + 1], P[4 * kk + 2], P[4 * kk + 3], dv + ((OFF) + kk * 16));

__device__ __forceinline__ uint32_t make_key(float r_bf16, int token) {
    const uint32_t u = __float_as_uint(r_bf16) >> 16;
    const uint32_t o = (u & 0x8000u) ? (~u & 0xFFFFu) : (u | 0x8000u);
    return (o << 16) | (uint32_t)(0xFFFF - token);
}
__device__ __forceinline__ float key_value(uint32_t k) {
    const uint32_t o = k >> 16;
    const uint32_t u = (o & 0x8000u) ? (o & 0x7FFFu) : (~o & 0xFFFFu);
    return __uint_as_float(u << 16);
}
__device__ __forceinline__ int key_token(uint32_t k) { return 0xFFFF - (int)(k & 0xFFFFu); }
__device__ __forceinline__ void warp_top2(uint32_t a, uint32_t b, uint32_t& k1, uint32_t& k2) {
    k1 = __reduce_max_sync(0xffffffffu, a > b ? a : b);
    const uint32_t a2 = (a == k1) ? 0u : a, b2 = (b == k1) ? 0u : b;
    k2 = __reduce_max_sync(0xffffffffu, a2 > b2 ? a2 : b2);
}
__device__ __forceinline__ unsigned int ld_acquire(const unsigned int* p) {
    unsigned int v; asm volatile("ld.acquire.gpu.global.u32 %0, [%1];" : "=r"(v) : "l"(p) : "memory"); return v;
}
__device__ __forceinline__ void red_release_add(unsigned int* p) {
    asm volatile("red.release.gpu.global.add.u32 [%0], 1;" ::"l"(p) : "memory");
}

__global__ void __launch_bounds__(512, 1)
kf_main(const __grid_constant__ CUtensorMap tm_o, const __grid_constant__ CUtensorMap tm_wo,
        const __grid_constant__ CUtensorMap tm_g, const __grid_constant__ CUtensorMap tm_u, const __grid_constant__ CUtensorMap tm_d,
        const __nv_bfloat16* __restrict__ x, const __nv_bfloat16* __restrict__ wo, const __nv_bfloat16* __restrict__ w_r,
        const __nv_bfloat16* __restrict__ w_gate, const __nv_bfloat16* __restrict__ w_up, const __nv_bfloat16* __restrict__ w_down,
        __nv_bfloat16* __restrict__ out) {
    extern __shared__ uint8_t smem_raw[];
    const uint32_t sraw = smem_u32(smem_raw);
    const uint32_t sb = (sraw + 1023) & ~1023u;
    uint8_t* sp = smem_raw + (sb - sraw);
    const uint32_t kvbar = sb + KF_OFF_MISC;
    const uint32_t wbar = kvbar + 64;
    const uint32_t obar = wbar + 64;
    const uint32_t gbar = obar + 64;
    const uint32_t dbar = gbar + 8;
    unsigned int* s_cnt = (unsigned int*)(sp + KF_OFF_MISC + 208);
    volatile unsigned int* s_order = (volatile unsigned int*)(sp + KF_OFF_MISC + 1056);
    uint32_t* s_key = (uint32_t*)(sp + KF_OFF_MISC + 256);
    float* s_gu = (float*)(sp + KF_OFF_MISC + 768);
    uint4* s_sel = (uint4*)(sp + KF_OFF_MISC + 1024);
    const int tid = threadIdx.x;
    const int head = blockIdx.x >> 2, quarter = blockIdx.x & 3;
    const int mt = blockIdx.x >> 2, nt = blockIdx.x & 3;
    if (tid == 0) TSTAMP0(1, 0);
    if (tid == 0) {
        for (int c = 0; c < 26; c++) mbar_init(kvbar + 8 * c, 1);
        for (int c = 0; c < 4; c++) s_cnt[c] = 0;
        fence_barrier_init();
        for (int kb = 0; kb < 4; kb++) {
            mbar_expect_tx(wbar + 8 * kb, 16384);
            tma_load_3d(sb + KF_OFF_WO + kb * 16384, &tm_wo, 0, kb * 64, nt * 2, wbar + 8 * kb);
        }
    }
    if (tid == 32) {
        prefetch_l2((const uint8_t*)wo + blockIdx.x * 4096, 4096);
        prefetch_l2((const uint8_t*)w_gate + blockIdx.x * 14336, 14336);
        prefetch_l2((const uint8_t*)w_up + blockIdx.x * 14336, 14336);
        prefetch_l2((const uint8_t*)w_down + blockIdx.x * 14336, 14336);
    }
    if (tid < 24) *(uint4*)(sp + KF_OFF_MISC + 1152 + tid * 16) =
        tid < 8 ? make_uint4(0x42FE4380u, 0x00003D80u, 0u, 0u) : (tid < 16 ? make_uint4(0x3F804380u, 0x00003E00u, 0u, 0u) : make_uint4(0u, 0u, 0u, 0u));
    for (int i = tid; i < KF_NCH * 256; i += 512)
        *(uint4*)(sp + (i >> 8) * KF_CH_S + 16384 + (i & 255) * 16) =
            make_uint4(0x3F803F80u, 0x3F803F80u, 0x3F803F80u, 0x3F803F80u);
    fence_proxy_async();
    __syncthreads();
    pdl_wait();
    if (tid == 0) TSTAMP0(1, 1);
    const uint8_t* kvsrc = g_kv + (size_t)head * (KF_NCH * KF_CH_G);
    if (tid == 32) {
        mbar_expect_tx(kvbar, KF_CH_G);
        bulk_g2s(sb, kvsrc, KF_CH_G, kvbar);
    }
    const int wg = tid >> 7, warp = (tid >> 5) & 3, lane = tid & 31, g = lane >> 2, t = lane & 3;
    if (tid < 32) {
        const int m16 = lane & 15;
        float kn = g_norm[(head * 16 + m16) * 3 + 1];
        float vn = g_norm[(head * 16 + m16) * 3 + 2];
        float qn = g_norm[(head * 16 + quarter * 4 + (lane & 3)) * 3 + 0];
        const bool bad = !(kn < 1e30f) || !(vn < 1e30f) || !(qn < 1e30f);
#pragma unroll
        for (int o = 8; o > 0; o >>= 1) {
            kn = fmaxf(kn, __shfl_xor_sync(0xffffffffu, kn, o));
            qn = fmaxf(qn, __shfl_xor_sync(0xffffffffu, qn, o));
        }
        const bool ok = __all_sync(0xffffffffu, !bad && (qn * kn <= 3500.f));
        if (lane == 0) s_cnt[4] = ok ? 1u : 0u;
    }
    uint32_t qn2[2][4];
#pragma unroll
    for (int ps = 0; ps < 2; ps++) {
        const uint8_t* qb = g_q + (size_t)head * 65536 + (quarter * 512 + ps * 256 + wg * 64 + warp * 16 + g) * 16 + t * 4;
        qn2[ps][0] = *(const uint32_t*)(qb);
        qn2[ps][1] = *(const uint32_t*)(qb + 128);
        qn2[ps][2] = *(const uint32_t*)(qb + 32768);
        qn2[ps][3] = *(const uint32_t*)(qb + 32768 + 128);
    }

    __syncthreads();
    const bool fast = __all_sync(0xffffffffu, s_cnt[4] != 0u);
    if (tid == 32) {
        for (int c = 1; c < KF_NCH; c++) {
            mbar_expect_tx(kvbar + 8 * c, KF_CH_G);
            bulk_g2s(sb + c * KF_CH_S, kvsrc + c * KF_CH_G, KF_CH_G, kvbar + 8 * c);
        }
    }
    if (tid == 0) TSTAMP0(1, 8);
    const uint64_t dbias_a = make_desc(sb + KF_OFF_MISC + 1152, 0, 0, 0);
    const uint64_t dbias_b = make_desc(sb + KF_OFF_MISC + 1280, 128, 0, 0);
    const uint64_t dk0 = make_desc(sb, 4096, 128, 0);
    const uint64_t dv0 = make_desc(sb + 8192, 128, 4096, 0);

#pragma unroll 1
    for (int pass = 0; pass < 2; pass++) {
        const int row0 = quarter * 512 + pass * 256 + wg * 64 + warp * 16 + g;
        uint32_t qa[4];
#pragma unroll
        for (int i = 0; i < 4; i++) qa[i] = pass ? qn2[1][i] : qn2[0][i];
        float o[12];
#pragma unroll
        for (int i = 0; i < 12; i++) o[i] = 0.f;
        fence_regs(o);
#define KF_RELEASE_CHUNK(c)                                                                          \
        if (pass == 1 && (c) >= 1 && (c) <= 4) {                                                     \
            named_sync(4 + wg, 128);            \
            if ((tid & 127) == 0 && atomicAdd(&s_cnt[(c) - 1], 1u) == 3u) {                          \
                mbar_expect_tx(wbar + 8 * (3 + (c)), 16384);                                         \
                tma_load_3d(sb + ((c) - 1) * KF_CH_S, &tm_wo, 0, (3 + (c)) * 64, nt * 2, wbar + 8 * (3 + (c))); \
            }                                                                                        \
        }
        if (fast) {
#pragma unroll 1
            for (int c = 0; c < KF_NCH; c++) {
                const uint64_t dk = dk0 + (uint64_t)(c * (KF_CH_S >> 4));
                const uint64_t dv = dv0 + (uint64_t)(c * (KF_CH_S >> 4));
                float s0[32], s1[32], s2[32], s3[32];
                uint32_t p0[16], p1[16], p2[16], p3[16];
                mbar_wait(kvbar + 8 * c, 0);
                wg_wait<1>();
                wg_fence();
                wgmma_qk_n64(s0, qa[0], qa[1], qa[2], qa[3], dk);
                wgmma_bias_n40(s0, dbias_a, dbias_b);
                wg_commit();
                wg_wait<1>();
                KF_RELEASE_CHUNK(c);
                wg_fence();
                wgmma_qk_n64(s1, qa[0], qa[1], qa[2], qa[3], dk + 64);
                wgmma_bias_n40(s1, dbias_a, dbias_b);
                wg_commit();
                wg_wait<1>();
                fence_regs(s0);
                softmax_part<0, 16>(s0, p0);
                wg_fence();
                KF_PV(p0, 0);
                wg_commit();
                wg_wait<1>();
                fence_regs(s1);
                softmax_part<0, 8>(s1, p1);
                wg_wait<0>();
                wg_fence();
                wgmma_qk_n64(s2, qa[0], qa[1], qa[2], qa[3], dk + 128);
                wgmma_bias_n40(s2, dbias_a, dbias_b);
                wg_commit();
                softmax_part<8, 16>(s1, p1);
                wg_fence();
                KF_PV(p1, 64);
                wg_commit();
                wg_wait<1>();
                fence_regs(s2);
                softmax_part<0, 8>(s2, p2);
                wg_wait<0>();
                wg_fence();
                wgmma_qk_n64(s3, qa[0], qa[1], qa[2], qa[3], dk + 192);
                wgmma_bias_n40(s3, dbias_a, dbias_b);
                wg_commit();
                softmax_part<8, 16>(s2, p2);
                wg_fence();
                KF_PV(p2, 128);
                wg_commit();
                wg_wait<1>();
                fence_regs(s3);
                softmax_part<0, 16>(s3, p3);
                wg_fence();
                KF_PV(p3, 192);
                wg_commit();
            }
            wg_wait<0>();
            fence_regs(o);
        } else {
            float m0 = -INFINITY, m1 = -INFINITY;
#pragma unroll 1
            for (int b = 0; b < 32; b++) {
                const int c = b >> 2;
                const uint64_t dk = dk0 + (uint64_t)(c * (KF_CH_S >> 4) + (b & 3) * 64);
                const uint64_t dv = dv0 + (uint64_t)(c * (KF_CH_S >> 4) + (b & 3) * 64);
                float s[32];
                uint32_t p[16];
                mbar_wait(kvbar + 8 * c, 0);
                wg_fence();
                wgmma_qk_n64(s, qa[0], qa[1], qa[2], qa[3], dk);
                wg_commit();
                if ((b & 3) == 0) { KF_RELEASE_CHUNK(c); }
                wg_wait<0>();
                fence_regs(s);
                float x0 = s[0], x1 = s[2];
#pragma unroll
                for (int j = 0; j < 8; j++) {
                    x0 = fmaxf(x0, fmaxf(s[4 * j], s[4 * j + 1]));
                    x1 = fmaxf(x1, fmaxf(s[4 * j + 2], s[4 * j + 3]));
                }
                x0 = fmaxf(x0, __shfl_xor_sync(0xffffffffu, x0, 1));
                x0 = fmaxf(x0, __shfl_xor_sync(0xffffffffu, x0, 2));
                x1 = fmaxf(x1, __shfl_xor_sync(0xffffffffu, x1, 1));
                x1 = fmaxf(x1, __shfl_xor_sync(0xffffffffu, x1, 2));
                const float n0 = fmaxf(m0, x0), n1 = fmaxf(m1, x1);
                const float c0 = ex2f(m0 - n0), c1 = ex2f(m1 - n1);
                m0 = n0; m1 = n1;
#pragma unroll
                for (int j = 0; j < 3; j++) {
                    o[4 * j] *= c0; o[4 * j + 1] *= c0; o[4 * j + 2] *= c1; o[4 * j + 3] *= c1;
                }
#pragma unroll
                for (int j = 0; j < 8; j++) {
                    p[2 * j] = pack_bf16(ex2f(s[4 * j] - n0), ex2f(s[4 * j + 1] - n0));
                    p[2 * j + 1] = pack_bf16(ex2f(s[4 * j + 2] - n1), ex2f(s[4 * j + 3] - n1));
                }
                fence_regs(o);
                wg_fence();
                KF_PV(p, 0);
                wg_commit();
                wg_wait<0>();
                fence_regs(o);
            }
        }
        const float inv0 = 1.f / o[8], inv1 = 1.f / o[10];
        {
            uint32_t v0 = pack_bf16(o[0] * inv0, o[1] * inv0), v1 = pack_bf16(o[4] * inv0, o[5] * inv0);
            uint32_t v2 = pack_bf16(o[2] * inv1, o[3] * inv1), v3 = pack_bf16(o[6] * inv1, o[7] * inv1);
            const bool o1 = t & 1, o2 = t & 2;
            uint32_t s0 = o1 ? v0 : v1, s1 = o1 ? v2 : v3;
            s0 = __shfl_xor_sync(0xffffffffu, s0, 1); s1 = __shfl_xor_sync(0xffffffffu, s1, 1);
            uint32_t a0 = o1 ? s0 : v0, a1 = o1 ? v1 : s0, b0 = o1 ? s1 : v2, b1 = o1 ? v3 : s1;
            uint32_t x0 = o2 ? a0 : b0, x1 = o2 ? a1 : b1;
            x0 = __shfl_xor_sync(0xffffffffu, x0, 2); x1 = __shfl_xor_sync(0xffffffffu, x1, 2);
            uint4 r;
            r.x = o2 ? x0 : a0; r.y = o2 ? x1 : a1; r.z = o2 ? b0 : x0; r.w = o2 ? b1 : x1;
            *(uint4*)(g_o + (size_t)(row0 + (t >> 1) * 8) * DM + head * 16 + (t & 1) * 8) = r;
        }
        if (tid == 0) TSTAMP0(1, 4 + pass);
    }
    if ((tid >> 5) != 10) named_arrive(1, 512);
    named_sync(4 + wg, 128);
    if ((tid & 127) == 0) {
        asm volatile("fence.acq_rel.gpu;" ::: "memory");
        asm volatile("red.relaxed.gpu.global.add.u32 [%0], 1;" ::"l"(&g_oflag[(quarter * 8 + 4 + wg) * 32 + (head >> 2) * 4]) : "memory");
        asm volatile("red.relaxed.gpu.global.add.u32 [%0], 1;" ::"l"(&g_oflag[(quarter * 8 + wg) * 32 + (head >> 2) * 4]) : "memory");
    }
    if (tid == 0) TSTAMP0(1, 3);

    if (wg < 2) {
        const int wi = warp;
        const int r0 = mt * 64 + wi * 16 + g;
        const int cb = nt * 128 + wg * 64;
        uint32_t xr[16], wr[8];
#pragma unroll
        for (int j = 0; j < 8; j++) {
            xr[2 * j] = __ldg((const uint32_t*)(x + (size_t)r0 * DM + cb + 8 * j + 2 * t));
            xr[2 * j + 1] = __ldg((const uint32_t*)(x + (size_t)(r0 + 8) * DM + cb + 8 * j + 2 * t));
            wr[j] = __ldg((const uint32_t*)(w_r + cb + 8 * j + 2 * t));
        }
        float wsum = 0.f;
        {
            const uint4 a = __ldg((const uint4*)(w_r + lane * 16)), b = __ldg((const uint4*)(w_r + lane * 16 + 8));
            const uint32_t w[8] = {a.x, a.y, a.z, a.w, b.x, b.y, b.z, b.w};
#pragma unroll
            for (int i = 0; i < 8; i++) wsum += bf_lo(w[i]) + bf_hi(w[i]);
#pragma unroll
            for (int o = 16; o > 0; o >>= 1) wsum += __shfl_xor_sync(0xffffffffu, wsum, o);
        }
        float acc[32];
#pragma unroll
        for (int i = 0; i < 32; i++) acc[i] = 0.f;
        fence_regs(acc);
#pragma unroll 1
        for (int i = 0; i < 8; i++) {
            mbar_wait(obar + 8 * i, 0);
            const int kb = __shfl_sync(0xffffffffu, (int)s_order[i], 0);
            mbar_wait(wbar + 8 * kb, 0);
            const uint32_t wa = (kb < 4) ? (KF_OFF_WO + kb * 16384) : ((kb - 4) * KF_CH_S);
            const uint64_t da = make_desc(sb + (4 + (kb >> 1)) * KF_CH_S + (kb & 1) * 8192, 16, 1024, 1);
            const uint64_t db = make_desc(sb + wa + wg * 8192, 1024, 1024, 1);
            wg_fence();
#pragma unroll
            for (int k = 0; k < 4; k++) wgmma_k3_n64(acc, da + k * 2, db + k * 128, (i | k) != 0);
            wg_commit();
        }
        wg_wait<0>();
        fence_regs(acc);
        if (tid == 0) TSTAMP0(2, 2);
        float hv[32];
        uint32_t hp[16];
        float s0 = 0.f, s1 = 0.f, d0 = 0.f, d1 = 0.f;
#pragma unroll
        for (int j = 0; j < 8; j++) {
            const uint32_t a01 = pack_bf16(acc[4 * j], acc[4 * j + 1]), a23 = pack_bf16(acc[4 * j + 2], acc[4 * j + 3]);
            hp[2 * j] = pack_bf16(bf_lo(xr[2 * j]) + bf_lo(a01), bf_hi(xr[2 * j]) + bf_hi(a01));
            hp[2 * j + 1] = pack_bf16(bf_lo(xr[2 * j + 1]) + bf_lo(a23), bf_hi(xr[2 * j + 1]) + bf_hi(a23));
            hv[4 * j] = bf_lo(hp[2 * j]); hv[4 * j + 1] = bf_hi(hp[2 * j]);
            hv[4 * j + 2] = bf_lo(hp[2 * j + 1]); hv[4 * j + 3] = bf_hi(hp[2 * j + 1]);
            const float wl = bf_lo(wr[j]), wh = bf_hi(wr[j]);
            s0 += hv[4 * j] + hv[4 * j + 1];
            s1 += hv[4 * j + 2] + hv[4 * j + 3];
            d0 = fmaf(hv[4 * j], wl, fmaf(hv[4 * j + 1], wh, d0));
            d1 = fmaf(hv[4 * j + 2], wl, fmaf(hv[4 * j + 3], wh, d1));
        }
        float mu0 = s0 * (1.f / 16), mu1 = s1 * (1.f / 16);
        float q0 = 0.f, q1 = 0.f;
#pragma unroll
        for (int j = 0; j < 8; j++) {
            float a = hv[4 * j] - mu0, b = hv[4 * j + 1] - mu0, c = hv[4 * j + 2] - mu1, d = hv[4 * j + 3] - mu1;
            q0 = fmaf(a, a, fmaf(b, b, q0));
            q1 = fmaf(c, c, fmaf(d, d, q1));
        }
#pragma unroll
        for (int o = 1; o < 4; o <<= 1) {
            const float m0 = __shfl_xor_sync(0xffffffffu, mu0, o), m1 = __shfl_xor_sync(0xffffffffu, mu1, o);
            const float e0 = __shfl_xor_sync(0xffffffffu, q0, o), e1 = __shfl_xor_sync(0xffffffffu, q1, o);
            d0 += __shfl_xor_sync(0xffffffffu, d0, o);
            d1 += __shfl_xor_sync(0xffffffffu, d1, o);
            const float f0 = mu0 - m0, f1 = mu1 - m1;
            q0 = q0 + e0 + f0 * f0 * (8.f * o);
            q1 = q1 + e1 + f1 * f1 * (8.f * o);
            mu0 = 0.5f * (mu0 + m0); mu1 = 0.5f * (mu1 + m1);
        }
        float4* part = g_part + (size_t)mt * 512 + wi * 16 + g;
        if (t < 2) {
            float4* dst = part + (nt * 2 + wg) * 64 + t * 8;
            const float a = t ? mu1 : mu0, b = t ? q1 : q0, c = t ? d1 : d0;
            asm volatile("st.relaxed.gpu.global.v4.f32 [%0], {%1, %2, %3, %4};" ::"l"(dst), "f"(a), "f"(b), "f"(c), "f"(1.0f) : "memory");
        }
        if (tid == 0) TSTAMP0(2, 5);
        const uint32_t stg_off = KF_OFF_WO + (wi >> 1) * 16384 + wg * 8192 + (wi & 1) * 4096;
        const uint32_t stg_o = sb + stg_off, stg_h = stg_o + 2048;
        const int srow = (lane & 7) + ((lane >> 3) & 1) * 8;
        const int sj = lane >> 4;
        named_sync(4 + wg, 128);
#pragma unroll
        for (int j = 0; j < 8; j += 2) {
            const uint32_t off = srow * 128 + (((j + sj) ^ (srow & 7)) << 4);
            stmatrix_x4(stg_h + off, hp[2 * j], hp[2 * j + 1], hp[2 * j + 2], hp[2 * j + 3]);
        }
        __syncwarp();
#pragma unroll
        for (int i = 0; i < 4; i++) {
            const int row = i * 4 + (lane >> 3), ch = lane & 7;
            const uint4 vh = *(const uint4*)(sp + stg_off + 2048 + row * 128 + ((ch ^ (row & 7)) << 4));
            *(uint4*)(g_h + (size_t)(mt * 64 + wi * 16 + row) * DM + cb + ch * 8) = vh;
        }
        named_arrive(8, 288);
        if (tid == 0) TSTAMP0(2, 6);
        float mean[2], den[2], rr[2];
        {
            float4 v[4];
            int spins = 0;
            while (true) {
#pragma unroll
                for (int i = 0; i < 4; i++) {
                    const float4* p = part + (t + (i & 1) * 4) * 64 + (i >> 1) * 8;
                    asm volatile("ld.relaxed.gpu.global.v4.f32 {%0, %1, %2, %3}, [%4];" : "=f"(v[i].x), "=f"(v[i].y), "=f"(v[i].z), "=f"(v[i].w) : "l"(p) : "memory");
                }
                const bool ok = (v[0].w != 0.f) && (v[1].w != 0.f) && (v[2].w != 0.f) && (v[3].w != 0.f);
                if (__all_sync(0xffffffffu, ok) || ++spins > (1 << 22)) break;
            }
#pragma unroll
            for (int u = 0; u < 2; u++) {
                float mu = v[2 * u].x + v[2 * u + 1].x, m2 = v[2 * u].y + v[2 * u + 1].y, hw = v[2 * u].z + v[2 * u + 1].z;
#pragma unroll
                for (int o = 1; o < 4; o <<= 1) {
                    mu += __shfl_xor_sync(0xffffffffu, mu, o);
                    m2 += __shfl_xor_sync(0xffffffffu, m2, o);
                    hw += __shfl_xor_sync(0xffffffffu, hw, o);
                }
                mu *= 0.125f;
                const float da = v[2 * u].x - mu, db = v[2 * u + 1].x - mu;
                float dd = 64.f * (da * da + db * db);
#pragma unroll
                for (int o = 1; o < 4; o <<= 1) dd += __shfl_xor_sync(0xffffffffu, dd, o);
                m2 += dd;
                mean[u] = rbf(mu);
                den[u] = rbf(sqrtf(rbf(rbf(m2 * (1.f / DM)) + 1e-5f)));
                rr[u] = rbf((hw - mean[u] * wsum) / den[u]);
            }
        }
        if (tid == 0) TSTAMP0(2, 3);
        named_arrive(3, 512);
        if (nt == 0 && wg == 0) {
            float2* s_st = (float2*)(sp + KF_OFF_WO + 49152);
            if (t == 0) {
                s_key[wi * 16 + g] = make_key(rr[0], r0);
                s_key[wi * 16 + g + 8] = make_key(rr[1], r0 + 8);
                s_st[wi * 16 + g] = make_float2(mean[0], den[0]);
                s_st[wi * 16 + g + 8] = make_float2(mean[1], den[1]);
            }
            named_sync(4, 128);
            if (warp == 0) {
                uint32_t k1, k2;
                warp_top2(s_key[lane], s_key[lane + 32], k1, k2);
                if (lane < 2) {
                    const uint32_t k = lane ? k2 : k1;
                    const float2 st = s_st[key_token(k) & 63];
                    asm volatile("st.relaxed.gpu.global.v4.u32 [%0], {%1, %2, %3, %4};" ::"l"(g_cand + mt * 2 + lane), "r"(k),
                                 "r"(1u), "r"(__float_as_uint(st.x)), "r"(__float_as_uint(st.y)) : "memory");
                }
            }
        }
        const float i0 = 1.f / den[0], i1 = 1.f / den[1];
#pragma unroll
        for (int j = 0; j < 8; j += 2) {
            uint32_t ro[4];
#pragma unroll
            for (int u = 0; u < 2; u++) {
                const int jj = j + u;
                const float a = hv[4 * jj], b = hv[4 * jj + 1], c = hv[4 * jj + 2], d = hv[4 * jj + 3];
                const uint32_t u01 = pack_bf16(a - mean[0], b - mean[0]), u23 = pack_bf16(c - mean[1], d - mean[1]);
                const uint32_t n01 = pack_bf16(bf_lo(u01) * i0, bf_hi(u01) * i0), n23 = pack_bf16(bf_lo(u23) * i1, bf_hi(u23) * i1);
                ro[2 * u] = pack_bf16(a + bf_lo(n01), b + bf_hi(n01));
                ro[2 * u + 1] = pack_bf16(c + bf_lo(n23), d + bf_hi(n23));
            }
            const uint32_t off = srow * 128 + (((j + sj) ^ (srow & 7)) << 4);
            stmatrix_x4(stg_o + off, ro[0], ro[1], ro[2], ro[3]);
        }
        __syncwarp();
#pragma unroll
        for (int i = 0; i < 4; i++) {
            const int row = i * 4 + (lane >> 3), ch = lane & 7;
            const uint4 vo = *(const uint4*)(sp + stg_off + row * 128 + ((ch ^ (row & 7)) << 4));
            *(uint4*)(out + (size_t)(mt * 64 + wi * 16 + row) * DM + cb + ch * 8) = vo;
        }
        named_sync(4 + wg, 128);
        if ((tid & 127) == 0) red_release_add(&g_sflag[mt]);
        if (tid == 0) TSTAMP0(2, 4);
    } else {
        const bool worker = blockIdx.x < FF / 16;
        const bool downer = blockIdx.x >= 64;
        const int mtid = tid - 256, mwarp = mtid >> 5;
        const int c0 = (blockIdx.x - 64) * 8;
        float* s_x = (float*)(sp + KF_OFF_WO + 49152 + 8192);
        float* s_red = (float*)(sp + KF_OFF_WO + 49152 + 8192 + 4096);
        if (mwarp == 2) {
            named_sync(1, 512);
            uint32_t done = 0;
            int n = 0, spins = 0;
            while (done != 0xFFu && ++spins < (1 << 22)) {
                const bool rdy = lane < 8 && ld_acquire(&g_oflag[mt * 32 + lane * 4]) >= 4u;
                uint32_t todo = __ballot_sync(0xffffffffu, rdy) & ~done;
                done |= todo;
                if (todo && lane == 0) {
                    asm volatile("fence.proxy.async.global;" ::: "memory");
                    while (todo) {
                        const int kb = __ffs(todo) - 1;
                        todo &= todo - 1;
                        s_order[n] = kb;
                        mbar_expect_tx(obar + 8 * n, 8192);
                        tma_load_3d(sb + (4 + (kb >> 1)) * KF_CH_S + (kb & 1) * 8192, &tm_o, 0, mt * 64, kb, obar + 8 * n);
                        n++;
                    }
                }
                n = __shfl_sync(0xffffffffu, n, 0);
                if (done != 0xFFu) __nanosleep(POLL_NS);
            }
            if (lane == 0) TSTAMP0(2, 1);
            if (lane == 0 && worker) {
                mbar_expect_tx(gbar, 32768);
                for (int i = 0; i < 4; i++) {
                    tma_load_2d(sb + i * KF_CH_S + 16384, &tm_g, blockIdx.x * 16, i * 128, gbar);
                    tma_load_2d(sb + (4 + i) * KF_CH_S + 16384, &tm_u, blockIdx.x * 16, i * 128, gbar);
                }
            }
        }
        if (mwarp == 1) {
            named_sync(8, 288);
            if (lane == 0) {
                red_release_add(&g_hflag[mt]);
                if (downer) {
                    mbar_expect_tx(dbar, 7 * 4096);
                    for (int i = 0; i < 7; i++) tma_load_2d(sb + (4 + (i >> 2)) * KF_CH_S + (i & 3) * 4096, &tm_d, c0, i * 256, dbar);
                }
            }
            __syncwarp();
        }
        if (mtid == 0) TSTAMP0(3, 0);
        named_sync(3, 512);
        if (mwarp == 0) {
            uint4 ca, cb4;
            int spins = 0;
            while (true) {
                asm volatile("ld.relaxed.gpu.global.v4.u32 {%0, %1, %2, %3}, [%4];" : "=r"(ca.x), "=r"(ca.y), "=r"(ca.z), "=r"(ca.w) : "l"(g_cand + 2 * lane) : "memory");
                asm volatile("ld.relaxed.gpu.global.v4.u32 {%0, %1, %2, %3}, [%4];" : "=r"(cb4.x), "=r"(cb4.y), "=r"(cb4.z), "=r"(cb4.w) : "l"(g_cand + 2 * lane + 1) : "memory");
                const unsigned int hf = ld_acquire(&g_hflag[lane]);
                const bool ok = ca.y != 0 && cb4.y != 0 && hf >= 4u;
                if (__all_sync(0xffffffffu, ok) || ++spins > (1 << 22)) break;
            }
            uint32_t k1, k2;
            warp_top2(ca.x, cb4.x, k1, k2);
            if (ca.x == k1) s_sel[0] = ca;
            if (cb4.x == k1) s_sel[0] = cb4;
            if (ca.x == k2) s_sel[1] = ca;
            if (cb4.x == k2) s_sel[1] = cb4;
        }
        named_sync(2, 256);
        if (mtid == 0) TSTAMP0(3, 1);
        int idx[2];
        float mean[2], inv[2], rv[2];
#pragma unroll
        for (int u = 0; u < 2; u++) {
            const uint4 c = s_sel[u];
            idx[u] = key_token(c.x);
            rv[u] = key_value(c.x);
            mean[u] = __uint_as_float(c.z);
            inv[u] = 1.f / __uint_as_float(c.w);
        }
        float hfin = 0.f;
        if (downer && mtid < 16) hfin = __bfloat162float(__ldcg((const __nv_bfloat16*)(g_h + (size_t)((mtid >> 3) ? idx[1] : idx[0]) * DM + c0 + (mtid & 7))));
        if (worker) {
            {
                const uint32_t h0 = __ldcg((const uint32_t*)(g_h + (size_t)idx[0] * DM + 2 * mtid));
                const uint32_t h1 = __ldcg((const uint32_t*)(g_h + (size_t)idx[1] * DM + 2 * mtid));
                const uint32_t u0 = pack_bf16(bf_lo(h0) - mean[0], bf_hi(h0) - mean[0]), u1 = pack_bf16(bf_lo(h1) - mean[1], bf_hi(h1) - mean[1]);
                const uint32_t n0 = pack_bf16(bf_lo(u0) * inv[0], bf_hi(u0) * inv[0]), n1 = pack_bf16(bf_lo(u1) * inv[1], bf_hi(u1) * inv[1]);
                *(float4*)(s_x + 4 * mtid) = make_float4(bf_lo(n0), bf_lo(n1), bf_hi(n0), bf_hi(n1));
            }
            if (mtid == 0) TSTAMP0(3, 5);
            mbar_wait(gbar, 0);
            named_sync(2, 256);
            if (mtid == 0) TSTAMP0(3, 6);
            float acc[8];
#pragma unroll
            for (int i = 0; i < 8; i++) acc[i] = 0.f;
            const uint8_t* wbase = sp + (mwarp >> 2) * (4 * KF_CH_S) + 16384 + lane * 32 + (mwarp & 3) * 8;
#pragma unroll
            for (int k = 0; k < 16; k++) {
                const uint2 w = *(const uint2*)(wbase + (k >> 2) * KF_CH_S + (k & 3) * 1024);
                const float2 xx = *(const float2*)(s_x + 2 * (lane + 32 * k));
                const float x0 = xx.x, x1 = xx.y;
                const float w0 = bf_lo(w.x), w1 = bf_hi(w.x), w2 = bf_lo(w.y), w3 = bf_hi(w.y);
                acc[0] = fmaf(x0, w0, acc[0]); acc[1] = fmaf(x0, w1, acc[1]); acc[2] = fmaf(x0, w2, acc[2]); acc[3] = fmaf(x0, w3, acc[3]);
                acc[4] = fmaf(x1, w0, acc[4]); acc[5] = fmaf(x1, w1, acc[5]); acc[6] = fmaf(x1, w2, acc[6]); acc[7] = fmaf(x1, w3, acc[7]);
            }
#define KF_STEP(O, N)                                                          \
            {                                                                  \
                const bool up = (lane & (O)) != 0;                             \
                _Pragma("unroll") for (int i = 0; i < (N); i++) {              \
                    const float send = up ? acc[i] : acc[i + (N)];             \
                    const float keep = up ? acc[i + (N)] : acc[i];             \
                    acc[i] = keep + __shfl_xor_sync(0xffffffffu, send, (O));   \
                }                                                              \
            }
            KF_STEP(16, 4) KF_STEP(8, 2) KF_STEP(4, 1)
            acc[0] += __shfl_xor_sync(0xffffffffu, acc[0], 2);
            acc[0] += __shfl_xor_sync(0xffffffffu, acc[0], 1);
            if ((lane & 3) == 0) {
                const int v = ((lane & 16) ? 4 : 0) + ((lane & 8) ? 2 : 0) + ((lane & 4) ? 1 : 0);
                s_gu[(v >> 2) * 32 + mwarp * 4 + (v & 3)] = acc[0];
            }
            named_sync(2, 256);
            if (mtid < 16) {
                uint32_t a2 = 0;
#pragma unroll
                for (int u = 0; u < 2; u++) {
                    const float gb = rbf(s_gu[u * 32 + mtid]);
                    const float sg = rbf(gb / (1.f + __expf(-gb)));
                    float a = sg * rbf(s_gu[u * 32 + 16 + mtid]);
                    uint32_t ab = (uint32_t)__bfloat16_as_ushort(__float2bfloat16_rn(a));
                    if (ab == 0xFFFFu) ab = 0x7FFFu;
                    a2 |= ab << (16 * u);
                }
                asm volatile("st.relaxed.gpu.global.u32 [%0], %1;" ::"l"(g_act + blockIdx.x * 16 + mtid), "r"(a2) : "memory");
            }
            if (mtid == 0) TSTAMP0(3, 2);
        }
        if (downer) {
            uint32_t av[7];
            {
                int spins = 0;
                while (true) {
                    bool ok = true;
#pragma unroll
                    for (int j = 0; j < 7; j++) {
                        asm volatile("ld.relaxed.gpu.global.u32 %0, [%1];" : "=r"(av[j]) : "l"(g_act + mtid + 256 * j) : "memory");
                        ok = ok && ((av[j] & 0xFFFFu) != 0xFFFFu) && ((av[j] >> 16) != 0xFFFFu);
                    }
                    if (mtid < 2) ok = ok && (ld_acquire(&g_sflag[(mtid ? idx[1] : idx[0]) >> 6]) >= 8u);
                    if (__all_sync(0xffffffffu, ok) || ++spins > (1 << 20)) break;
                    __nanosleep(20);
                }
            }
            if (mtid == 0) TSTAMP0(3, 3);
            mbar_wait(dbar, 0);
            float acc[16];
#pragma unroll
            for (int i = 0; i < 16; i++) acc[i] = 0.f;
#pragma unroll
            for (int j = 0; j < 7; j++) {
                const uint4 w = *(const uint4*)(sp + (4 + (j >> 2)) * KF_CH_S + (j & 3) * 4096 + mtid * 16);
                const float a0 = bf_lo(av[j]), a1 = bf_hi(av[j]);
                const uint32_t ww[4] = {w.x, w.y, w.z, w.w};
#pragma unroll
                for (int q = 0; q < 4; q++) {
                    const float wl = bf_lo(ww[q]), wh = bf_hi(ww[q]);
                    acc[2 * q] = fmaf(a0, wl, acc[2 * q]); acc[2 * q + 1] = fmaf(a0, wh, acc[2 * q + 1]);
                    acc[8 + 2 * q] = fmaf(a1, wl, acc[8 + 2 * q]); acc[8 + 2 * q + 1] = fmaf(a1, wh, acc[8 + 2 * q + 1]);
                }
            }
            KF_STEP(16, 8) KF_STEP(8, 4) KF_STEP(4, 2) KF_STEP(2, 1)
            acc[0] += __shfl_xor_sync(0xffffffffu, acc[0], 1);
            if ((lane & 1) == 0) {
                const int v = ((lane & 16) ? 8 : 0) + ((lane & 8) ? 4 : 0) + ((lane & 4) ? 2 : 0) + ((lane & 2) ? 1 : 0);
                s_red[mwarp * 16 + v] = acc[0];
            }
            named_sync(2, 256);
            if (mtid < 16) {
                const int u = mtid >> 3;
                float y = 0.f;
#pragma unroll
                for (int w = 0; w < 8; w++) y += s_red[w * 16 + mtid];
                const float sig = rbf(1.f / (1.f + __expf(-(u ? rv[1] : rv[0]))));
                const float xn = rbf(rbf(hfin - (u ? mean[1] : mean[0])) * (u ? inv[1] : inv[0]));
                const float ov = hfin + rbf(xn + rbf(rbf(y) * sig));
                out[(size_t)(u ? idx[1] : idx[0]) * DM + c0 + (mtid & 7)] = __float2bfloat16_rn(ov);
            }
            if (blockIdx.x == gridDim.x - 1 && mtid == 0) g_epoch = g_epoch + 1u;
            if (mtid == 0) TSTAMP0(3, 4);
        }
    }
}

typedef CUresult (*PFN_encodeTiled)(CUtensorMap*, CUtensorMapDataType, cuuint32_t, void*, const cuuint64_t*, const cuuint64_t*,
                                    const cuuint32_t*, const cuuint32_t*, CUtensorMapInterleave, CUtensorMapSwizzle,
                                    CUtensorMapL2promotion, CUtensorMapFloatOOBfill);

void make_map(PFN_encodeTiled enc, CUtensorMap* m, const void* ptr, uint64_t cols, uint64_t rows, uint32_t bcols, uint32_t brows) {
    cuuint64_t dims[2] = {cols, rows};
    cuuint64_t strides[1] = {cols * 2};
    cuuint32_t box[2] = {bcols, brows};
    cuuint32_t es[2] = {1, 1};
    enc(m, CU_TENSOR_MAP_DATA_TYPE_BFLOAT16, 2, const_cast<void*>(ptr), dims, strides, box, es, CU_TENSOR_MAP_INTERLEAVE_NONE,
        CU_TENSOR_MAP_SWIZZLE_128B, CU_TENSOR_MAP_L2_PROMOTION_L2_256B, CU_TENSOR_MAP_FLOAT_OOB_FILL_NONE);
}

void make_map3(PFN_encodeTiled enc, CUtensorMap* m, const void* ptr, uint64_t d0, uint64_t rows, uint64_t d2, uint64_t row_stride_bytes,
               uint64_t d2_stride_bytes, uint32_t b0, uint32_t b1, uint32_t b2) {
    cuuint64_t dims[3] = {d0, rows, d2};
    cuuint64_t strides[2] = {row_stride_bytes, d2_stride_bytes};
    cuuint32_t box[3] = {b0, b1, b2};
    cuuint32_t es[3] = {1, 1, 1};
    enc(m, CU_TENSOR_MAP_DATA_TYPE_BFLOAT16, 3, const_cast<void*>(ptr), dims, strides, box, es, CU_TENSOR_MAP_INTERLEAVE_NONE,
        CU_TENSOR_MAP_SWIZZLE_128B, CU_TENSOR_MAP_L2_PROMOTION_L2_256B, CU_TENSOR_MAP_FLOAT_OOB_FILL_NONE);
}

void make_map_plain(PFN_encodeTiled enc, CUtensorMap* m, const void* ptr, uint64_t cols, uint64_t rows, uint32_t bcols, uint32_t brows) {
    cuuint64_t dims[2] = {cols, rows};
    cuuint64_t strides[1] = {cols * 2};
    cuuint32_t box[2] = {bcols, brows};
    cuuint32_t es[2] = {1, 1};
    enc(m, CU_TENSOR_MAP_DATA_TYPE_BFLOAT16, 2, const_cast<void*>(ptr), dims, strides, box, es, CU_TENSOR_MAP_INTERLEAVE_NONE,
        CU_TENSOR_MAP_SWIZZLE_NONE, CU_TENSOR_MAP_L2_PROMOTION_NONE, CU_TENSOR_MAP_FLOAT_OOB_FILL_NONE);
}

template <typename... KArgs, typename... Args>
void launch(void (*kern)(KArgs...), int grid, int block, int smem, bool pdl, Args... args) {
    cudaLaunchConfig_t cfg = {};
    cfg.gridDim = dim3(grid);
    cfg.blockDim = dim3(block);
    cfg.dynamicSmemBytes = smem;
    cfg.stream = cudaStreamPerThread;
    cudaLaunchAttribute at[1];
    at[0].id = cudaLaunchAttributeProgrammaticStreamSerialization;
    at[0].val.programmaticStreamSerializationAllowed = 1;
    cfg.attrs = at;
    cfg.numAttrs = pdl ? 1 : 0;
    cudaLaunchKernelEx(&cfg, kern, KArgs(args)...);
}

}

extern "C" void kernel_launch(void* const* d_in, const int* in_sizes, int n_in, void* d_out, int out_size) {
    const __nv_bfloat16* x = (const __nv_bfloat16*)d_in[0];
    const __nv_bfloat16* wqkv = (const __nv_bfloat16*)d_in[1];
    const __nv_bfloat16* wo = (const __nv_bfloat16*)d_in[2];
    const __nv_bfloat16* w_r = (const __nv_bfloat16*)d_in[4];
    const __nv_bfloat16* w_gate = (const __nv_bfloat16*)d_in[5];
    const __nv_bfloat16* w_up = (const __nv_bfloat16*)d_in[6];
    const __nv_bfloat16* w_down = (const __nv_bfloat16*)d_in[7];
    __nv_bfloat16* out = (__nv_bfloat16*)d_out;

    static PFN_encodeTiled enc = nullptr;
    static void* g_o_ptr = nullptr;
    if (!enc) {
        cudaDriverEntryPointQueryResult qres;
        void* fn = nullptr;
        cudaGetDriverEntryPoint("cuTensorMapEncodeTiled", &fn, cudaEnableDefault, &qres);
        enc = (PFN_encodeTiled)fn;
        cudaGetSymbolAddress(&g_o_ptr, g_o);
        cudaFuncSetAttribute(k1_qkv, cudaFuncAttributeMaxDynamicSharedMemorySize, K1_SMEM);
        cudaFuncSetAttribute(kf_main, cudaFuncAttributeMaxDynamicSharedMemorySize, KF_SMEM);
    }
    CUtensorMap tm_x, tm_w, tm_o, tm_wo, tm_g, tm_u, tm_d;
    make_map_plain(enc, &tm_d, w_down, DM, FF, 8, 256);
    make_map_plain(enc, &tm_g, w_gate, FF, DM, 16, 128);
    make_map_plain(enc, &tm_u, w_up, FF, DM, 16, 128);
    make_map(enc, &tm_x, x, DM, SEQ, 64, 128);
    make_map3(enc, &tm_w, wqkv, DM, DM, 3, 3 * DM * 2, DM * 2, 64, 64, 3);
    make_map3(enc, &tm_o, g_o_ptr, 64, SEQ, 8, DM * 2, 128, 64, 64, 1);
    make_map3(enc, &tm_wo, wo, 64, DM, 8, DM * 2, 128, 64, 64, 2);

    const bool pdl = true;
    launch(k1_qkv, 128, 544, K1_SMEM, false, tm_x, tm_w, x);
    launch(kf_main, 128, 512, KF_SMEM, pdl, tm_o, tm_wo, tm_g, tm_u, tm_d, x, wo, w_r, w_gate, w_up, w_down, out);
}
```

```cpp
#include <cuda_runtime.h>
#include <cuda_bf16.h>
#include <cuda.h>
#include <stdint.h>

namespace {

constexpr int SEQ = 2048, DM = 512, NH = 32, FF = 1792;

__device__ __align__(1024) uint8_t g_q[NH * 2 * SEQ * 16];
__device__ __align__(1024) uint8_t g_kv[NH * 8 * 16384];
__device__ float g_norm[16 * NH * 3];
__device__ __align__(1024) __nv_bfloat16 g_o[SEQ * DM];
__device__ __align__(1024) __nv_bfloat16 g_h[SEQ * DM];
__device__ __align__(16) uint4 g_cand[64];
__device__ unsigned int g_oflag[32 * 32];
__device__ unsigned int g_hflag[32];
__device__ unsigned int g_sflag[32];
__device__ unsigned int g_act[FF];
__device__ unsigned int g_epoch;
__device__ __align__(16) float4 g_ln1[SEQ];
__device__ __align__(16) float4 g_part[32 * 8 * 64];

#define TSTAMP(K, I)
#define TSTAMP0(K, I)
__device__ __forceinline__ uint32_t smem_u32(const void* p) { return (uint32_t)__cvta_generic_to_shared(p); }
__device__ __forceinline__ void wg_fence() { asm volatile("wgmma.fence.sync.aligned;" ::: "memory"); }
__device__ __forceinline__ void wg_commit() { asm volatile("wgmma.commit_group.sync.aligned;" ::: "memory"); }
template <int N> __device__ __forceinline__ void wg_wait() { asm volatile("wgmma.wait_group.sync.aligned %0;" ::"n"(N) : "memory"); }
template <int N> __device__ __forceinline__ void fence_regs(float (&r)[N]) {
#pragma unroll
    for (int i = 0; i < N; i++) asm volatile("" : "+f"(r[i])::"memory");
}
__device__ __forceinline__ uint64_t make_desc(uint32_t addr, uint32_t lbo, uint32_t sbo, uint32_t swz) {
    uint64_t d = 0;
    d |= (uint64_t)((addr & 0x3FFFF) >> 4);
    d |= (uint64_t)((lbo & 0x3FFFF) >> 4) << 16;
    d |= (uint64_t)((sbo & 0x3FFFF) >> 4) << 32;
    d |= (uint64_t)swz << 62;
    return d;
}
__device__ __forceinline__ void mbar_init(uint32_t bar, uint32_t cnt) {
    asm volatile("mbarrier.init.shared::cta.b64 [%0], %1;" ::"r"(bar), "r"(cnt) : "memory");
}
__device__ __forceinline__ void mbar_expect_tx(uint32_t bar, uint32_t bytes) {
    asm volatile("mbarrier.arrive.expect_tx.shared::cta.b64 _, [%0], %1;" ::"r"(bar), "r"(bytes) : "memory");
}
__device__ __forceinline__ void mbar_arrive(uint32_t bar) {
    asm volatile("mbarrier.arrive.shared::cta.b64 _, [%0];" ::"r"(bar) : "memory");
}
__device__ __forceinline__ void mbar_wait(uint32_t bar, uint32_t parity) {
    asm volatile(
        "{\n.reg .pred p;\nWAIT_%=:\n"
        "mbarrier.try_wait.parity.shared::cta.b64 p, [%0], %1;\n"
        "@p bra DONE_%=;\nbra WAIT_%=;\nDONE_%=:\n}\n" ::"r"(bar), "r"(parity) : "memory");
}
__device__ __forceinline__ void bulk_g2s(uint32_t dst, const void* src, uint32_t bytes, uint32_t bar) {
    asm volatile("cp.async.bulk.shared::cluster.global.mbarrier::complete_tx::bytes [%0], [%1], %2, [%3];" ::"r"(dst),
                 "l"(src), "r"(bytes), "r"(bar) : "memory");
}
__device__ __forceinline__ void bulk_s2g(void* dst, uint32_t src, uint32_t bytes) {
    asm volatile("cp.async.bulk.global.shared::cta.bulk_group [%0], [%1], %2;" ::"l"(dst), "r"(src), "r"(bytes) : "memory");
}
__device__ __forceinline__ void tma_load_2d(uint32_t dst, const CUtensorMap* tm, int c0, int c1, uint32_t bar) {
    asm volatile("cp.async.bulk.tensor.2d.shared::cluster.global.mbarrier::complete_tx::bytes [%0], [%1, {%3, %4}], [%2];" ::"r"(dst),
                 "l"(tm), "r"(bar), "r"(c0), "r"(c1) : "memory");
}
__device__ __forceinline__ void tma_load_3d(uint32_t dst, const CUtensorMap* tm, int c0, int c1, int c2, uint32_t bar) {
    asm volatile("cp.async.bulk.tensor.3d.shared::cluster.global.mbarrier::complete_tx::bytes [%0], [%1, {%3, %4, %5}], [%2];" ::"r"(dst),
                 "l"(tm), "r"(bar), "r"(c0), "r"(c1), "r"(c2) : "memory");
}
__device__ __forceinline__ void tma_load_2d_mc(uint32_t dst, const CUtensorMap* tm, int c0, int c1, uint32_t bar, uint16_t mask) {
    asm volatile("cp.async.bulk.tensor.2d.shared::cluster.global.mbarrier::complete_tx::bytes.multicast::cluster [%0], [%1, {%3, %4}], [%2], %5;" ::"r"(dst),
                 "l"(tm), "r"(bar), "r"(c0), "r"(c1), "h"(mask) : "memory");
}
__device__ __forceinline__ void mbar_arrive_cluster(uint32_t bar, uint32_t cta) {
    asm volatile("{\n.reg .b32 ra;\nmapa.shared::cluster.u32 ra, %0, %1;\nmbarrier.arrive.release.cluster.shared::cluster.b64 _, [ra];\n}" ::"r"(bar), "r"(cta) : "memory");
}
__device__ __forceinline__ void cluster_sync() {
    asm volatile("barrier.cluster.arrive.release.aligned;\nbarrier.cluster.wait.acquire.aligned;" ::: "memory");
}
__device__ __forceinline__ void prefetch_l2(const void* p, uint32_t bytes) {
    asm volatile("cp.async.bulk.prefetch.L2.global [%0], %1;" ::"l"(p), "r"(bytes) : "memory");
}
__device__ __forceinline__ void fence_proxy_async() { asm volatile("fence.proxy.async.shared::cta;" ::: "memory"); }
__device__ __forceinline__ void fence_barrier_init() { asm volatile("fence.mbarrier_init.release.cluster;" ::: "memory"); }
__device__ __forceinline__ void pdl_launch() { asm volatile("griddepcontrol.launch_dependents;" ::: "memory"); }
__device__ __forceinline__ void pdl_wait() { asm volatile("griddepcontrol.wait;" ::: "memory"); }
__device__ __forceinline__ void named_sync(int id, int n) { asm volatile("bar.sync %0, %1;" ::"r"(id), "r"(n) : "memory"); }
__device__ __forceinline__ void named_arrive(int id, int n) { asm volatile("bar.arrive %0, %1;" ::"r"(id), "r"(n) : "memory"); }

__device__ __forceinline__ float ex2f(float x) { float y; asm("ex2.approx.ftz.f32 %0, %1;" : "=f"(y) : "f"(x)); return y; }
__device__ __forceinline__ uint32_t pack_bf16(float lo, float hi) {
    uint32_t r; asm("cvt.rn.bf16x2.f32 %0, %1, %2;" : "=r"(r) : "f"(hi), "f"(lo)); return r;
}
__device__ __forceinline__ float bf_lo(uint32_t v) { return __uint_as_float(v << 16); }
__device__ __forceinline__ float bf_hi(uint32_t v) { return __uint_as_float(v & 0xFFFF0000u); }
__device__ __forceinline__ float rbf(float x) { return __bfloat162float(__float2bfloat16_rn(x)); }
__device__ __forceinline__ uint32_t fma_bf16x2(uint32_t a, uint32_t b, uint32_t c) {
    uint32_t r; asm("fma.rn.bf16x2 %0, %1, %2, %3;" : "=r"(r) : "r"(a), "r"(b), "r"(c)); return r;
}
__device__ __forceinline__ void stmatrix_x4(uint32_t addr, uint32_t r0, uint32_t r1, uint32_t r2, uint32_t r3) {
    asm volatile("stmatrix.sync.aligned.m8n8.x4.shared.b16 [%0], {%1, %2, %3, %4};" ::"r"(addr), "r"(r0), "r"(r1), "r"(r2), "r"(r3) : "memory");
}
__device__ __forceinline__ void stmatrix_x4_trans(uint32_t addr, uint32_t r0, uint32_t r1, uint32_t r2, uint32_t r3) {
    asm volatile("stmatrix.sync.aligned.m8n8.x4.trans.shared.b16 [%0], {%1, %2, %3, %4};" ::"r"(addr), "r"(r0), "r"(r1), "r"(r2), "r"(r3) : "memory");
}

__device__ __forceinline__ void wgmma_k1_n136(float (&d)[68], uint64_t desca, uint64_t descb, int scale_d) {
  asm volatile("{\n.reg .pred p;\nsetp.ne.b32 p, %70, 0;\n"
    "wgmma.mma_async.sync.aligned.m64n136k16.f32.bf16.bf16 "
    "{%0, %1, %2, %3, %4, %5, %6, %7, %8, %9, %10, %11, %12, %13, %14, %15, %16, %17, %18, %19, %20, %21, %22, %23, %24, %25, %26, %27, %28, %29, %30, %31, %32, %33, %34, %35, %36, %37, %38, %39, %40, %41, %42, %43, %44, %45, %46, %47, %48, %49, %50, %51, %52, %53, %54, %55, %56, %57, %58, %59, %60, %61, %62, %63, %64, %65, %66, %67}, "
    "%68, %69, p, 1, 1, 1, 0;\n}\n"
    : "+f"(d[0]), "+f"(d[1]), "+f"(d[2]), "+f"(d[3]), "+f"(d[4]), "+f"(d[5]), "+f"(d[6]), "+f"(d[7]), "+f"(d[8]), "+f"(d[9]), "+f"(d[10]), "+f"(d[11]), "+f"(d[12]), "+f"(d[13]), "+f"(d[14]), "+f"(d[15]), "+f"(d[16]), "+f"(d[17]), "+f"(d[18]), "+f"(d[19]), "+f"(d[20]), "+f"(d[21]), "+f"(d[22]), "+f"(d[23]), "+f"(d[24]), "+f"(d[25]), "+f"(d[26]), "+f"(d[27]), "+f"(d[28]), "+f"(d[29]), "+f"(d[30]), "+f"(d[31]), "+f"(d[32]), "+f"(d[33]), "+f"(d[34]), "+f"(d[35]), "+f"(d[36]), "+f"(d[37]), "+f"(d[38]), "+f"(d[39]), "+f"(d[40]), "+f"(d[41]), "+f"(d[42]), "+f"(d[43]), "+f"(d[44]), "+f"(d[45]), "+f"(d[46]), "+f"(d[47]), "+f"(d[48]), "+f"(d[49]), "+f"(d[50]), "+f"(d[51]), "+f"(d[52]), "+f"(d[53]), "+f"(d[54]), "+f"(d[55]), "+f"(d[56]), "+f"(d[57]), "+f"(d[58]), "+f"(d[59]), "+f"(d[60]), "+f"(d[61]), "+f"(d[62]), "+f"(d[63]), "+f"(d[64]), "+f"(d[65]), "+f"(d[66]), "+f"(d[67])
    : "l"(desca), "l"(descb), "r"(scale_d));
}
__device__ __forceinline__ void wgmma_qk_n64(float (&d)[32], uint32_t a0, uint32_t a1, uint32_t a2, uint32_t a3, uint64_t descb) {
  asm volatile("{\n.reg .pred p;\nsetp.ne.b32 p, 0, 0;\n"
    "wgmma.mma_async.sync.aligned.m64n64k16.f32.bf16.bf16 "
    "{%0, %1, %2, %3, %4, %5, %6, %7, %8, %9, %10, %11, %12, %13, %14, %15, %16, %17, %18, %19, %20, %21, %22, %23, %24, %25, %26, %27, %28, %29, %30, %31}, "
    "{%32, %33, %34, %35}, %36, p, 1, 1, 0;\n}\n"
    : "=f"(d[0]), "=f"(d[1]), "=f"(d[2]), "=f"(d[3]), "=f"(d[4]), "=f"(d[5]), "=f"(d[6]), "=f"(d[7]), "=f"(d[8]), "=f"(d[9]), "=f"(d[10]), "=f"(d[11]), "=f"(d[12]), "=f"(d[13]), "=f"(d[14]), "=f"(d[15]), "=f"(d[16]), "=f"(d[17]), "=f"(d[18]), "=f"(d[19]), "=f"(d[20]), "=f"(d[21]), "=f"(d[22]), "=f"(d[23]), "=f"(d[24]), "=f"(d[25]), "=f"(d[26]), "=f"(d[27]), "=f"(d[28]), "=f"(d[29]), "=f"(d[30]), "=f"(d[31])
    : "r"(a0), "r"(a1), "r"(a2), "r"(a3), "l"(descb));
}
__device__ __forceinline__ void wgmma_pv_n24(float (&d)[12], uint32_t a0, uint32_t a1, uint32_t a2, uint32_t a3, uint64_t descb) {
  asm volatile("{\n.reg .pred p;\nsetp.eq.b32 p, 0, 0;\n"
    "wgmma.mma_async.sync.aligned.m64n24k16.f32.bf16.bf16 "
    "{%0, %1, %2, %3, %4, %5, %6, %7, %8, %9, %10, %11}, "
    "{%12, %13, %14, %15}, %16, p, 1, 1, 1;\n}\n"
    : "+f"(d[0]), "+f"(d[1]), "+f"(d[2]), "+f"(d[3]), "+f"(d[4]), "+f"(d[5]), "+f"(d[6]), "+f"(d[7]), "+f"(d[8]), "+f"(d[9]), "+f"(d[10]), "+f"(d[11])
    : "r"(a0), "r"(a1), "r"(a2), "r"(a3), "l"(descb));
}
__device__ __forceinline__ void wgmma_k3_n64(float (&d)[32], uint64_t desca, uint64_t descb, int scale_d) {
  asm volatile("{\n.reg .pred p;\nsetp.ne.b32 p, %34, 0;\n"
    "wgmma.mma_async.sync.aligned.m64n64k16.f32.bf16.bf16 "
    "{%0, %1, %2, %3, %4, %5, %6, %7, %8, %9, %10, %11, %12, %13, %14, %15, %16, %17, %18, %19, %20, %21, %22, %23, %24, %25, %26, %27, %28, %29, %30, %31}, "
    "%32, %33, p, 1, 1, 0, 1;\n}\n"
    : "+f"(d[0]), "+f"(d[1]), "+f"(d[2]), "+f"(d[3]), "+f"(d[4]), "+f"(d[5]), "+f"(d[6]), "+f"(d[7]), "+f"(d[8]), "+f"(d[9]), "+f"(d[10]), "+f"(d[11]), "+f"(d[12]), "+f"(d[13]), "+f"(d[14]), "+f"(d[15]), "+f"(d[16]), "+f"(d[17]), "+f"(d[18]), "+f"(d[19]), "+f"(d[20]), "+f"(d[21]), "+f"(d[22]), "+f"(d[23]), "+f"(d[24]), "+f"(d[25]), "+f"(d[26]), "+f"(d[27]), "+f"(d[28]), "+f"(d[29]), "+f"(d[30]), "+f"(d[31])
    : "l"(desca), "l"(descb), "r"(scale_d));
}
__device__ __forceinline__ void wgmma_bias_n40(float (&d)[32], uint64_t desca, uint64_t descb) {
  asm volatile("{\n.reg .pred p;\nsetp.eq.b32 p, 0, 0;\n"
    "wgmma.mma_async.sync.aligned.m64n40k16.f32.bf16.bf16 "
    "{%0, %1, %2, %3, %4, %5, %6, %7, %8, %9, %10, %11, %12, %13, %14, %15, %16, %17, %18, %19}, "
    "%20, %21, p, 1, 1, 0, 0;\n}\n"
    : "+f"(d[0]), "+f"(d[1]), "+f"(d[2]), "+f"(d[3]), "+f"(d[4]), "+f"(d[5]), "+f"(d[6]), "+f"(d[7]), "+f"(d[8]), "+f"(d[9]), "+f"(d[10]), "+f"(d[11]), "+f"(d[12]), "+f"(d[13]), "+f"(d[14]), "+f"(d[15]), "+f"(d[16]), "+f"(d[17]), "+f"(d[18]), "+f"(d[19])
    : "l"(desca), "l"(descb));
}

constexpr int K1_XS = 17408;
constexpr int K1_WS = 24576;
constexpr int K1_ST = K1_XS + K1_WS;
constexpr int K1_NST = 5;
constexpr int K1_OFF_MISC = K1_NST * K1_ST;
constexpr int K1_SMEM = K1_OFF_MISC + 2048 + 1024;
constexpr float QSCALE = 0.25f * 1.4426950408889634f;

__global__ void __launch_bounds__(544, 1)
k1_qkv(const __grid_constant__ CUtensorMap tm_x, const __grid_constant__ CUtensorMap tm_w, const __nv_bfloat16* __restrict__ x) {
    extern __shared__ uint8_t smem_raw[];
    const uint32_t sraw = smem_u32(smem_raw);
    const uint32_t sb = (sraw + 1023) & ~1023u;
    uint8_t* sp = smem_raw + (sb - sraw);
    const uint32_t full = sb + K1_OFF_MISC;
    const uint32_t empty = full + 64;
    float* s_mr = (float*)(sp + K1_OFF_MISC + 256);

    const int tid = threadIdx.x, warp = tid >> 5, lane = tid & 31;
    const int mt = blockIdx.x >> 3, nt = blockIdx.x & 7;
    if (tid == 0) TSTAMP0(0, 0);
    pdl_launch();
    if (tid == 512) {
        for (int i = 0; i < K1_NST; i++) { mbar_init(full + 8 * i, 1); mbar_init(empty + 8 * i, 3); }
        fence_barrier_init();
        for (int kb = 0; kb < K1_NST; kb++) {
            mbar_expect_tx(full + 8 * kb, 16384 + K1_WS);
            tma_load_2d(sb + kb * K1_ST, &tm_x, kb * 64, mt * 128, full + 8 * kb);
            tma_load_3d(sb + kb * K1_ST + K1_XS, &tm_w, nt * 64, kb * 64, 0, full + 8 * kb);
        }
    }
    if (tid < K1_NST * 64) {
        *(uint4*)(sp + (tid >> 6) * K1_ST + 16384 + (tid & 63) * 16) =
            make_uint4(0x3F803F80u, 0x3F803F80u, 0x3F803F80u, 0x3F803F80u);
    }
    fence_proxy_async();
    __syncthreads();

    if (warp == 16) {
        if (lane == 0) {
            for (int kb = K1_NST; kb < 8; kb++) {
                const int s = kb % K1_NST;
                mbar_wait(empty + 8 * s, 0);
                mbar_expect_tx(full + 8 * s, 16384 + K1_WS);
                tma_load_2d(sb + s * K1_ST, &tm_x, kb * 64, mt * 128, full + 8 * s);
                tma_load_3d(sb + s * K1_ST + K1_XS, &tm_w, nt * 64, kb * 64, 0, full + 8 * s);
            }
        }
        __syncwarp();
        if (lane < FF / 128) g_act[blockIdx.x * (FF / 128) + lane] = 0xFFFFFFFFu;
        for (int i = lane; i < 128; i += 32) g_part[blockIdx.x * 128 + i] = make_float4(0.f, 0.f, 0.f, 0.f);
        if (blockIdx.x == 1) { g_cand[lane] = make_uint4(0, 0, 0, 0); g_cand[lane + 32] = make_uint4(0, 0, 0, 0); g_hflag[lane] = 0; g_sflag[lane] = 0; }
        if (blockIdx.x == 2) for (int i = lane; i < 1024; i += 32) g_oflag[i] = 0;
    } else if (warp >= 12) {
        const int r = tid - 384;
        const unsigned int tag = *(volatile unsigned int*)&g_epoch + 1u;
        {
            const int row = mt * 128 + nt * 16 + (r >> 3);
            const uint4* xp = (const uint4*)(x + (size_t)row * DM) + (r & 7);
            uint4 v[8];
#pragma unroll
            for (int i = 0; i < 8; i++) v[i] = __ldg(xp + i * 8);
            float s1 = 0.f;
#pragma unroll
            for (int i = 0; i < 8; i++)
                s1 += ((bf_lo(v[i].x) + bf_hi(v[i].x)) + (bf_lo(v[i].y) + bf_hi(v[i].y))) + ((bf_lo(v[i].z) + bf_hi(v[i].z)) + (bf_lo(v[i].w) + bf_hi(v[i].w)));
#pragma unroll
            for (int o = 1; o < 8; o <<= 1) s1 += __shfl_xor_sync(0xffffffffu, s1, o);
            const float mean = s1 * (1.f / DM);
            float q0 = 0.f, q1 = 0.f;
#pragma unroll
            for (int i = 0; i < 8; i++) {
                const uint32_t w[4] = {v[i].x, v[i].y, v[i].z, v[i].w};
#pragma unroll
                for (int j = 0; j < 4; j++) {
                    const float a = bf_lo(w[j]) - mean, b = bf_hi(w[j]) - mean;
                    q0 = fmaf(a, a, q0); q1 = fmaf(b, b, q1);
                }
            }
            float q = q0 + q1;
#pragma unroll
            for (int o = 1; o < 8; o <<= 1) q += __shfl_xor_sync(0xffffffffu, q, o);
            const float den = rbf(sqrtf(rbf(rbf(q * (1.f / DM)) + 1e-5f)));
            if ((r & 7) == 0)
                asm volatile("st.relaxed.gpu.global.v4.f32 [%0], {%1, %2, %3, %4};" ::"l"(g_ln1 + row), "f"(rbf(mean)), "f"(1.f / den),
                             "f"(__uint_as_float(tag)), "f"(0.f) : "memory");
        }
        if (r == 0) TSTAMP0(0, 6);
        {
            float4 v;
            int spins = 0;
            do {
                asm volatile("ld.relaxed.gpu.global.v4.f32 {%0, %1, %2, %3}, [%4];" : "=f"(v.x), "=f"(v.y), "=f"(v.z), "=f"(v.w) : "l"(g_ln1 + mt * 128 + r) : "memory");
            } while (__float_as_uint(v.z) != tag && ++spins < (1 << 22));
            s_mr[(r >> 1) * 4 + (r & 1)] = v.x;
            s_mr[(r >> 1) * 4 + 2 + (r & 1)] = v.y;
        }
        if (r == 0) TSTAMP0(0, 7);
        named_arrive(1, 512);
    } else {
        const int part = warp >> 2, hw = warp & 3;
        float acc[68];
#pragma unroll
        for (int i = 0; i < 68; i++) acc[i] = 0.f;
        fence_regs(acc);
#pragma unroll 1
        for (int kb = 0; kb < 8; kb++) {
            const int s = kb % K1_NST;
            mbar_wait(full + 8 * s, (kb / K1_NST) & 1);
            const uint64_t da = make_desc(sb + s * K1_ST + K1_XS + part * 8192, 1024, 1024, 1);
            const uint64_t db = make_desc(sb + s * K1_ST, 16, 1024, 1);
            wg_fence();
#pragma unroll
            for (int k = 0; k < 4; k++) wgmma_k1_n136(acc, da + k * 128, db + k * 2, (kb | k) != 0);
            wg_commit();
            if (kb > 0 && kb <= 8 - K1_NST) {
                wg_wait<1>();
                if ((tid & 127) == 0) mbar_arrive(empty + 8 * (kb - 1));
            }
        }
        wg_wait<0>();
        fence_regs(acc);
        if (tid == 0) TSTAMP0(0, 1);
        named_sync(1, 512);
        if (tid == 0) TSTAMP0(0, 2);

        const int t = lane & 3;
        const float cs0 = acc[64], cs1 = acc[66];
        const float sc = (part == 0) ? QSCALE : 1.f;
        const uint32_t stg = sb + (hw >> 1) * K1_ST + K1_XS + part * 8192 + (hw & 1) * 4096;
        const uint32_t st_addr = stg + ((lane >> 3) & 1) * 2048 + ((lane >> 4) * 8 + (lane & 7)) * 16;
#pragma unroll
        for (int j = 0; j < 16; j += 2) {
            uint32_t rr[4];
#pragma unroll
            for (int u = 0; u < 2; u++) {
                const int jj = j + u;
                const float4 mr = *(const float4*)(s_mr + (4 * jj + t) * 4);
                const float2 m2 = make_float2(mr.x, mr.y);
                const float ra = mr.z * sc, rb = mr.w * sc;
                rr[2 * u] = pack_bf16((acc[4 * jj] - m2.x * cs0) * ra, (acc[4 * jj + 1] - m2.y * cs0) * rb);
                rr[2 * u + 1] = pack_bf16((acc[4 * jj + 2] - m2.x * cs1) * ra, (acc[4 * jj + 3] - m2.y * cs1) * rb);
            }
            stmatrix_x4_trans(st_addr + j * 128, rr[0], rr[1], rr[2], rr[3]);
        }
        __syncwarp();
        if (tid == 0) TSTAMP0(0, 4);
        const int head = nt * 4 + hw;
        uint8_t* dst;
        uint32_t hstride;
        if (part == 0) { dst = g_q + (size_t)head * 65536 + mt * 2048; hstride = 32768; }
        else { dst = g_kv + (size_t)head * 131072 + (mt >> 1) * 16384 + (part - 1) * 8192 + (mt & 1) * 2048; hstride = 4096; }
        float nmax = 0.f;
#pragma unroll
        for (int i = 0; i < 4; i++) {
            const int tok = lane + 32 * i;
            const uint4 a = *(const uint4*)(sp + (stg - sb) + tok * 16);
            const uint4 b = *(const uint4*)(sp + (stg - sb) + 2048 + tok * 16);
            *(uint4*)(dst + tok * 16) = a;
            *(uint4*)(dst + hstride + tok * 16) = b;
            uint32_t n0 = fma_bf16x2(a.x, a.x, 0u), n1 = fma_bf16x2(b.x, b.x, 0u);
            n0 = fma_bf16x2(a.y, a.y, n0); n1 = fma_bf16x2(b.y, b.y, n1);
            n0 = fma_bf16x2(a.z, a.z, n0); n1 = fma_bf16x2(b.z, b.z, n1);
            n0 = fma_bf16x2(a.w, a.w, n0); n1 = fma_bf16x2(b.w, b.w, n1);
            const float n2 = ((bf_lo(n0) + bf_hi(n0)) + (bf_lo(n1) + bf_hi(n1))) * 1.125f;
            nmax = (n2 > nmax || n2 != n2) ? n2 : nmax;
        }
#pragma unroll
        for (int o = 16; o > 0; o >>= 1) {
            const float v = __shfl_xor_sync(0xffffffffu, nmax, o);
            nmax = (v > nmax || v != v) ? v : nmax;
        }
        if (tid == 0) TSTAMP0(0, 5);
        if (lane == 0) {
            g_norm[(head * 16 + mt) * 3 + part] = nmax;
            if (tid == 0) TSTAMP0(0, 3);
        }
    }
}

#define POLL_NS 50
constexpr int KF_CH_G = 16384, KF_CH_S = 20480, KF_NCH = 8;
constexpr int KF_OFF_WO = KF_NCH * KF_CH_S;
constexpr int KF_OFF_MISC = KF_OFF_WO + 65536;
constexpr int KF_SMEM = KF_OFF_MISC + 1536 + 1024;

__device__ __forceinline__ uint32_t exp2_pair_poly(float t0, float t1) {
    const uint32_t w = __byte_perm(__float_as_uint(t0), __float_as_uint(t1), 0x5410);
    uint32_t z;
    asm("lop3.b32 %0, %1, %2, %3, 0xEA;" : "=r"(z) : "r"(w), "r"(0x007F007Fu), "r"(0x3F803F80u));
    uint32_t p = fma_bf16x2(0x3eab3eabu, z, 0xbc73bc73u);
    p = fma_bf16x2(p, z, 0x3f2f3f2fu);
    return p + w - z;
}
constexpr uint32_t KF_EMASK = 0x03FFu;
template <int LO, int HI>
__device__ __forceinline__ void softmax_part(const float (&s)[32], uint32_t (&p)[16]) {
#pragma unroll
    for (int i = LO; i < HI; i++) {
        if ((KF_EMASK >> i) & 1) p[i] = exp2_pair_poly(s[2 * i], s[2 * i + 1]);
        else p[i] = pack_bf16(ex2f(s[2 * i]), ex2f(s[2 * i + 1]));
    }
}
#define KF_PV(P, OFF)                                                                              \
    _Pragma("unroll") for (int kk = 0; kk < 4; kk++)                                               \
        wgmma_pv_n24(o, P[4 * kk], P[4 * kk + 1], P[4 * kk + 2], P[4 * kk + 3], dv + ((OFF) + kk * 16));

__device__ __forceinline__ uint32_t make_key(float r_bf16, int token) {
    const uint32_t u = __float_as_uint(r_bf16) >> 16;
    const uint32_t o = (u & 0x8000u) ? (~u & 0xFFFFu) : (u | 0x8000u);
    return (o << 16) | (uint32_t)(0xFFFF - token);
}
__device__ __forceinline__ float key_value(uint32_t k) {
    const uint32_t o = k >> 16;
    const uint32_t u = (o & 0x8000u) ? (o & 0x7FFFu) : (~o & 0xFFFFu);
    return __uint_as_float(u << 16);
}
__device__ __forceinline__ int key_token(uint32_t k) { return 0xFFFF - (int)(k & 0xFFFFu); }
__device__ __forceinline__ void warp_top2(uint32_t a, uint32_t b, uint32_t& k1, uint32_t& k2) {
    k1 = __reduce_max_sync(0xffffffffu, a > b ? a : b);
    const uint32_t a2 = (a == k1) ? 0u : a, b2 = (b == k1) ? 0u : b;
    k2 = __reduce_max_sync(0xffffffffu, a2 > b2 ? a2 : b2);
}
__device__ __forceinline__ unsigned int ld_acquire(const unsigned int* p) {
    unsigned int v; asm volatile("ld.acquire.gpu.global.u32 %0, [%1];" : "=r"(v) : "l"(p) : "memory"); return v;
}
__device__ __forceinline__ void red_release_add(unsigned int* p) {
    asm volatile("red.release.gpu.global.add.u32 [%0], 1;" ::"l"(p) : "memory");
}

__global__ void __launch_bounds__(512, 1)
kf_main(const __grid_constant__ CUtensorMap tm_o, const __grid_constant__ CUtensorMap tm_wo,
        const __grid_constant__ CUtensorMap tm_g, const __grid_constant__ CUtensorMap tm_u, const __grid_constant__ CUtensorMap tm_d,
        const __nv_bfloat16* __restrict__ x, const __nv_bfloat16* __restrict__ wo, const __nv_bfloat16* __restrict__ w_r,
        const __nv_bfloat16* __restrict__ w_gate, const __nv_bfloat16* __restrict__ w_up, const __nv_bfloat16* __restrict__ w_down,
        __nv_bfloat16* __restrict__ out) {
    extern __shared__ uint8_t smem_raw[];
    const uint32_t sraw = smem_u32(smem_raw);
    const uint32_t sb = (sraw + 1023) & ~1023u;
    uint8_t* sp = smem_raw + (sb - sraw);
    const uint32_t kvbar = sb + KF_OFF_MISC;
    const uint32_t wbar = kvbar + 64;
    const uint32_t obar = wbar + 64;
    const uint32_t gbar = obar + 64;
    const uint32_t dbar = gbar + 8;
    unsigned int* s_cnt = (unsigned int*)(sp + KF_OFF_MISC + 208);
    volatile unsigned int* s_order = (volatile unsigned int*)(sp + KF_OFF_MISC + 1056);
    uint32_t* s_key = (uint32_t*)(sp + KF_OFF_MISC + 256);
    float* s_gu = (float*)(sp + KF_OFF_MISC + 768);
    uint4* s_sel = (uint4*)(sp + KF_OFF_MISC + 1024);
    const int tid = threadIdx.x;
    const int head = blockIdx.x >> 2, quarter = blockIdx.x & 3;
    const int mt = blockIdx.x >> 2, nt = blockIdx.x & 3;
    if (tid == 0) TSTAMP0(1, 0);
    if (tid == 0) {
        for (int c = 0; c < 26; c++) mbar_init(kvbar + 8 * c, 1);
        for (int c = 0; c < 4; c++) s_cnt[c] = 0;
        fence_barrier_init();
        for (int kb = 0; kb < 4; kb++) {
            mbar_expect_tx(wbar + 8 * kb, 16384);
            tma_load_3d(sb + KF_OFF_WO + kb * 16384, &tm_wo, 0, kb * 64, nt * 2, wbar + 8 * kb);
        }
    }
    if (tid == 32) {
        prefetch_l2((const uint8_t*)wo + blockIdx.x * 4096, 4096);
        prefetch_l2((const uint8_t*)w_gate + blockIdx.x * 14336, 14336);
        prefetch_l2((const uint8_t*)w_up + blockIdx.x * 14336, 14336);
        prefetch_l2((const uint8_t*)w_down + blockIdx.x * 14336, 14336);
    }
    if (tid < 24) *(uint4*)(sp + KF_OFF_MISC + 1152 + tid * 16) =
        tid < 8 ? make_uint4(0x42FE4380u, 0x00003D80u, 0u, 0u) : (tid < 16 ? make_uint4(0x3F804380u, 0x00003E00u, 0u, 0u) : make_uint4(0u, 0u, 0u, 0u));
    for (int i = tid; i < KF_NCH * 256; i += 512)
        *(uint4*)(sp + (i >> 8) * KF_CH_S + 16384 + (i & 255) * 16) =
            make_uint4(0x3F803F80u, 0x3F803F80u, 0x3F803F80u, 0x3F803F80u);
    fence_proxy_async();
    __syncthreads();
    pdl_wait();
    if (tid == 0) TSTAMP0(1, 1);
    const uint8_t* kvsrc = g_kv + (size_t)head * (KF_NCH * KF_CH_G);
    if (tid == 32) {
        mbar_expect_tx(kvbar, KF_CH_G);
        bulk_g2s(sb, kvsrc, KF_CH_G, kvbar);
    }
    const int wg = tid >> 7, warp = (tid >> 5) & 3, lane = tid & 31, g = lane >> 2, t = lane & 3;
    if (tid < 32) {
        const int m16 = lane & 15;
        float kn = g_norm[(head * 16 + m16) * 3 + 1];
        float vn = g_norm[(head * 16 + m16) * 3 + 2];
        float qn = g_norm[(head * 16 + quarter * 4 + (lane & 3)) * 3 + 0];
        const bool bad = !(kn < 1e30f) || !(vn < 1e9f) || !(qn < 1e30f);
#pragma unroll
        for (int o = 8; o > 0; o >>= 1) {
            kn = fmaxf(kn, __shfl_xor_sync(0xffffffffu, kn, o));
            qn = fmaxf(qn, __shfl_xor_sync(0xffffffffu, qn, o));
        }
        const bool ok = __all_sync(0xffffffffu, !bad && (qn * kn <= 9000.f));
        if (lane == 0) s_cnt[4] = ok ? 1u : 0u;
    }
    uint32_t qn2[2][4];
#pragma unroll
    for (int ps = 0; ps < 2; ps++) {
        const uint8_t* qb = g_q + (size_t)head * 65536 + (quarter * 512 + ps * 256 + wg * 64 + warp * 16 + g) * 16 + t * 4;
        qn2[ps][0] = *(const uint32_t*)(qb);
        qn2[ps][1] = *(const uint32_t*)(qb + 128);
        qn2[ps][2] = *(const uint32_t*)(qb + 32768);
        qn2[ps][3] = *(const uint32_t*)(qb + 32768 + 128);
    }

    __syncthreads();
    const bool fast = __all_sync(0xffffffffu, s_cnt[4] != 0u);
    if (tid == 32) {
        for (int c = 1; c < KF_NCH; c++) {
            mbar_expect_tx(kvbar + 8 * c, KF_CH_G);
            bulk_g2s(sb + c * KF_CH_S, kvsrc + c * KF_CH_G, KF_CH_G, kvbar + 8 * c);
        }
    }
    if (tid == 0) TSTAMP0(1, 8);
    const uint64_t dbias_a = make_desc(sb + KF_OFF_MISC + 1152, 0, 0, 0);
    const uint64_t dbias_b = make_desc(sb + KF_OFF_MISC + 1280, 128, 0, 0);
    const uint64_t dk0 = make_desc(sb, 4096, 128, 0);
    const uint64_t dv0 = make_desc(sb + 8192, 128, 4096, 0);

#pragma unroll 1
    for (int pass = 0; pass < 2; pass++) {
        const int row0 = quarter * 512 + pass * 256 + wg * 64 + warp * 16 + g;
        uint32_t qa[4];
#pragma unroll
        for (int i = 0; i < 4; i++) qa[i] = pass ? qn2[1][i] : qn2[0][i];
        float o[12];
#pragma unroll
        for (int i = 0; i < 12; i++) o[i] = 0.f;
        fence_regs(o);
#define KF_RELEASE_CHUNK(c)                                                                          \
        if (pass == 1 && (c) >= 1 && (c) <= 4) {                                                     \
            named_sync(4 + wg, 128);            \
            if ((tid & 127) == 0 && atomicAdd(&s_cnt[(c) - 1], 1u) == 3u) {                          \
                mbar_expect_tx(wbar + 8 * (3 + (c)), 16384);                                         \
                tma_load_3d(sb + ((c) - 1) * KF_CH_S, &tm_wo, 0, (3 + (c)) * 64, nt * 2, wbar + 8 * (3 + (c))); \
            }                                                                                        \
        }
        if (fast) {
#pragma unroll 1
            for (int c = 0; c < KF_NCH; c++) {
                const uint64_t dk = dk0 + (uint64_t)(c * (KF_CH_S >> 4));
                const uint64_t dv = dv0 + (uint64_t)(c * (KF_CH_S >> 4));
                float s0[32], s1[32], s2[32], s3[32];
                uint32_t p0[16], p1[16], p2[16], p3[16];
                mbar_wait(kvbar + 8 * c, 0);
                wg_wait<1>();
                wg_fence();
                wgmma_qk_n64(s0, qa[0], qa[1], qa[2], qa[3], dk);
                wgmma_bias_n40(s0, dbias_a, dbias_b);
                wg_commit();
                wg_wait<1>();
                KF_RELEASE_CHUNK(c);
                wg_fence();
                wgmma_qk_n64(s1, qa[0], qa[1], qa[2], qa[3], dk + 64);
                wgmma_bias_n40(s1, dbias_a, dbias_b);
                wg_commit();
                wg_wait<1>();
                fence_regs(s0);
                softmax_part<0, 16>(s0, p0);
                wg_fence();
                KF_PV(p0, 0);
                wg_commit();
                wg_wait<1>();
                fence_regs(s1);
                softmax_part<0, 8>(s1, p1);
                wg_wait<0>();
                wg_fence();
                wgmma_qk_n64(s2, qa[0], qa[1], qa[2], qa[3], dk + 128);
                wgmma_bias_n40(s2, dbias_a, dbias_b);
                wg_commit();
                softmax_part<8, 16>(s1, p1);
                wg_fence();
                KF_PV(p1, 64);
                wg_commit();
                wg_wait<1>();
                fence_regs(s2);
                softmax_part<0, 8>(s2, p2);
                wg_wait<0>();
                wg_fence();
                wgmma_qk_n64(s3, qa[0], qa[1], qa[2], qa[3], dk + 192);
                wgmma_bias_n40(s3, dbias_a, dbias_b);
                wg_commit();
                softmax_part<8, 16>(s2, p2);
                wg_fence();
                KF_PV(p2, 128);
                wg_commit();
                wg_wait<1>();
                fence_regs(s3);
                softmax_part<0, 16>(s3, p3);
                wg_fence();
                KF_PV(p3, 192);
                wg_commit();
            }
            wg_wait<0>();
            fence_regs(o);
        } else {
            float m0 = -INFINITY, m1 = -INFINITY;
#pragma unroll 1
            for (int b = 0; b < 32; b++) {
                const int c = b >> 2;
                const uint64_t dk = dk0 + (uint64_t)(c * (KF_CH_S >> 4) + (b & 3) * 64);
                const uint64_t dv = dv0 + (uint64_t)(c * (KF_CH_S >> 4) + (b & 3) * 64);
                float s[32];
                uint32_t p[16];
                mbar_wait(kvbar + 8 * c, 0);
                wg_fence();
                wgmma_qk_n64(s, qa[0], qa[1], qa[2], qa[3], dk);
                wg_commit();
                if ((b & 3) == 0) { KF_RELEASE_CHUNK(c); }
                wg_wait<0>();
                fence_regs(s);
                float x0 = s[0], x1 = s[2];
#pragma unroll
                for (int j = 0; j < 8; j++) {
                    x0 = fmaxf(x0, fmaxf(s[4 * j], s[4 * j + 1]));
                    x1 = fmaxf(x1, fmaxf(s[4 * j + 2], s[4 * j + 3]));
                }
                x0 = fmaxf(x0, __shfl_xor_sync(0xffffffffu, x0, 1));
                x0 = fmaxf(x0, __shfl_xor_sync(0xffffffffu, x0, 2));
                x1 = fmaxf(x1, __shfl_xor_sync(0xffffffffu, x1, 1));
                x1 = fmaxf(x1, __shfl_xor_sync(0xffffffffu, x1, 2));
                const float n0 = fmaxf(m0, x0), n1 = fmaxf(m1, x1);
                const float c0 = ex2f(m0 - n0), c1 = ex2f(m1 - n1);
                m0 = n0; m1 = n1;
#pragma unroll
                for (int j = 0; j < 3; j++) {
                    o[4 * j] *= c0; o[4 * j + 1] *= c0; o[4 * j + 2] *= c1; o[4 * j + 3] *= c1;
                }
#pragma unroll
                for (int j = 0; j < 8; j++) {
                    p[2 * j] = pack_bf16(ex2f(s[4 * j] - n0), ex2f(s[4 * j + 1] - n0));
                    p[2 * j + 1] = pack_bf16(ex2f(s[4 * j + 2] - n1), ex2f(s[4 * j + 3] - n1));
                }
                fence_regs(o);
                wg_fence();
                KF_PV(p, 0);
                wg_commit();
                wg_wait<0>();
                fence_regs(o);
            }
        }
        const float inv0 = 1.f / o[8], inv1 = 1.f / o[10];
        {
            uint32_t v0 = pack_bf16(o[0] * inv0, o[1] * inv0), v1 = pack_bf16(o[4] * inv0, o[5] * inv0);
            uint32_t v2 = pack_bf16(o[2] * inv1, o[3] * inv1), v3 = pack_bf16(o[6] * inv1, o[7] * inv1);
            const bool o1 = t & 1, o2 = t & 2;
            uint32_t s0 = o1 ? v0 : v1, s1 = o1 ? v2 : v3;
            s0 = __shfl_xor_sync(0xffffffffu, s0, 1); s1 = __shfl_xor_sync(0xffffffffu, s1, 1);
            uint32_t a0 = o1 ? s0 : v0, a1 = o1 ? v1 : s0, b0 = o1 ? s1 : v2, b1 = o1 ? v3 : s1;
            uint32_t x0 = o2 ? a0 : b0, x1 = o2 ? a1 : b1;
            x0 = __shfl_xor_sync(0xffffffffu, x0, 2); x1 = __shfl_xor_sync(0xffffffffu, x1, 2);
            uint4 r;
            r.x = o2 ? x0 : a0; r.y = o2 ? x1 : a1; r.z = o2 ? b0 : x0; r.w = o2 ? b1 : x1;
            *(uint4*)(g_o + (size_t)(row0 + (t >> 1) * 8) * DM + head * 16 + (t & 1) * 8) = r;
        }
        if (tid == 0) TSTAMP0(1, 4 + pass);
    }
    if ((tid >> 5) != 10) named_arrive(1, 512);
    named_sync(4 + wg, 128);
    if ((tid & 127) == 0) {
        asm volatile("fence.acq_rel.gpu;" ::: "memory");
        asm volatile("red.relaxed.gpu.global.add.u32 [%0], 1;" ::"l"(&g_oflag[(quarter * 8 + 4 + wg) * 32 + (head >> 2) * 4]) : "memory");
        asm volatile("red.relaxed.gpu.global.add.u32 [%0], 1;" ::"l"(&g_oflag[(quarter * 8 + wg) * 32 + (head >> 2) * 4]) : "memory");
    }
    if (tid == 0) TSTAMP0(1, 3);

    if (wg < 2) {
        const int wi = warp;
        const int r0 = mt * 64 + wi * 16 + g;
        const int cb = nt * 128 + wg * 64;
        uint32_t xr[16], wr[8];
#pragma unroll
        for (int j = 0; j < 8; j++) {
            xr[2 * j] = __ldg((const uint32_t*)(x + (size_t)r0 * DM + cb + 8 * j + 2 * t));
            xr[2 * j + 1] = __ldg((const uint32_t*)(x + (size_t)(r0 + 8) * DM + cb + 8 * j + 2 * t));
            wr[j] = __ldg((const uint32_t*)(w_r + cb + 8 * j + 2 * t));
        }
        float wsum = 0.f;
        {
            const uint4 a = __ldg((const uint4*)(w_r + lane * 16)), b = __ldg((const uint4*)(w_r + lane * 16 + 8));
            const uint32_t w[8] = {a.x, a.y, a.z, a.w, b.x, b.y, b.z, b.w};
#pragma unroll
            for (int i = 0; i < 8; i++) wsum += bf_lo(w[i]) + bf_hi(w[i]);
#pragma unroll
            for (int o = 16; o > 0; o >>= 1) wsum += __shfl_xor_sync(0xffffffffu, wsum, o);
        }
        float acc[32];
#pragma unroll
        for (int i = 0; i < 32; i++) acc[i] = 0.f;
        fence_regs(acc);
#pragma unroll 1
        for (int i = 0; i < 8; i++) {
            mbar_wait(obar + 8 * i, 0);
            const int kb = __shfl_sync(0xffffffffu, (int)s_order[i], 0);
            mbar_wait(wbar + 8 * kb, 0);
            const uint32_t wa = (kb < 4) ? (KF_OFF_WO + kb * 16384) : ((kb - 4) * KF_CH_S);
            const uint64_t da = make_desc(sb + (4 + (kb >> 1)) * KF_CH_S + (kb & 1) * 8192, 16, 1024, 1);
            const uint64_t db = make_desc(sb + wa + wg * 8192, 1024, 1024, 1);
            wg_fence();
#pragma unroll
            for (int k = 0; k < 4; k++) wgmma_k3_n64(acc, da + k * 2, db + k * 128, (i | k) != 0);
            wg_commit();
        }
        wg_wait<0>();
        fence_regs(acc);
        if (tid == 0) TSTAMP0(2, 2);
        float hv[32];
        uint32_t hp[16];
        float s0 = 0.f, s1 = 0.f, d0 = 0.f, d1 = 0.f;
#pragma unroll
        for (int j = 0; j < 8; j++) {
            const uint32_t a01 = pack_bf16(acc[4 * j], acc[4 * j + 1]), a23 = pack_bf16(acc[4 * j + 2], acc[4 * j + 3]);
            hp[2 * j] = pack_bf16(bf_lo(xr[2 * j]) + bf_lo(a01), bf_hi(xr[2 * j]) + bf_hi(a01));
            hp[2 * j + 1] = pack_bf16(bf_lo(xr[2 * j + 1]) + bf_lo(a23), bf_hi(xr[2 * j + 1]) + bf_hi(a23));
            hv[4 * j] = bf_lo(hp[2 * j]); hv[4 * j + 1] = bf_hi(hp[2 * j]);
            hv[4 * j + 2] = bf_lo(hp[2 * j + 1]); hv[4 * j + 3] = bf_hi(hp[2 * j + 1]);
            const float wl = bf_lo(wr[j]), wh = bf_hi(wr[j]);
            s0 += hv[4 * j] + hv[4 * j + 1];
            s1 += hv[4 * j + 2] + hv[4 * j + 3];
            d0 = fmaf(hv[4 * j], wl, fmaf(hv[4 * j + 1], wh, d0));
            d1 = fmaf(hv[4 * j + 2], wl, fmaf(hv[4 * j + 3], wh, d1));
        }
        float mu0 = s0 * (1.f / 16), mu1 = s1 * (1.f / 16);
        float q0 = 0.f, q1 = 0.f;
#pragma unroll
        for (int j = 0; j < 8; j++) {
            float a = hv[4 * j] - mu0, b = hv[4 * j + 1] - mu0, c = hv[4 * j + 2] - mu1, d = hv[4 * j + 3] - mu1;
            q0 = fmaf(a, a, fmaf(b, b, q0));
            q1 = fmaf(c, c, fmaf(d, d, q1));
        }
#pragma unroll
        for (int o = 1; o < 4; o <<= 1) {
            const float m0 = __shfl_xor_sync(0xffffffffu, mu0, o), m1 = __shfl_xor_sync(0xffffffffu, mu1, o);
            const float e0 = __shfl_xor_sync(0xffffffffu, q0, o), e1 = __shfl_xor_sync(0xffffffffu, q1, o);
            d0 += __shfl_xor_sync(0xffffffffu, d0, o);
            d1 += __shfl_xor_sync(0xffffffffu, d1, o);
            const float f0 = mu0 - m0, f1 = mu1 - m1;
            q0 = q0 + e0 + f0 * f0 * (8.f * o);
            q1 = q1 + e1 + f1 * f1 * (8.f * o);
            mu0 = 0.5f * (mu0 + m0); mu1 = 0.5f * (mu1 + m1);
        }
        float4* part = g_part + (size_t)mt * 512 + wi * 16 + g;
        if (t < 2) {
            float4* dst = part + (nt * 2 + wg) * 64 + t * 8;
            const float a = t ? mu1 : mu0, b = t ? q1 : q0, c = t ? d1 : d0;
            asm volatile("st.relaxed.gpu.global.v4.f32 [%0], {%1, %2, %3, %4};" ::"l"(dst), "f"(a), "f"(b), "f"(c), "f"(1.0f) : "memory");
        }
        if (tid == 0) TSTAMP0(2, 5);
        const uint32_t stg_off = KF_OFF_WO + (wi >> 1) * 16384 + wg * 8192 + (wi & 1) * 4096;
        const uint32_t stg_o = sb + stg_off, stg_h = stg_o + 2048;
        const int srow = (lane & 7) + ((lane >> 3) & 1) * 8;
        const int sj = lane >> 4;
        named_sync(4 + wg, 128);
#pragma unroll
        for (int j = 0; j < 8; j += 2) {
            const uint32_t off = srow * 128 + (((j + sj) ^ (srow & 7)) << 4);
            stmatrix_x4(stg_h + off, hp[2 * j], hp[2 * j + 1], hp[2 * j + 2], hp[2 * j + 3]);
        }
        __syncwarp();
#pragma unroll
        for (int i = 0; i < 4; i++) {
            const int row = i * 4 + (lane >> 3), ch = lane & 7;
            const uint4 vh = *(const uint4*)(sp + stg_off + 2048 + row * 128 + ((ch ^ (row & 7)) << 4));
            *(uint4*)(g_h + (size_t)(mt * 64 + wi * 16 + row) * DM + cb + ch * 8) = vh;
        }
        named_arrive(8, 288);
        if (tid == 0) TSTAMP0(2, 6);
        float mean[2], den[2], rr[2];
        {
            float4 v[4];
            int spins = 0;
            while (true) {
#pragma unroll
                for (int i = 0; i < 4; i++) {
                    const float4* p = part + (t + (i & 1) * 4) * 64 + (i >> 1) * 8;
                    asm volatile("ld.relaxed.gpu.global.v4.f32 {%0, %1, %2, %3}, [%4];" : "=f"(v[i].x), "=f"(v[i].y), "=f"(v[i].z), "=f"(v[i].w) : "l"(p) : "memory");
                }
                const bool ok = (v[0].w != 0.f) && (v[1].w != 0.f) && (v[2].w != 0.f) && (v[3].w != 0.f);
                if (__all_sync(0xffffffffu, ok) || ++spins > (1 << 22)) break;
            }
#pragma unroll
            for (int u = 0; u < 2; u++) {
                float mu = v[2 * u].x + v[2 * u + 1].x, m2 = v[2 * u].y + v[2 * u + 1].y, hw = v[2 * u].z + v[2 * u + 1].z;
#pragma unroll
                for (int o = 1; o < 4; o <<= 1) {
                    mu += __shfl_xor_sync(0xffffffffu, mu, o);
                    m2 += __shfl_xor_sync(0xffffffffu, m2, o);
                    hw += __shfl_xor_sync(0xffffffffu, hw, o);
                }
                mu *= 0.125f;
                const float da = v[2 * u].x - mu, db = v[2 * u + 1].x - mu;
                float dd = 64.f * (da * da + db * db);
#pragma unroll
                for (int o = 1; o < 4; o <<= 1) dd += __shfl_xor_sync(0xffffffffu, dd, o);
                m2 += dd;
                mean[u] = rbf(mu);
                den[u] = rbf(sqrtf(rbf(rbf(m2 * (1.f / DM)) + 1e-5f)));
                rr[u] = rbf((hw - mean[u] * wsum) / den[u]);
            }
        }
        if (tid == 0) TSTAMP0(2, 3);
        named_arrive(3, 512);
        if (nt == 0 && wg == 0) {
            float2* s_st = (float2*)(sp + KF_OFF_WO + 49152);
            if (t == 0) {
                s_key[wi * 16 + g] = make_key(rr[0], r0);
                s_key[wi * 16 + g + 8] = make_key(rr[1], r0 + 8);
                s_st[wi * 16 + g] = make_float2(mean[0], den[0]);
                s_st[wi * 16 + g + 8] = make_float2(mean[1], den[1]);
            }
            named_sync(4, 128);
            if (warp == 0) {
                uint32_t k1, k2;
                warp_top2(s_key[lane], s_key[lane + 32], k1, k2);
                if (lane < 2) {
                    const uint32_t k = lane ? k2 : k1;
                    const float2 st = s_st[key_token(k) & 63];
                    asm volatile("st.relaxed.gpu.global.v4.u32 [%0], {%1, %2, %3, %4};" ::"l"(g_cand + mt * 2 + lane), "r"(k),
                                 "r"(1u), "r"(__float_as_uint(st.x)), "r"(__float_as_uint(st.y)) : "memory");
                }
            }
        }
        const float i0 = 1.f / den[0], i1 = 1.f / den[1];
#pragma unroll
        for (int j = 0; j < 8; j += 2) {
            uint32_t ro[4];
#pragma unroll
            for (int u = 0; u < 2; u++) {
                const int jj = j + u;
                const float a = hv[4 * jj], b = hv[4 * jj + 1], c = hv[4 * jj + 2], d = hv[4 * jj + 3];
                const uint32_t u01 = pack_bf16(a - mean[0], b - mean[0]), u23 = pack_bf16(c - mean[1], d - mean[1]);
                const uint32_t n01 = pack_bf16(bf_lo(u01) * i0, bf_hi(u01) * i0), n23 = pack_bf16(bf_lo(u23) * i1, bf_hi(u23) * i1);
                ro[2 * u] = pack_bf16(a + bf_lo(n01), b + bf_hi(n01));
                ro[2 * u + 1] = pack_bf16(c + bf_lo(n23), d + bf_hi(n23));
            }
            const uint32_t off = srow * 128 + (((j + sj) ^ (srow & 7)) << 4);
            stmatrix_x4(stg_o + off, ro[0], ro[1], ro[2], ro[3]);
        }
        __syncwarp();
#pragma unroll
        for (int i = 0; i < 4; i++) {
            const int row = i * 4 + (lane >> 3), ch = lane & 7;
            const uint4 vo = *(const uint4*)(sp + stg_off + row * 128 + ((ch ^ (row & 7)) << 4));
            *(uint4*)(out + (size_t)(mt * 64 + wi * 16 + row) * DM + cb + ch * 8) = vo;
        }
        named_sync(4 + wg, 128);
        if ((tid & 127) == 0) red_release_add(&g_sflag[mt]);
        if (tid == 0) TSTAMP0(2, 4);
    } else {
        const bool worker = blockIdx.x < FF / 16;
        const bool downer = blockIdx.x >= 64;
        const int mtid = tid - 256, mwarp = mtid >> 5;
        const int c0 = (blockIdx.x - 64) * 8;
        float* s_x = (float*)(sp + KF_OFF_WO + 49152 + 8192);
        float* s_red = (float*)(sp + KF_OFF_WO + 49152 + 8192 + 4096);
        if (mwarp == 2) {
            named_sync(1, 512);
            uint32_t done = 0;
            int n = 0, spins = 0;
            while (done != 0xFFu && ++spins < (1 << 22)) {
                const bool rdy = lane < 8 && ld_acquire(&g_oflag[mt * 32 + lane * 4]) >= 4u;
                uint32_t todo = __ballot_sync(0xffffffffu, rdy) & ~done;
                done |= todo;
                if (todo && lane == 0) {
                    asm volatile("fence.proxy.async.global;" ::: "memory");
                    while (todo) {
                        const int kb = __ffs(todo) - 1;
                        todo &= todo - 1;
                        s_order[n] = kb;
                        mbar_expect_tx(obar + 8 * n, 8192);
                        tma_load_3d(sb + (4 + (kb >> 1)) * KF_CH_S + (kb & 1) * 8192, &tm_o, 0, mt * 64, kb, obar + 8 * n);
                        n++;
                    }
                }
                n = __shfl_sync(0xffffffffu, n, 0);
                if (done != 0xFFu) __nanosleep(POLL_NS);
            }
            if (lane == 0) TSTAMP0(2, 1);
            if (lane == 0 && worker) {
                mbar_expect_tx(gbar, 32768);
                for (int i = 0; i < 4; i++) {
                    tma_load_2d(sb + i * KF_CH_S + 16384, &tm_g, blockIdx.x * 16, i * 128, gbar);
                    tma_load_2d(sb + (4 + i) * KF_CH_S + 16384, &tm_u, blockIdx.x * 16, i * 128, gbar);
                }
            }
        }
        if (mwarp == 1) {
            named_sync(8, 288);
            if (lane == 0) {
                red_release_add(&g_hflag[mt]);
                if (downer) {
                    mbar_expect_tx(dbar, 7 * 4096);
                    for (int i = 0; i < 7; i++) tma_load_2d(sb + (4 + (i >> 2)) * KF_CH_S + (i & 3) * 4096, &tm_d, c0, i * 256, dbar);
                }
            }
            __syncwarp();
        }
        if (mtid == 0) TSTAMP0(3, 0);
        named_sync(3, 512);
        if (mwarp == 0) {
            uint4 ca, cb4;
            int spins = 0;
            while (true) {
                asm volatile("ld.relaxed.gpu.global.v4.u32 {%0, %1, %2, %3}, [%4];" : "=r"(ca.x), "=r"(ca.y), "=r"(ca.z), "=r"(ca.w) : "l"(g_cand + 2 * lane) : "memory");
                asm volatile("ld.relaxed.gpu.global.v4.u32 {%0, %1, %2, %3}, [%4];" : "=r"(cb4.x), "=r"(cb4.y), "=r"(cb4.z), "=r"(cb4.w) : "l"(g_cand + 2 * lane + 1) : "memory");
                const unsigned int hf = ld_acquire(&g_hflag[lane]);
                const bool ok = ca.y != 0 && cb4.y != 0 && hf >= 4u;
                if (__all_sync(0xffffffffu, ok) || ++spins > (1 << 22)) break;
            }
            uint32_t k1, k2;
            warp_top2(ca.x, cb4.x, k1, k2);
            if (ca.x == k1) s_sel[0] = ca;
            if (cb4.x == k1) s_sel[0] = cb4;
            if (ca.x == k2) s_sel[1] = ca;
            if (cb4.x == k2) s_sel[1] = cb4;
        }
        named_sync(2, 256);
        if (mtid == 0) TSTAMP0(3, 1);
        int idx[2];
        float mean[2], inv[2], rv[2];
#pragma unroll
        for (int u = 0; u < 2; u++) {
            const uint4 c = s_sel[u];
            idx[u] = key_token(c.x);
            rv[u] = key_value(c.x);
            mean[u] = __uint_as_float(c.z);
            inv[u] = 1.f / __uint_as_float(c.w);
        }
        float hfin = 0.f;
        if (downer && mtid < 16) hfin = __bfloat162float(__ldcg((const __nv_bfloat16*)(g_h + (size_t)((mtid >> 3) ? idx[1] : idx[0]) * DM + c0 + (mtid & 7))));
        if (worker) {
            {
                const uint32_t h0 = __ldcg((const uint32_t*)(g_h + (size_t)idx[0] * DM + 2 * mtid));
                const uint32_t h1 = __ldcg((const uint32_t*)(g_h + (size_t)idx[1] * DM + 2 * mtid));
                const uint32_t u0 = pack_bf16(bf_lo(h0) - mean[0], bf_hi(h0) - mean[0]), u1 = pack_bf16(bf_lo(h1) - mean[1], bf_hi(h1) - mean[1]);
                const uint32_t n0 = pack_bf16(bf_lo(u0) * inv[0], bf_hi(u0) * inv[0]), n1 = pack_bf16(bf_lo(u1) * inv[1], bf_hi(u1) * inv[1]);
                *(float4*)(s_x + 4 * mtid) = make_float4(bf_lo(n0), bf_lo(n1), bf_hi(n0), bf_hi(n1));
            }
            if (mtid == 0) TSTAMP0(3, 5);
            mbar_wait(gbar, 0);
            named_sync(2, 256);
            if (mtid == 0) TSTAMP0(3, 6);
            float acc[8];
#pragma unroll
            for (int i = 0; i < 8; i++) acc[i] = 0.f;
            const uint8_t* wbase = sp + (mwarp >> 2) * (4 * KF_CH_S) + 16384 + lane * 32 + (mwarp & 3) * 8;
#pragma unroll
            for (int k = 0; k < 16; k++) {
                const uint2 w = *(const uint2*)(wbase + (k >> 2) * KF_CH_S + (k & 3) * 1024);
                const float2 xx = *(const float2*)(s_x + 2 * (lane + 32 * k));
                const float x0 = xx.x, x1 = xx.y;
                const float w0 = bf_lo(w.x), w1 = bf_hi(w.x), w2 = bf_lo(w.y), w3 = bf_hi(w.y);
                acc[0] = fmaf(x0, w0, acc[0]); acc[1] = fmaf(x0, w1, acc[1]); acc[2] = fmaf(x0, w2, acc[2]); acc[3] = fmaf(x0, w3, acc[3]);
                acc[4] = fmaf(x1, w0, acc[4]); acc[5] = fmaf(x1, w1, acc[5]); acc[6] = fmaf(x1, w2, acc[6]); acc[7] = fmaf(x1, w3, acc[7]);
            }
#define KF_STEP(O, N)                                                          \
            {                                                                  \
                const bool up = (lane & (O)) != 0;                             \
                _Pragma("unroll") for (int i = 0; i < (N); i++) {              \
                    const float send = up ? acc[i] : acc[i + (N)];             \
                    const float keep = up ? acc[i + (N)] : acc[i];             \
                    acc[i] = keep + __shfl_xor_sync(0xffffffffu, send, (O));   \
                }                                                              \
            }
            KF_STEP(16, 4) KF_STEP(8, 2) KF_STEP(4, 1)
            acc[0] += __shfl_xor_sync(0xffffffffu, acc[0], 2);
            acc[0] += __shfl_xor_sync(0xffffffffu, acc[0], 1);
            if ((lane & 3) == 0) {
                const int v = ((lane & 16) ? 4 : 0) + ((lane & 8) ? 2 : 0) + ((lane & 4) ? 1 : 0);
                s_gu[(v >> 2) * 32 + mwarp * 4 + (v & 3)] = acc[0];
            }
            named_sync(2, 256);
            if (mtid < 16) {
                uint32_t a2 = 0;
#pragma unroll
                for (int u = 0; u < 2; u++) {
                    const float gb = rbf(s_gu[u * 32 + mtid]);
                    const float sg = rbf(gb / (1.f + __expf(-gb)));
                    float a = sg * rbf(s_gu[u * 32 + 16 + mtid]);
                    uint32_t ab = (uint32_t)__bfloat16_as_ushort(__float2bfloat16_rn(a));
                    if (ab == 0xFFFFu) ab = 0x7FFFu;
                    a2 |= ab << (16 * u);
                }
                asm volatile("st.relaxed.gpu.global.u32 [%0], %1;" ::"l"(g_act + blockIdx.x * 16 + mtid), "r"(a2) : "memory");
            }
            if (mtid == 0) TSTAMP0(3, 2);
        }
        if (downer) {
            uint32_t av[7];
            {
                int spins = 0;
                while (true) {
                    bool ok = true;
#pragma unroll
                    for (int j = 0; j < 7; j++) {
                        asm volatile("ld.relaxed.gpu.global.u32 %0, [%1];" : "=r"(av[j]) : "l"(g_act + mtid + 256 * j) : "memory");
                        ok = ok && ((av[j] & 0xFFFFu) != 0xFFFFu) && ((av[j] >> 16) != 0xFFFFu);
                    }
                    if (mtid < 2) ok = ok && (ld_acquire(&g_sflag[(mtid ? idx[1] : idx[0]) >> 6]) >= 8u);
                    if (__all_sync(0xffffffffu, ok) || ++spins > (1 << 20)) break;
                    __nanosleep(20);
                }
            }
            if (mtid == 0) TSTAMP0(3, 3);
            mbar_wait(dbar, 0);
            float acc[16];
#pragma unroll
            for (int i = 0; i < 16; i++) acc[i] = 0.f;
#pragma unroll
            for (int j = 0; j < 7; j++) {
                const uint4 w = *(const uint4*)(sp + (4 + (j >> 2)) * KF_CH_S + (j & 3) * 4096 + mtid * 16);
                const float a0 = bf_lo(av[j]), a1 = bf_hi(av[j]);
                const uint32_t ww[4] = {w.x, w.y, w.z, w.w};
#pragma unroll
                for (int q = 0; q < 4; q++) {
                    const float wl = bf_lo(ww[q]), wh = bf_hi(ww[q]);
                    acc[2 * q] = fmaf(a0, wl, acc[2 * q]); acc[2 * q + 1] = fmaf(a0, wh, acc[2 * q + 1]);
                    acc[8 + 2 * q] = fmaf(a1, wl, acc[8 + 2 * q]); acc[8 + 2 * q + 1] = fmaf(a1, wh, acc[8 + 2 * q + 1]);
                }
            }
            KF_STEP(16, 8) KF_STEP(8, 4) KF_STEP(4, 2) KF_STEP(2, 1)
            acc[0] += __shfl_xor_sync(0xffffffffu, acc[0], 1);
            if ((lane & 1) == 0) {
                const int v = ((lane & 16) ? 8 : 0) + ((lane & 8) ? 4 : 0) + ((lane & 4) ? 2 : 0) + ((lane & 2) ? 1 : 0);
                s_red[mwarp * 16 + v] = acc[0];
            }
            named_sync(2, 256);
            if (mtid < 16) {
                const int u = mtid >> 3;
                float y = 0.f;
#pragma unroll
                for (int w = 0; w < 8; w++) y += s_red[w * 16 + mtid];
                const float sig = rbf(1.f / (1.f + __expf(-(u ? rv[1] : rv[0]))));
                const float xn = rbf(rbf(hfin - (u ? mean[1] : mean[0])) * (u ? inv[1] : inv[0]));
                const float ov = hfin + rbf(xn + rbf(rbf(y) * sig));
                out[(size_t)(u ? idx[1] : idx[0]) * DM + c0 + (mtid & 7)] = __float2bfloat16_rn(ov);
            }
            if (blockIdx.x == gridDim.x - 1 && mtid == 0) g_epoch = g_epoch + 1u;
            if (mtid == 0) TSTAMP0(3, 4);
        }
    }
}

typedef CUresult (*PFN_encodeTiled)(CUtensorMap*, CUtensorMapDataType, cuuint32_t, void*, const cuuint64_t*, const cuuint64_t*,
                                    const cuuint32_t*, const cuuint32_t*, CUtensorMapInterleave, CUtensorMapSwizzle,
                                    CUtensorMapL2promotion, CUtensorMapFloatOOBfill);

void make_map(PFN_encodeTiled enc, CUtensorMap* m, const void* ptr, uint64_t cols, uint64_t rows, uint32_t bcols, uint32_t brows) {
    cuuint64_t dims[2] = {cols, rows};
    cuuint64_t strides[1] = {cols * 2};
    cuuint32_t box[2] = {bcols, brows};
    cuuint32_t es[2] = {1, 1};
    enc(m, CU_TENSOR_MAP_DATA_TYPE_BFLOAT16, 2, const_cast<void*>(ptr), dims, strides, box, es, CU_TENSOR_MAP_INTERLEAVE_NONE,
        CU_TENSOR_MAP_SWIZZLE_128B, CU_TENSOR_MAP_L2_PROMOTION_L2_256B, CU_TENSOR_MAP_FLOAT_OOB_FILL_NONE);
}

void make_map3(PFN_encodeTiled enc, CUtensorMap* m, const void* ptr, uint64_t d0, uint64_t rows, uint64_t d2, uint64_t row_stride_bytes,
               uint64_t d2_stride_bytes, uint32_t b0, uint32_t b1, uint32_t b2) {
    cuuint64_t dims[3] = {d0, rows, d2};
    cuuint64_t strides[2] = {row_stride_bytes, d2_stride_bytes};
    cuuint32_t box[3] = {b0, b1, b2};
    cuuint32_t es[3] = {1, 1, 1};
    enc(m, CU_TENSOR_MAP_DATA_TYPE_BFLOAT16, 3, const_cast<void*>(ptr), dims, strides, box, es, CU_TENSOR_MAP_INTERLEAVE_NONE,
        CU_TENSOR_MAP_SWIZZLE_128B, CU_TENSOR_MAP_L2_PROMOTION_L2_256B, CU_TENSOR_MAP_FLOAT_OOB_FILL_NONE);
}

void make_map_plain(PFN_encodeTiled enc, CUtensorMap* m, const void* ptr, uint64_t cols, uint64_t rows, uint32_t bcols, uint32_t brows) {
    cuuint64_t dims[2] = {cols, rows};
    cuuint64_t strides[1] = {cols * 2};
    cuuint32_t box[2] = {bcols, brows};
    cuuint32_t es[2] = {1, 1};
    enc(m, CU_TENSOR_MAP_DATA_TYPE_BFLOAT16, 2, const_cast<void*>(ptr), dims, strides, box, es, CU_TENSOR_MAP_INTERLEAVE_NONE,
        CU_TENSOR_MAP_SWIZZLE_NONE, CU_TENSOR_MAP_L2_PROMOTION_NONE, CU_TENSOR_MAP_FLOAT_OOB_FILL_NONE);
}

template <typename... KArgs, typename... Args>
void launch(void (*kern)(KArgs...), int grid, int block, int smem, bool pdl, Args... args) {
    cudaLaunchConfig_t cfg = {};
    cfg.gridDim = dim3(grid);
    cfg.blockDim = dim3(block);
    cfg.dynamicSmemBytes = smem;
    cfg.stream = cudaStreamPerThread;
    cudaLaunchAttribute at[1];
    at[0].id = cudaLaunchAttributeProgrammaticStreamSerialization;
    at[0].val.programmaticStreamSerializationAllowed = 1;
    cfg.attrs = at;
    cfg.numAttrs = pdl ? 1 : 0;
    cudaLaunchKernelEx(&cfg, kern, KArgs(args)...);
}

}

extern "C" void kernel_launch(void* const* d_in, const int* in_sizes, int n_in, void* d_out, int out_size) {
    const __nv_bfloat16* x = (const __nv_bfloat16*)d_in[0];
    const __nv_bfloat16* wqkv = (const __nv_bfloat16*)d_in[1];
    const __nv_bfloat16* wo = (const __nv_bfloat16*)d_in[2];
    const __nv_bfloat16* w_r = (const __nv_bfloat16*)d_in[4];
    const __nv_bfloat16* w_gate = (const __nv_bfloat16*)d_in[5];
    const __nv_bfloat16* w_up = (const __nv_bfloat16*)d_in[6];
    const __nv_bfloat16* w_down = (const __nv_bfloat16*)d_in[7];
    __nv_bfloat16* out = (__nv_bfloat16*)d_out;

    static PFN_encodeTiled enc = nullptr;
    static void* g_o_ptr = nullptr;
    if (!enc) {
        cudaDriverEntryPointQueryResult qres;
        void* fn = nullptr;
        cudaGetDriverEntryPoint("cuTensorMapEncodeTiled", &fn, cudaEnableDefault, &qres);
        enc = (PFN_encodeTiled)fn;
        cudaGetSymbolAddress(&g_o_ptr, g_o);
        cudaFuncSetAttribute(k1_qkv, cudaFuncAttributeMaxDynamicSharedMemorySize, K1_SMEM);
        cudaFuncSetAttribute(kf_main, cudaFuncAttributeMaxDynamicSharedMemorySize, KF_SMEM);
    }
    CUtensorMap tm_x, tm_w, tm_o, tm_wo, tm_g, tm_u, tm_d;
    make_map_plain(enc, &tm_d, w_down, DM, FF, 8, 256);
    make_map_plain(enc, &tm_g, w_gate, FF, DM, 16, 128);
    make_map_plain(enc, &tm_u, w_up, FF, DM, 16, 128);
    make_map(enc, &tm_x, x, DM, SEQ, 64, 128);
    make_map3(enc, &tm_w, wqkv, DM, DM, 3, 3 * DM * 2, DM * 2, 64, 64, 3);
    make_map3(enc, &tm_o, g_o_ptr, 64, SEQ, 8, DM * 2, 128, 64, 64, 1);
    make_map3(enc, &tm_wo, wo, 64, DM, 8, DM * 2, 128, 64, 64, 2);

    const bool pdl = true;
    launch(k1_qkv, 128, 544, K1_SMEM, false, tm_x, tm_w, x);
    launch(kf_main, 128, 512, KF_SMEM, pdl, tm_o, tm_wo, tm_g, tm_u, tm_d, x, wo, w_r, w_gate, w_up, w_down, out);
}
```

```cpp
#include <cuda_runtime.h>
#include <cuda_bf16.h>
#include <cuda.h>
#include <stdint.h>

namespace {

constexpr int SEQ = 2048, DM = 512, NH = 32, FF = 1792;

__device__ __align__(1024) uint8_t g_q[NH * 2 * SEQ * 16];
__device__ __align__(1024) uint8_t g_kv[NH * 8 * 16384];
__device__ float g_norm[16 * NH * 3];
__device__ __align__(1024) __nv_bfloat16 g_o[SEQ * DM];
__device__ __align__(1024) __nv_bfloat16 g_h[SEQ * DM];
__device__ __align__(16) uint4 g_cand[64];
__device__ unsigned int g_oflag[32 * 32];
__device__ unsigned int g_hflag[32];
__device__ unsigned int g_sflag[32];
__device__ unsigned int g_act[FF];
__device__ unsigned int g_epoch;
__device__ __align__(16) float4 g_ln1[SEQ];
__device__ __align__(16) float4 g_part[32 * 8 * 64];

#define TSTAMP(K, I)
#define TSTAMP0(K, I)
__device__ __forceinline__ uint32_t smem_u32(const void* p) { return (uint32_t)__cvta_generic_to_shared(p); }
__device__ __forceinline__ void wg_fence() { asm volatile("wgmma.fence.sync.aligned;" ::: "memory"); }
__device__ __forceinline__ void wg_commit() { asm volatile("wgmma.commit_group.sync.aligned;" ::: "memory"); }
template <int N> __device__ __forceinline__ void wg_wait() { asm volatile("wgmma.wait_group.sync.aligned %0;" ::"n"(N) : "memory"); }
template <int N> __device__ __forceinline__ void fence_regs(float (&r)[N]) {
#pragma unroll
    for (int i = 0; i < N; i++) asm volatile("" : "+f"(r[i])::"memory");
}
__device__ __forceinline__ uint64_t make_desc(uint32_t addr, uint32_t lbo, uint32_t sbo, uint32_t swz) {
    uint64_t d = 0;
    d |= (uint64_t)((addr & 0x3FFFF) >> 4);
    d |= (uint64_t)((lbo & 0x3FFFF) >> 4) << 16;
    d |= (uint64_t)((sbo & 0x3FFFF) >> 4) << 32;
    d |= (uint64_t)swz << 62;
    return d;
}
__device__ __forceinline__ void mbar_init(uint32_t bar, uint32_t cnt) {
    asm volatile("mbarrier.init.shared::cta.b64 [%0], %1;" ::"r"(bar), "r"(cnt) : "memory");
}
__device__ __forceinline__ void mbar_expect_tx(uint32_t bar, uint32_t bytes) {
    asm volatile("mbarrier.arrive.expect_tx.shared::cta.b64 _, [%0], %1;" ::"r"(bar), "r"(bytes) : "memory");
}
__device__ __forceinline__ void mbar_arrive(uint32_t bar) {
    asm volatile("mbarrier.arrive.shared::cta.b64 _, [%0];" ::"r"(bar) : "memory");
}
__device__ __forceinline__ void mbar_wait(uint32_t bar, uint32_t parity) {
    asm volatile(
        "{\n.reg .pred p;\nWAIT_%=:\n"
        "mbarrier.try_wait.parity.shared::cta.b64 p, [%0], %1;\n"
        "@p bra DONE_%=;\nbra WAIT_%=;\nDONE_%=:\n}\n" ::"r"(bar), "r"(parity) : "memory");
}
__device__ __forceinline__ void bulk_g2s(uint32_t dst, const void* src, uint32_t bytes, uint32_t bar) {
    asm volatile("cp.async.bulk.shared::cluster.global.mbarrier::complete_tx::bytes [%0], [%1], %2, [%3];" ::"r"(dst),
                 "l"(src), "r"(bytes), "r"(bar) : "memory");
}
__device__ __forceinline__ void bulk_s2g(void* dst, uint32_t src, uint32_t bytes) {
    asm volatile("cp.async.bulk.global.shared::cta.bulk_group [%0], [%1], %2;" ::"l"(dst), "r"(src), "r"(bytes) : "memory");
}
__device__ __forceinline__ void tma_load_2d(uint32_t dst, const CUtensorMap* tm, int c0, int c1, uint32_t bar) {
    asm volatile("cp.async.bulk.tensor.2d.shared::cluster.global.mbarrier::complete_tx::bytes [%0], [%1, {%3, %4}], [%2];" ::"r"(dst),
                 "l"(tm), "r"(bar), "r"(c0), "r"(c1) : "memory");
}
__device__ __forceinline__ void tma_load_3d(uint32_t dst, const CUtensorMap* tm, int c0, int c1, int c2, uint32_t bar) {
    asm volatile("cp.async.bulk.tensor.3d.shared::cluster.global.mbarrier::complete_tx::bytes [%0], [%1, {%3, %4, %5}], [%2];" ::"r"(dst),
                 "l"(tm), "r"(bar), "r"(c0), "r"(c1), "r"(c2) : "memory");
}
__device__ __forceinline__ void tma_load_2d_mc(uint32_t dst, const CUtensorMap* tm, int c0, int c1, uint32_t bar, uint16_t mask) {
    asm volatile("cp.async.bulk.tensor.2d.shared::cluster.global.mbarrier::complete_tx::bytes.multicast::cluster [%0], [%1, {%3, %4}], [%2], %5;" ::"r"(dst),
                 "l"(tm), "r"(bar), "r"(c0), "r"(c1), "h"(mask) : "memory");
}
__device__ __forceinline__ void mbar_arrive_cluster(uint32_t bar, uint32_t cta) {
    asm volatile("{\n.reg .b32 ra;\nmapa.shared::cluster.u32 ra, %0, %1;\nmbarrier.arrive.release.cluster.shared::cluster.b64 _, [ra];\n}" ::"r"(bar), "r"(cta) : "memory");
}
__device__ __forceinline__ void cluster_sync() {
    asm volatile("barrier.cluster.arrive.release.aligned;\nbarrier.cluster.wait.acquire.aligned;" ::: "memory");
}
__device__ __forceinline__ void prefetch_l2(const void* p, uint32_t bytes) {
    asm volatile("cp.async.bulk.prefetch.L2.global [%0], %1;" ::"l"(p), "r"(bytes) : "memory");
}
__device__ __forceinline__ void fence_proxy_async() { asm volatile("fence.proxy.async.shared::cta;" ::: "memory"); }
__device__ __forceinline__ void fence_barrier_init() { asm volatile("fence.mbarrier_init.release.cluster;" ::: "memory"); }
__device__ __forceinline__ void pdl_launch() { asm volatile("griddepcontrol.launch_dependents;" ::: "memory"); }
__device__ __forceinline__ void pdl_wait() { asm volatile("griddepcontrol.wait;" ::: "memory"); }
__device__ __forceinline__ void named_sync(int id, int n) { asm volatile("bar.sync %0, %1;" ::"r"(id), "r"(n) : "memory"); }
__device__ __forceinline__ void named_arrive(int id, int n) { asm volatile("bar.arrive %0, %1;" ::"r"(id), "r"(n) : "memory"); }

__device__ __forceinline__ float ex2f(float x) { float y; asm("ex2.approx.ftz.f32 %0, %1;" : "=f"(y) : "f"(x)); return y; }
__device__ __forceinline__ uint32_t pack_bf16(float lo, float hi) {
    uint32_t r; asm("cvt.rn.bf16x2.f32 %0, %1, %2;" : "=r"(r) : "f"(hi), "f"(lo)); return r;
}
__device__ __forceinline__ float bf_lo(uint32_t v) { return __uint_as_float(v << 16); }
__device__ __forceinline__ float bf_hi(uint32_t v) { return __uint_as_float(v & 0xFFFF0000u); }
__device__ __forceinline__ float rbf(float x) { return __bfloat162float(__float2bfloat16_rn(x)); }
__device__ __forceinline__ uint32_t fma_bf16x2(uint32_t a, uint32_t b, uint32_t c) {
    uint32_t r; asm("fma.rn.bf16x2 %0, %1, %2, %3;" : "=r"(r) : "r"(a), "r"(b), "r"(c)); return r;
}
__device__ __forceinline__ void stmatrix_x4(uint32_t addr, uint32_t r0, uint32_t r1, uint32_t r2, uint32_t r3) {
    asm volatile("stmatrix.sync.aligned.m8n8.x4.shared.b16 [%0], {%1, %2, %3, %4};" ::"r"(addr), "r"(r0), "r"(r1), "r"(r2), "r"(r3) : "memory");
}
__device__ __forceinline__ void stmatrix_x4_trans(uint32_t addr, uint32_t r0, uint32_t r1, uint32_t r2, uint32_t r3) {
    asm volatile("stmatrix.sync.aligned.m8n8.x4.trans.shared.b16 [%0], {%1, %2, %3, %4};" ::"r"(addr), "r"(r0), "r"(r1), "r"(r2), "r"(r3) : "memory");
}

__device__ __forceinline__ void wgmma_k1_n136(float (&d)[68], uint64_t desca, uint64_t descb, int scale_d) {
  asm volatile("{\n.reg .pred p;\nsetp.ne.b32 p, %70, 0;\n"
    "wgmma.mma_async.sync.aligned.m64n136k16.f32.bf16.bf16 "
    "{%0, %1, %2, %3, %4, %5, %6, %7, %8, %9, %10, %11, %12, %13, %14, %15, %16, %17, %18, %19, %20, %21, %22, %23, %24, %25, %26, %27, %28, %29, %30, %31, %32, %33, %34, %35, %36, %37, %38, %39, %40, %41, %42, %43, %44, %45, %46, %47, %48, %49, %50, %51, %52, %53, %54, %55, %56, %57, %58, %59, %60, %61, %62, %63, %64, %65, %66, %67}, "
    "%68, %69, p, 1, 1, 1, 0;\n}\n"
    : "+f"(d[0]), "+f"(d[1]), "+f"(d[2]), "+f"(d[3]), "+f"(d[4]), "+f"(d[5]), "+f"(d[6]), "+f"(d[7]), "+f"(d[8]), "+f"(d[9]), "+f"(d[10]), "+f"(d[11]), "+f"(d[12]), "+f"(d[13]), "+f"(d[14]), "+f"(d[15]), "+f"(d[16]), "+f"(d[17]), "+f"(d[18]), "+f"(d[19]), "+f"(d[20]), "+f"(d[21]), "+f"(d[22]), "+f"(d[23]), "+f"(d[24]), "+f"(d[25]), "+f"(d[26]), "+f"(d[27]), "+f"(d[28]), "+f"(d[29]), "+f"(d[30]), "+f"(d[31]), "+f"(d[32]), "+f"(d[33]), "+f"(d[34]), "+f"(d[35]), "+f"(d[36]), "+f"(d[37]), "+f"(d[38]), "+f"(d[39]), "+f"(d[40]), "+f"(d[41]), "+f"(d[42]), "+f"(d[43]), "+f"(d[44]), "+f"(d[45]), "+f"(d[46]), "+f"(d[47]), "+f"(d[48]), "+f"(d[49]), "+f"(d[50]), "+f"(d[51]), "+f"(d[52]), "+f"(d[53]), "+f"(d[54]), "+f"(d[55]), "+f"(d[56]), "+f"(d[57]), "+f"(d[58]), "+f"(d[59]), "+f"(d[60]), "+f"(d[61]), "+f"(d[62]), "+f"(d[63]), "+f"(d[64]), "+f"(d[65]), "+f"(d[66]), "+f"(d[67])
    : "l"(desca), "l"(descb), "r"(scale_d));
}
__device__ __forceinline__ void wgmma_qk_n64(float (&d)[32], uint32_t a0, uint32_t a1, uint32_t a2, uint32_t a3, uint64_t descb) {
  asm volatile("{\n.reg .pred p;\nsetp.ne.b32 p, 0, 0;\n"
    "wgmma.mma_async.sync.aligned.m64n64k16.f32.bf16.bf16 "
    "{%0, %1, %2, %3, %4, %5, %6, %7, %8, %9, %10, %11, %12, %13, %14, %15, %16, %17, %18, %19, %20, %21, %22, %23, %24, %25, %26, %27, %28, %29, %30, %31}, "
    "{%32, %33, %34, %35}, %36, p, 1, 1, 0;\n}\n"
    : "=f"(d[0]), "=f"(d[1]), "=f"(d[2]), "=f"(d[3]), "=f"(d[4]), "=f"(d[5]), "=f"(d[6]), "=f"(d[7]), "=f"(d[8]), "=f"(d[9]), "=f"(d[10]), "=f"(d[11]), "=f"(d[12]), "=f"(d[13]), "=f"(d[14]), "=f"(d[15]), "=f"(d[16]), "=f"(d[17]), "=f"(d[18]), "=f"(d[19]), "=f"(d[20]), "=f"(d[21]), "=f"(d[22]), "=f"(d[23]), "=f"(d[24]), "=f"(d[25]), "=f"(d[26]), "=f"(d[27]), "=f"(d[28]), "=f"(d[29]), "=f"(d[30]), "=f"(d[31])
    : "r"(a0), "r"(a1), "r"(a2), "r"(a3), "l"(descb));
}
__device__ __forceinline__ void wgmma_pv_n24(float (&d)[12], uint32_t a0, uint32_t a1, uint32_t a2, uint32_t a3, uint64_t descb) {
  asm volatile("{\n.reg .pred p;\nsetp.eq.b32 p, 0, 0;\n"
    "wgmma.mma_async.sync.aligned.m64n24k16.f32.bf16.bf16 "
    "{%0, %1, %2, %3, %4, %5, %6, %7, %8, %9, %10, %11}, "
    "{%12, %13, %14, %15}, %16, p, 1, 1, 1;\n}\n"
    : "+f"(d[0]), "+f"(d[1]), "+f"(d[2]), "+f"(d[3]), "+f"(d[4]), "+f"(d[5]), "+f"(d[6]), "+f"(d[7]), "+f"(d[8]), "+f"(d[9]), "+f"(d[10]), "+f"(d[11])
    : "r"(a0), "r"(a1), "r"(a2), "r"(a3), "l"(descb));
}
__device__ __forceinline__ void wgmma_k3_n64(float (&d)[32], uint64_t desca, uint64_t descb, int scale_d) {
  asm volatile("{\n.reg .pred p;\nsetp.ne.b32 p, %34, 0;\n"
    "wgmma.mma_async.sync.aligned.m64n64k16.f32.bf16.bf16 "
    "{%0, %1, %2, %3, %4, %5, %6, %7, %8, %9, %10, %11, %12, %13, %14, %15, %16, %17, %18, %19, %20, %21, %22, %23, %24, %25, %26, %27, %28, %29, %30, %31}, "
    "%32, %33, p, 1, 1, 0, 1;\n}\n"
    : "+f"(d[0]), "+f"(d[1]), "+f"(d[2]), "+f"(d[3]), "+f"(d[4]), "+f"(d[5]), "+f"(d[6]), "+f"(d[7]), "+f"(d[8]), "+f"(d[9]), "+f"(d[10]), "+f"(d[11]), "+f"(d[12]), "+f"(d[13]), "+f"(d[14]), "+f"(d[15]), "+f"(d[16]), "+f"(d[17]), "+f"(d[18]), "+f"(d[19]), "+f"(d[20]), "+f"(d[21]), "+f"(d[22]), "+f"(d[23]), "+f"(d[24]), "+f"(d[25]), "+f"(d[26]), "+f"(d[27]), "+f"(d[28]), "+f"(d[29]), "+f"(d[30]), "+f"(d[31])
    : "l"(desca), "l"(descb), "r"(scale_d));
}
__device__ __forceinline__ void wgmma_bias_n40(float (&d)[32], uint64_t desca, uint64_t descb) {
  asm volatile("{\n.reg .pred p;\nsetp.eq.b32 p, 0, 0;\n"
    "wgmma.mma_async.sync.aligned.m64n40k16.f32.bf16.bf16 "
    "{%0, %1, %2, %3, %4, %5, %6, %7, %8, %9, %10, %11, %12, %13, %14, %15, %16, %17, %18, %19}, "
    "%20, %21, p, 1, 1, 0, 0;\n}\n"
    : "+f"(d[0]), "+f"(d[1]), "+f"(d[2]), "+f"(d[3]), "+f"(d[4]), "+f"(d[5]), "+f"(d[6]), "+f"(d[7]), "+f"(d[8]), "+f"(d[9]), "+f"(d[10]), "+f"(d[11]), "+f"(d[12]), "+f"(d[13]), "+f"(d[14]), "+f"(d[15]), "+f"(d[16]), "+f"(d[17]), "+f"(d[18]), "+f"(d[19])
    : "l"(desca), "l"(descb));
}

constexpr int K1_XS = 17408;
constexpr int K1_WS = 24576;
constexpr int K1_ST = K1_XS + K1_WS;
constexpr int K1_NST = 5;
constexpr int K1_OFF_MISC = K1_NST * K1_ST;
constexpr int K1_SMEM = K1_OFF_MISC + 2048 + 1024;
constexpr float QSCALE = 0.25f * 1.4426950408889634f;

__global__ void __launch_bounds__(544, 1)
k1_qkv(const __grid_constant__ CUtensorMap tm_x, const __grid_constant__ CUtensorMap tm_w, const __nv_bfloat16* __restrict__ x) {
    extern __shared__ uint8_t smem_raw[];
    const uint32_t sraw = smem_u32(smem_raw);
    const uint32_t sb = (sraw + 1023) & ~1023u;
    uint8_t* sp = smem_raw + (sb - sraw);
    const uint32_t full = sb + K1_OFF_MISC;
    const uint32_t empty = full + 64;
    float* s_mr = (float*)(sp + K1_OFF_MISC + 256);

    const int tid = threadIdx.x, warp = tid >> 5, lane = tid & 31;
    const int mt = blockIdx.x >> 3, nt = blockIdx.x & 7;
    if (tid == 0) TSTAMP0(0, 0);
    pdl_launch();
    if (tid == 512) {
        for (int i = 0; i < K1_NST; i++) { mbar_init(full + 8 * i, 1); mbar_init(empty + 8 * i, 3); }
        fence_barrier_init();
        for (int kb = 0; kb < K1_NST; kb++) {
            mbar_expect_tx(full + 8 * kb, 16384 + K1_WS);
            tma_load_2d(sb + kb * K1_ST, &tm_x, kb * 64, mt * 128, full + 8 * kb);
            tma_load_3d(sb + kb * K1_ST + K1_XS, &tm_w, nt * 64, kb * 64, 0, full + 8 * kb);
        }
    }
    if (tid < K1_NST * 64) {
        *(uint4*)(sp + (tid >> 6) * K1_ST + 16384 + (tid & 63) * 16) =
            make_uint4(0x3F803F80u, 0x3F803F80u, 0x3F803F80u, 0x3F803F80u);
    }
    fence_proxy_async();
    __syncthreads();

    if (warp == 16) {
        if (lane == 0) {
            for (int kb = K1_NST; kb < 8; kb++) {
                const int s = kb % K1_NST;
                mbar_wait(empty + 8 * s, 0);
                mbar_expect_tx(full + 8 * s, 16384 + K1_WS);
                tma_load_2d(sb + s * K1_ST, &tm_x, kb * 64, mt * 128, full + 8 * s);
                tma_load_3d(sb + s * K1_ST + K1_XS, &tm_w, nt * 64, kb * 64, 0, full + 8 * s);
            }
        }
        __syncwarp();
        if (lane < FF / 128) g_act[blockIdx.x * (FF / 128) + lane] = 0xFFFFFFFFu;
        for (int i = lane; i < 128; i += 32) g_part[blockIdx.x * 128 + i] = make_float4(0.f, 0.f, 0.f, 0.f);
        if (blockIdx.x == 1) { g_cand[lane] = make_uint4(0, 0, 0, 0); g_cand[lane + 32] = make_uint4(0, 0, 0, 0); g_hflag[lane] = 0; g_sflag[lane] = 0; }
        if (blockIdx.x == 2) for (int i = lane; i < 1024; i += 32) g_oflag[i] = 0;
    } else if (warp >= 12) {
        const int r = tid - 384;
        const unsigned int tag = *(volatile unsigned int*)&g_epoch + 1u;
        {
            const int row = mt * 128 + nt * 16 + (r >> 3);
            const uint4* xp = (const uint4*)(x + (size_t)row * DM) + (r & 7);
            uint4 v[8];
#pragma unroll
            for (int i = 0; i < 8; i++) v[i] = __ldg(xp + i * 8);
            float s1 = 0.f;
#pragma unroll
            for (int i = 0; i < 8; i++)
                s1 += ((bf_lo(v[i].x) + bf_hi(v[i].x)) + (bf_lo(v[i].y) + bf_hi(v[i].y))) + ((bf_lo(v[i].z) + bf_hi(v[i].z)) + (bf_lo(v[i].w) + bf_hi(v[i].w)));
#pragma unroll
            for (int o = 1; o < 8; o <<= 1) s1 += __shfl_xor_sync(0xffffffffu, s1, o);
            const float mean = s1 * (1.f / DM);
            float q0 = 0.f, q1 = 0.f;
#pragma unroll
            for (int i = 0; i < 8; i++) {
                const uint32_t w[4] = {v[i].x, v[i].y, v[i].z, v[i].w};
#pragma unroll
                for (int j = 0; j < 4; j++) {
                    const float a = bf_lo(w[j]) - mean, b = bf_hi(w[j]) - mean;
                    q0 = fmaf(a, a, q0); q1 = fmaf(b, b, q1);
                }
            }
            float q = q0 + q1;
#pragma unroll
            for (int o = 1; o < 8; o <<= 1) q += __shfl_xor_sync(0xffffffffu, q, o);
            const float den = rbf(sqrtf(rbf(rbf(q * (1.f / DM)) + 1e-5f)));
            if ((r & 7) == 0)
                asm volatile("st.relaxed.gpu.global.v4.f32 [%0], {%1, %2, %3, %4};" ::"l"(g_ln1 + row), "f"(rbf(mean)), "f"(1.f / den),
                             "f"(__uint_as_float(tag)), "f"(0.f) : "memory");
        }
        if (r == 0) TSTAMP0(0, 6);
        {
            float4 v;
            int spins = 0;
            do {
                asm volatile("ld.relaxed.gpu.global.v4.f32 {%0, %1, %2, %3}, [%4];" : "=f"(v.x), "=f"(v.y), "=f"(v.z), "=f"(v.w) : "l"(g_ln1 + mt * 128 + r) : "memory");
            } while (__float_as_uint(v.z) != tag && ++spins < (1 << 22));
            s_mr[(r >> 1) * 4 + (r & 1)] = v.x;
            s_mr[(r >> 1) * 4 + 2 + (r & 1)] = v.y;
        }
        if (r == 0) TSTAMP0(0, 7);
        named_arrive(1, 512);
    } else {
        const int part = warp >> 2, hw = warp & 3;
        float acc[68];
#pragma unroll
        for (int i = 0; i < 68; i++) acc[i] = 0.f;
        fence_regs(acc);
#pragma unroll 1
        for (int kb = 0; kb < 8; kb++) {
            const int s = kb % K1_NST;
            mbar_wait(full + 8 * s, (kb / K1_NST) & 1);
            const uint64_t da = make_desc(sb + s * K1_ST + K1_XS + part * 8192, 1024, 1024, 1);
            const uint64_t db = make_desc(sb + s * K1_ST, 16, 1024, 1);
            wg_fence();
#pragma unroll
            for (int k = 0; k < 4; k++) wgmma_k1_n136(acc, da + k * 128, db + k * 2, (kb | k) != 0);
            wg_commit();
            if (kb > 0 && kb <= 8 - K1_NST) {
                wg_wait<1>();
                if ((tid & 127) == 0) mbar_arrive(empty + 8 * (kb - 1));
            }
        }
        wg_wait<0>();
        fence_regs(acc);
        if (tid == 0) TSTAMP0(0, 1);
        named_sync(1, 512);
        if (tid == 0) TSTAMP0(0, 2);

        const int t = lane & 3;
        const float cs0 = acc[64], cs1 = acc[66];
        const float sc = (part == 0) ? QSCALE : 1.f;
        const uint32_t stg = sb + (hw >> 1) * K1_ST + K1_XS + part * 8192 + (hw & 1) * 4096;
        const uint32_t st_addr = stg + ((lane >> 3) & 1) * 2048 + ((lane >> 4) * 8 + (lane & 7)) * 16;
#pragma unroll
        for (int j = 0; j < 16; j += 2) {
            uint32_t rr[4];
#pragma unroll
            for (int u = 0; u < 2; u++) {
                const int jj = j + u;
                const float4 mr = *(const float4*)(s_mr + (4 * jj + t) * 4);
                const float2 m2 = make_float2(mr.x, mr.y);
                const float ra = mr.z * sc, rb = mr.w * sc;
                rr[2 * u] = pack_bf16((acc[4 * jj] - m2.x * cs0) * ra, (acc[4 * jj + 1] - m2.y * cs0) * rb);
                rr[2 * u + 1] = pack_bf16((acc[4 * jj + 2] - m2.x * cs1) * ra, (acc[4 * jj + 3] - m2.y * cs1) * rb);
            }
            stmatrix_x4_trans(st_addr + j * 128, rr[0], rr[1], rr[2], rr[3]);
        }
        fence_proxy_async();
        __syncwarp();
        if (tid == 0) TSTAMP0(0, 4);
        const int head = nt * 4 + hw;
        if (lane == 0) {
            uint8_t* dst;
            uint32_t hstride;
            if (part == 0) { dst = g_q + (size_t)head * 65536 + mt * 2048; hstride = 32768; }
            else { dst = g_kv + (size_t)head * 131072 + (mt >> 1) * 16384 + (part - 1) * 8192 + (mt & 1) * 2048; hstride = 4096; }
            bulk_s2g(dst, stg, 2048);
            bulk_s2g(dst + hstride, stg + 2048, 2048);
            asm volatile("cp.async.bulk.commit_group;" ::: "memory");
        }
        float nmax = 0.f;
#pragma unroll
        for (int i = 0; i < 4; i++) {
            const int tok = lane + 32 * i;
            const uint4 a = *(const uint4*)(sp + (stg - sb) + tok * 16);
            const uint4 b = *(const uint4*)(sp + (stg - sb) + 2048 + tok * 16);
            uint32_t n0 = fma_bf16x2(a.x, a.x, 0u), n1 = fma_bf16x2(b.x, b.x, 0u);
            n0 = fma_bf16x2(a.y, a.y, n0); n1 = fma_bf16x2(b.y, b.y, n1);
            n0 = fma_bf16x2(a.z, a.z, n0); n1 = fma_bf16x2(b.z, b.z, n1);
            n0 = fma_bf16x2(a.w, a.w, n0); n1 = fma_bf16x2(b.w, b.w, n1);
            const float n2 = ((bf_lo(n0) + bf_hi(n0)) + (bf_lo(n1) + bf_hi(n1))) * 1.125f;
            nmax = (n2 > nmax || n2 != n2) ? n2 : nmax;
        }
#pragma unroll
        for (int o = 16; o > 0; o >>= 1) {
            const float v = __shfl_xor_sync(0xffffffffu, nmax, o);
            nmax = (v > nmax || v != v) ? v : nmax;
        }
        if (tid == 0) TSTAMP0(0, 5);
        if (lane == 0) {
            g_norm[(head * 16 + mt) * 3 + part] = nmax;
            asm volatile("cp.async.bulk.wait_group.read 0;" ::: "memory");
            if (tid == 0) TSTAMP0(0, 3);
        }
    }
}

#define POLL_NS 50
constexpr int KF_CH_G = 16384, KF_CH_S = 20480, KF_NCH = 8;
constexpr int KF_OFF_WO = KF_NCH * KF_CH_S;
constexpr int KF_OFF_MISC = KF_OFF_WO + 65536;
constexpr int KF_SMEM = KF_OFF_MISC + 1536 + 1024;

__device__ __forceinline__ uint32_t exp2_pair_poly(float t0, float t1) {
    const uint32_t w = __byte_perm(__float_as_uint(t0), __float_as_uint(t1), 0x5410);
    uint32_t z;
    asm("lop3.b32 %0, %1, %2, %3, 0xEA;" : "=r"(z) : "r"(w), "r"(0x007F007Fu), "r"(0x3F803F80u));
    uint32_t p = fma_bf16x2(0x3eab3eabu, z, 0xbc73bc73u);
    p = fma_bf16x2(p, z, 0x3f2f3f2fu);
    return p + w - z;
}
constexpr uint32_t KF_EMASK = 0x03FFu;
template <int LO, int HI>
__device__ __forceinline__ void softmax_part(const float (&s)[32], uint32_t (&p)[16]) {
#pragma unroll
    for (int i = LO; i < HI; i++) {
        if ((KF_EMASK >> i) & 1) p[i] = exp2_pair_poly(s[2 * i], s[2 * i + 1]);
        else p[i] = pack_bf16(ex2f(s[2 * i]), ex2f(s[2 * i + 1]));
    }
}
#define KF_PV(P, OFF)                                                                              \
    _Pragma("unroll") for (int kk = 0; kk < 4; kk++)                                               \
        wgmma_pv_n24(o, P[4 * kk], P[4 * kk + 1], P[4 * kk + 2], P[4 * kk + 3], dv + ((OFF) + kk * 16));

__device__ __forceinline__ uint32_t make_key(float r_bf16, int token) {
    const uint32_t u = __float_as_uint(r_bf16) >> 16;
    const uint32_t o = (u & 0x8000u) ? (~u & 0xFFFFu) : (u | 0x8000u);
    return (o << 16) | (uint32_t)(0xFFFF - token);
}
__device__ __forceinline__ float key_value(uint32_t k) {
    const uint32_t o = k >> 16;
    const uint32_t u = (o & 0x8000u) ? (o & 0x7FFFu) : (~o & 0xFFFFu);
    return __uint_as_float(u << 16);
}
__device__ __forceinline__ int key_token(uint32_t k) { return 0xFFFF - (int)(k & 0xFFFFu); }
__device__ __forceinline__ void warp_top2(uint32_t a, uint32_t b, uint32_t& k1, uint32_t& k2) {
    k1 = __reduce_max_sync(0xffffffffu, a > b ? a : b);
    const uint32_t a2 = (a == k1) ? 0u : a, b2 = (b == k1) ? 0u : b;
    k2 = __reduce_max_sync(0xffffffffu, a2 > b2 ? a2 : b2);
}
__device__ __forceinline__ unsigned int ld_acquire(const unsigned int* p) {
    unsigned int v; asm volatile("ld.acquire.gpu.global.u32 %0, [%1];" : "=r"(v) : "l"(p) : "memory"); return v;
}
__device__ __forceinline__ void red_release_add(unsigned int* p) {
    asm volatile("red.release.gpu.global.add.u32 [%0], 1;" ::"l"(p) : "memory");
}

__global__ void __launch_bounds__(512, 1)
kf_main(const __grid_constant__ CUtensorMap tm_o, const __grid_constant__ CUtensorMap tm_wo,
        const __grid_constant__ CUtensorMap tm_g, const __grid_constant__ CUtensorMap tm_u, const __grid_constant__ CUtensorMap tm_d,
        const __nv_bfloat16* __restrict__ x, const __nv_bfloat16* __restrict__ wo, const __nv_bfloat16* __restrict__ w_r,
        const __nv_bfloat16* __restrict__ w_gate, const __nv_bfloat16* __restrict__ w_up, const __nv_bfloat16* __restrict__ w_down,
        __nv_bfloat16* __restrict__ out) {
    extern __shared__ uint8_t smem_raw[];
    const uint32_t sraw = smem_u32(smem_raw);
    const uint32_t sb = (sraw + 1023) & ~1023u;
    uint8_t* sp = smem_raw + (sb - sraw);
    const uint32_t kvbar = sb + KF_OFF_MISC;
    const uint32_t wbar = kvbar + 64;
    const uint32_t obar = wbar + 64;
    const uint32_t gbar = obar + 64;
    const uint32_t dbar = gbar + 8;
    unsigned int* s_cnt = (unsigned int*)(sp + KF_OFF_MISC + 208);
    volatile unsigned int* s_order = (volatile unsigned int*)(sp + KF_OFF_MISC + 1056);
    uint32_t* s_key = (uint32_t*)(sp + KF_OFF_MISC + 256);
    float* s_gu = (float*)(sp + KF_OFF_WO + 49152 + 8192 + 4608);
    uint4* s_sel = (uint4*)(sp + KF_OFF_MISC + 1024);
    const int tid = threadIdx.x;
    const int head = blockIdx.x >> 2, quarter = blockIdx.x & 3;
    const int mt = blockIdx.x >> 2, nt = blockIdx.x & 3;
    if (tid == 0) TSTAMP0(1, 0);
    if (tid == 0) {
        for (int c = 0; c < 26; c++) mbar_init(kvbar + 8 * c, 1);
        for (int c = 0; c < 4; c++) s_cnt[c] = 0;
        fence_barrier_init();
        for (int kb = 0; kb < 4; kb++) {
            mbar_expect_tx(wbar + 8 * kb, 16384);
            tma_load_3d(sb + KF_OFF_WO + kb * 16384, &tm_wo, 0, kb * 64, nt * 2, wbar + 8 * kb);
        }
    }
    if (tid == 32) {
        prefetch_l2((const uint8_t*)wo + blockIdx.x * 4096, 4096);
        prefetch_l2((const uint8_t*)w_gate + blockIdx.x * 14336, 14336);
        prefetch_l2((const uint8_t*)w_up + blockIdx.x * 14336, 14336);
        prefetch_l2((const uint8_t*)w_down + blockIdx.x * 14336, 14336);
    }
    if (tid < 24) *(uint4*)(sp + KF_OFF_MISC + 1152 + tid * 16) =
        tid < 8 ? make_uint4(0x42FE4380u, 0x00003D80u, 0u, 0u) : (tid < 16 ? make_uint4(0x3F804380u, 0x00003E00u, 0u, 0u) : make_uint4(0u, 0u, 0u, 0u));
    for (int i = tid; i < KF_NCH * 256; i += 512)
        *(uint4*)(sp + (i >> 8) * KF_CH_S + 16384 + (i & 255) * 16) =
            make_uint4(0x3F803F80u, 0x3F803F80u, 0x3F803F80u, 0x3F803F80u);
    fence_proxy_async();
    __syncthreads();
    pdl_wait();
    if (tid == 0) TSTAMP0(1, 1);
    const uint8_t* kvsrc = g_kv + (size_t)head * (KF_NCH * KF_CH_G);
    if (tid == 32) {
        mbar_expect_tx(kvbar, KF_CH_G);
        bulk_g2s(sb, kvsrc, KF_CH_G, kvbar);
    }
    const int wg = tid >> 7, warp = (tid >> 5) & 3, lane = tid & 31, g = lane >> 2, t = lane & 3;
    if (tid < 32) {
        const int m16 = lane & 15;
        float kn = g_norm[(head * 16 + m16) * 3 + 1];
        float vn = g_norm[(head * 16 + m16) * 3 + 2];
        float qn = g_norm[(head * 16 + quarter * 4 + (lane & 3)) * 3 + 0];
        const bool bad = !(kn < 1e30f) || !(vn < 1e9f) || !(qn < 1e30f);
#pragma unroll
        for (int o = 8; o > 0; o >>= 1) {
            kn = fmaxf(kn, __shfl_xor_sync(0xffffffffu, kn, o));
            qn = fmaxf(qn, __shfl_xor_sync(0xffffffffu, qn, o));
        }
        const bool ok = __all_sync(0xffffffffu, !bad && (qn * kn <= 9000.f));
        if (lane == 0) s_cnt[4] = ok ? 1u : 0u;
    }
    uint32_t qn2[2][4];
#pragma unroll
    for (int ps = 0; ps < 2; ps++) {
        const uint8_t* qb = g_q + (size_t)head * 65536 + (quarter * 512 + ps * 256 + wg * 64 + warp * 16 + g) * 16 + t * 4;
        qn2[ps][0] = *(const uint32_t*)(qb);
        qn2[ps][1] = *(const uint32_t*)(qb + 128);
        qn2[ps][2] = *(const uint32_t*)(qb + 32768);
        qn2[ps][3] = *(const uint32_t*)(qb + 32768 + 128);
    }

    __syncthreads();
    const bool fast = __all_sync(0xffffffffu, s_cnt[4] != 0u);
    if (tid == 32) {
        for (int c = 1; c < KF_NCH; c++) {
            mbar_expect_tx(kvbar + 8 * c, KF_CH_G);
            bulk_g2s(sb + c * KF_CH_S, kvsrc + c * KF_CH_G, KF_CH_G, kvbar + 8 * c);
        }
    }
    if (tid == 0) TSTAMP0(1, 8);
    const uint64_t dbias_a = make_desc(sb + KF_OFF_MISC + 1152, 0, 0, 0);
    const uint64_t dbias_b = make_desc(sb + KF_OFF_MISC + 1280, 128, 0, 0);
    const uint64_t dk0 = make_desc(sb, 4096, 128, 0);
    const uint64_t dv0 = make_desc(sb + 8192, 128, 4096, 0);

#pragma unroll 1
    for (int pass = 0; pass < 2; pass++) {
        const int row0 = quarter * 512 + pass * 256 + wg * 64 + warp * 16 + g;
        uint32_t qa[4];
#pragma unroll
        for (int i = 0; i < 4; i++) qa[i] = pass ? qn2[1][i] : qn2[0][i];
        float o[12];
#pragma unroll
        for (int i = 0; i < 12; i++) o[i] = 0.f;
        fence_regs(o);
#define KF_RELEASE_CHUNK(c)                                                                          \
        if (pass == 1 && (c) >= 1 && (c) <= 4) {                                                     \
            named_sync(4 + wg, 128);            \
            if ((tid & 127) == 0 && atomicAdd(&s_cnt[(c) - 1], 1u) == 3u) {                          \
                mbar_expect_tx(wbar + 8 * (3 + (c)), 16384);                                         \
                tma_load_3d(sb + ((c) - 1) * KF_CH_S, &tm_wo, 0, (3 + (c)) * 64, nt * 2, wbar + 8 * (3 + (c))); \
            }                                                                                        \
        }
        if (fast) {
#pragma unroll 1
            for (int c = 0; c < KF_NCH; c++) {
                const uint64_t dk = dk0 + (uint64_t)(c * (KF_CH_S >> 4));
                const uint64_t dv = dv0 + (uint64_t)(c * (KF_CH_S >> 4));
                float s0[32], s1[32], s2[32], s3[32];
                uint32_t p0[16], p1[16], p2[16], p3[16];
                mbar_wait(kvbar + 8 * c, 0);
                wg_wait<1>();
                wg_fence();
                wgmma_qk_n64(s0, qa[0], qa[1], qa[2], qa[3], dk);
                wgmma_bias_n40(s0, dbias_a, dbias_b);
                wg_commit();
                wg_wait<1>();
                KF_RELEASE_CHUNK(c);
                wg_fence();
                wgmma_qk_n64(s1, qa[0], qa[1], qa[2], qa[3], dk + 64);
                wgmma_bias_n40(s1, dbias_a, dbias_b);
                wg_commit();
                wg_wait<1>();
                fence_regs(s0);
                softmax_part<0, 16>(s0, p0);
                wg_fence();
                KF_PV(p0, 0);
                wg_commit();
                wg_wait<1>();
                fence_regs(s1);
                softmax_part<0, 8>(s1, p1);
                wg_wait<0>();
                wg_fence();
                wgmma_qk_n64(s2, qa[0], qa[1], qa[2], qa[3], dk + 128);
                wgmma_bias_n40(s2, dbias_a, dbias_b);
                wg_commit();
                softmax_part<8, 16>(s1, p1);
                wg_fence();
                KF_PV(p1, 64);
                wg_commit();
                wg_wait<1>();
                fence_regs(s2);
                softmax_part<0, 8>(s2, p2);
                wg_wait<0>();
                wg_fence();
                wgmma_qk_n64(s3, qa[0], qa[1], qa[2], qa[3], dk + 192);
                wgmma_bias_n40(s3, dbias_a, dbias_b);
                wg_commit();
                softmax_part<8, 16>(s2, p2);
                wg_fence();
                KF_PV(p2, 128);
                wg_commit();
                wg_wait<1>();
                fence_regs(s3);
                softmax_part<0, 16>(s3, p3);
                wg_fence();
                KF_PV(p3, 192);
                wg_commit();
            }
            wg_wait<0>();
            fence_regs(o);
        } else {
            float m0 = -INFINITY, m1 = -INFINITY;
#pragma unroll 1
            for (int b = 0; b < 32; b++) {
                const int c = b >> 2;
                const uint64_t dk = dk0 + (uint64_t)(c * (KF_CH_S >> 4) + (b & 3) * 64);
                const uint64_t dv = dv0 + (uint64_t)(c * (KF_CH_S >> 4) + (b & 3) * 64);
                float s[32];
                uint32_t p[16];
                mbar_wait(kvbar + 8 * c, 0);
                wg_fence();
                wgmma_qk_n64(s, qa[0], qa[1], qa[2], qa[3], dk);
                wg_commit();
                if ((b & 3) == 0) { KF_RELEASE_CHUNK(c); }
                wg_wait<0>();
                fence_regs(s);
                float x0 = s[0], x1 = s[2];
#pragma unroll
                for (int j = 0; j < 8; j++) {
                    x0 = fmaxf(x0, fmaxf(s[4 * j], s[4 * j + 1]));
                    x1 = fmaxf(x1, fmaxf(s[4 * j + 2], s[4 * j + 3]));
                }
                x0 = fmaxf(x0, __shfl_xor_sync(0xffffffffu, x0, 1));
                x0 = fmaxf(x0, __shfl_xor_sync(0xffffffffu, x0, 2));
                x1 = fmaxf(x1, __shfl_xor_sync(0xffffffffu, x1, 1));
                x1 = fmaxf(x1, __shfl_xor_sync(0xffffffffu, x1, 2));
                const float n0 = fmaxf(m0, x0), n1 = fmaxf(m1, x1);
                const float c0 = ex2f(m0 - n0), c1 = ex2f(m1 - n1);
                m0 = n0; m1 = n1;
#pragma unroll
                for (int j = 0; j < 3; j++) {
                    o[4 * j] *= c0; o[4 * j + 1] *= c0; o[4 * j + 2] *= c1; o[4 * j + 3] *= c1;
                }
#pragma unroll
                for (int j = 0; j < 8; j++) {
                    p[2 * j] = pack_bf16(ex2f(s[4 * j] - n0), ex2f(s[4 * j + 1] - n0));
                    p[2 * j + 1] = pack_bf16(ex2f(s[4 * j + 2] - n1), ex2f(s[4 * j + 3] - n1));
                }
                fence_regs(o);
                wg_fence();
                KF_PV(p, 0);
                wg_commit();
                wg_wait<0>();
                fence_regs(o);
            }
        }
        const float inv0 = 1.f / o[8], inv1 = 1.f / o[10];
        {
            uint32_t v0 = pack_bf16(o[0] * inv0, o[1] * inv0), v1 = pack_bf16(o[4] * inv0, o[5] * inv0);
            uint32_t v2 = pack_bf16(o[2] * inv1, o[3] * inv1), v3 = pack_bf16(o[6] * inv1, o[7] * inv1);
            const bool o1 = t & 1, o2 = t & 2;
            uint32_t s0 = o1 ? v0 : v1, s1 = o1 ? v2 : v3;
            s0 = __shfl_xor_sync(0xffffffffu, s0, 1); s1 = __shfl_xor_sync(0xffffffffu, s1, 1);
            uint32_t a0 = o1 ? s0 : v0, a1 = o1 ? v1 : s0, b0 = o1 ? s1 : v2, b1 = o1 ? v3 : s1;
            uint32_t x0 = o2 ? a0 : b0, x1 = o2 ? a1 : b1;
            x0 = __shfl_xor_sync(0xffffffffu, x0, 2); x1 = __shfl_xor_sync(0xffffffffu, x1, 2);
            uint4 r;
            r.x = o2 ? x0 : a0; r.y = o2 ? x1 : a1; r.z = o2 ? b0 : x0; r.w = o2 ? b1 : x1;
            *(uint4*)(g_o + (size_t)(row0 + (t >> 1) * 8) * DM + head * 16 + (t & 1) * 8) = r;
        }
        if (tid == 0) TSTAMP0(1, 4 + pass);
    }
    if ((tid >> 5) != 10) named_arrive(1, 512);
    named_sync(4 + wg, 128);
    if ((tid & 127) == 0) {
        asm volatile("fence.acq_rel.gpu;" ::: "memory");
        asm volatile("red.relaxed.gpu.global.add.u32 [%0], 1;" ::"l"(&g_oflag[(quarter * 8 + 4 + wg) * 32 + (head >> 2) * 4]) : "memory");
        asm volatile("red.relaxed.gpu.global.add.u32 [%0], 1;" ::"l"(&g_oflag[(quarter * 8 + wg) * 32 + (head >> 2) * 4]) : "memory");
    }
    if (tid == 0) TSTAMP0(1, 3);

    if (wg < 2) {
        const int wi = warp;
        const int r0 = mt * 64 + wi * 16 + g;
        const int cb = nt * 128 + wg * 64;
        uint32_t xr[16], wr[8];
#pragma unroll
        for (int j = 0; j < 8; j++) {
            xr[2 * j] = __ldg((const uint32_t*)(x + (size_t)r0 * DM + cb + 8 * j + 2 * t));
            xr[2 * j + 1] = __ldg((const uint32_t*)(x + (size_t)(r0 + 8) * DM + cb + 8 * j + 2 * t));
            wr[j] = __ldg((const uint32_t*)(w_r + cb + 8 * j + 2 * t));
        }
        float wsum = 0.f;
        {
            const uint4 a = __ldg((const uint4*)(w_r + lane * 16)), b = __ldg((const uint4*)(w_r + lane * 16 + 8));
            const uint32_t w[8] = {a.x, a.y, a.z, a.w, b.x, b.y, b.z, b.w};
#pragma unroll
            for (int i = 0; i < 8; i++) wsum += bf_lo(w[i]) + bf_hi(w[i]);
#pragma unroll
            for (int o = 16; o > 0; o >>= 1) wsum += __shfl_xor_sync(0xffffffffu, wsum, o);
        }
        float acc[32];
#pragma unroll
        for (int i = 0; i < 32; i++) acc[i] = 0.f;
        fence_regs(acc);
#pragma unroll 1
        for (int i = 0; i < 8; i++) {
            mbar_wait(obar + 8 * i, 0);
            const int kb = __shfl_sync(0xffffffffu, (int)s_order[i], 0);
            mbar_wait(wbar + 8 * kb, 0);
            const uint32_t wa = (kb < 4) ? (KF_OFF_WO + kb * 16384) : ((kb - 4) * KF_CH_S);
            const uint64_t da = make_desc(sb + (4 + (kb >> 1)) * KF_CH_S + (kb & 1) * 8192, 16, 1024, 1);
            const uint64_t db = make_desc(sb + wa + wg * 8192, 1024, 1024, 1);
            wg_fence();
#pragma unroll
            for (int k = 0; k < 4; k++) wgmma_k3_n64(acc, da + k * 2, db + k * 128, (i | k) != 0);
            wg_commit();
        }
        wg_wait<0>();
        fence_regs(acc);
        if (tid == 0) TSTAMP0(2, 2);
        float hv[32];
        uint32_t hp[16];
        float s0 = 0.f, s1 = 0.f, d0 = 0.f, d1 = 0.f;
#pragma unroll
        for (int j = 0; j < 8; j++) {
            const uint32_t a01 = pack_bf16(acc[4 * j], acc[4 * j + 1]), a23 = pack_bf16(acc[4 * j + 2], acc[4 * j + 3]);
            hp[2 * j] = pack_bf16(bf_lo(xr[2 * j]) + bf_lo(a01), bf_hi(xr[2 * j]) + bf_hi(a01));
            hp[2 * j + 1] = pack_bf16(bf_lo(xr[2 * j + 1]) + bf_lo(a23), bf_hi(xr[2 * j + 1]) + bf_hi(a23));
            hv[4 * j] = bf_lo(hp[2 * j]); hv[4 * j + 1] = bf_hi(hp[2 * j]);
            hv[4 * j + 2] = bf_lo(hp[2 * j + 1]); hv[4 * j + 3] = bf_hi(hp[2 * j + 1]);
            const float wl = bf_lo(wr[j]), wh = bf_hi(wr[j]);
            s0 += hv[4 * j] + hv[4 * j + 1];
            s1 += hv[4 * j + 2] + hv[4 * j + 3];
            d0 = fmaf(hv[4 * j], wl, fmaf(hv[4 * j + 1], wh, d0));
            d1 = fmaf(hv[4 * j + 2], wl, fmaf(hv[4 * j + 3], wh, d1));
        }
        float mu0 = s0 * (1.f / 16), mu1 = s1 * (1.f / 16);
        float q0 = 0.f, q1 = 0.f;
#pragma unroll
        for (int j = 0; j < 8; j++) {
            float a = hv[4 * j] - mu0, b = hv[4 * j + 1] - mu0, c = hv[4 * j + 2] - mu1, d = hv[4 * j + 3] - mu1;
            q0 = fmaf(a, a, fmaf(b, b, q0));
            q1 = fmaf(c, c, fmaf(d, d, q1));
        }
#pragma unroll
        for (int o = 1; o < 4; o <<= 1) {
            const float m0 = __shfl_xor_sync(0xffffffffu, mu0, o), m1 = __shfl_xor_sync(0xffffffffu, mu1, o);
            const float e0 = __shfl_xor_sync(0xffffffffu, q0, o), e1 = __shfl_xor_sync(0xffffffffu, q1, o);
            d0 += __shfl_xor_sync(0xffffffffu, d0, o);
            d1 += __shfl_xor_sync(0xffffffffu, d1, o);
            const float f0 = mu0 - m0, f1 = mu1 - m1;
            q0 = q0 + e0 + f0 * f0 * (8.f * o);
            q1 = q1 + e1 + f1 * f1 * (8.f * o);
            mu0 = 0.5f * (mu0 + m0); mu1 = 0.5f * (mu1 + m1);
        }
        float4* part = g_part + (size_t)mt * 512 + wi * 16 + g;
        if (t < 2) {
            float4* dst = part + (nt * 2 + wg) * 64 + t * 8;
            const float a = t ? mu1 : mu0, b = t ? q1 : q0, c = t ? d1 : d0;
            asm volatile("st.relaxed.gpu.global.v4.f32 [%0], {%1, %2, %3, %4};" ::"l"(dst), "f"(a), "f"(b), "f"(c), "f"(1.0f) : "memory");
        }
        if (tid == 0) TSTAMP0(2, 5);
        const uint32_t stg_off = KF_OFF_WO + (wi >> 1) * 16384 + wg * 8192 + (wi & 1) * 4096;
        const uint32_t stg_o = sb + stg_off, stg_h = stg_o + 2048;
        const int srow = (lane & 7) + ((lane >> 3) & 1) * 8;
        const int sj = lane >> 4;
        named_sync(4 + wg, 128);
#pragma unroll
        for (int j = 0; j < 8; j += 2) {
            const uint32_t off = srow * 128 + (((j + sj) ^ (srow & 7)) << 4);
            stmatrix_x4(stg_h + off, hp[2 * j], hp[2 * j + 1], hp[2 * j + 2], hp[2 * j + 3]);
        }
        __syncwarp();
#pragma unroll
        for (int i = 0; i < 4; i++) {
            const int row = i * 4 + (lane >> 3), ch = lane & 7;
            const uint4 vh = *(const uint4*)(sp + stg_off + 2048 + row * 128 + ((ch ^ (row & 7)) << 4));
            *(uint4*)(g_h + (size_t)(mt * 64 + wi * 16 + row) * DM + cb + ch * 8) = vh;
        }
        named_arrive(8, 288);
        if (tid == 0) TSTAMP0(2, 6);
        float mean[2], den[2], rr[2];
        {
            float4 v[4];
            int spins = 0;
            while (true) {
#pragma unroll
                for (int i = 0; i < 4; i++) {
                    const float4* p = part + (t + (i & 1) * 4) * 64 + (i >> 1) * 8;
                    asm volatile("ld.relaxed.gpu.global.v4.f32 {%0, %1, %2, %3}, [%4];" : "=f"(v[i].x), "=f"(v[i].y), "=f"(v[i].z), "=f"(v[i].w) : "l"(p) : "memory");
                }
                const bool ok = (v[0].w != 0.f) && (v[1].w != 0.f) && (v[2].w != 0.f) && (v[3].w != 0.f);
                if (__all_sync(0xffffffffu, ok) || ++spins > (1 << 22)) break;
            }
#pragma unroll
            for (int u = 0; u < 2; u++) {
                float mu = v[2 * u].x + v[2 * u + 1].x, m2 = v[2 * u].y + v[2 * u + 1].y, hw = v[2 * u].z + v[2 * u + 1].z;
#pragma unroll
                for (int o = 1; o < 4; o <<= 1) {
                    mu += __shfl_xor_sync(0xffffffffu, mu, o);
                    m2 += __shfl_xor_sync(0xffffffffu, m2, o);
                    hw += __shfl_xor_sync(0xffffffffu, hw, o);
                }
                mu *= 0.125f;
                const float da = v[2 * u].x - mu, db = v[2 * u + 1].x - mu;
                float dd = 64.f * (da * da + db * db);
#pragma unroll
                for (int o = 1; o < 4; o <<= 1) dd += __shfl_xor_sync(0xffffffffu, dd, o);
                m2 += dd;
                mean[u] = rbf(mu);
                den[u] = rbf(sqrtf(rbf(rbf(m2 * (1.f / DM)) + 1e-5f)));
                rr[u] = rbf((hw - mean[u] * wsum) / den[u]);
            }
        }
        if (tid == 0) TSTAMP0(2, 3);
        named_arrive(3, 512);
        if (nt == 0 && wg == 0) {
            float2* s_st = (float2*)(sp + KF_OFF_WO + 49152);
            if (t == 0) {
                s_key[wi * 16 + g] = make_key(rr[0], r0);
                s_key[wi * 16 + g + 8] = make_key(rr[1], r0 + 8);
                s_st[wi * 16 + g] = make_float2(mean[0], den[0]);
                s_st[wi * 16 + g + 8] = make_float2(mean[1], den[1]);
            }
            named_sync(4, 128);
            if (warp == 0) {
                uint32_t k1, k2;
                warp_top2(s_key[lane], s_key[lane + 32], k1, k2);
                if (lane < 2) {
                    const uint32_t k = lane ? k2 : k1;
                    const float2 st = s_st[key_token(k) & 63];
                    asm volatile("st.relaxed.gpu.global.v4.u32 [%0], {%1, %2, %3, %4};" ::"l"(g_cand + mt * 2 + lane), "r"(k),
                                 "r"(1u), "r"(__float_as_uint(st.x)), "r"(__float_as_uint(st.y)) : "memory");
                }
            }
        }
        const float i0 = 1.f / den[0], i1 = 1.f / den[1];
#pragma unroll
        for (int j = 0; j < 8; j += 2) {
            uint32_t ro[4];
#pragma unroll
            for (int u = 0; u < 2; u++) {
                const int jj = j + u;
                const float a = hv[4 * jj], b = hv[4 * jj + 1], c = hv[4 * jj + 2], d = hv[4 * jj + 3];
                const uint32_t u01 = pack_bf16(a - mean[0], b - mean[0]), u23 = pack_bf16(c - mean[1], d - mean[1]);
                const uint32_t n01 = pack_bf16(bf_lo(u01) * i0, bf_hi(u01) * i0), n23 = pack_bf16(bf_lo(u23) * i1, bf_hi(u23) * i1);
                ro[2 * u] = pack_bf16(a + bf_lo(n01), b + bf_hi(n01));
                ro[2 * u + 1] = pack_bf16(c + bf_lo(n23), d + bf_hi(n23));
            }
            const uint32_t off = srow * 128 + (((j + sj) ^ (srow & 7)) << 4);
            stmatrix_x4(stg_o + off, ro[0], ro[1], ro[2], ro[3]);
        }
        __syncwarp();
#pragma unroll
        for (int i = 0; i < 4; i++) {
            const int row = i * 4 + (lane >> 3), ch = lane & 7;
            const uint4 vo = *(const uint4*)(sp + stg_off + row * 128 + ((ch ^ (row & 7)) << 4));
            *(uint4*)(out + (size_t)(mt * 64 + wi * 16 + row) * DM + cb + ch * 8) = vo;
        }
        named_sync(4 + wg, 128);
        if ((tid & 127) == 0) red_release_add(&g_sflag[mt]);
        if (tid == 0) TSTAMP0(2, 4);
    } else {
        const bool worker = blockIdx.x < FF / 16;
        const bool downer = blockIdx.x >= 64;
        const int mtid = tid - 256, mwarp = mtid >> 5;
        const int c0 = (blockIdx.x - 64) * 8;
        float* s_x = (float*)(sp + KF_OFF_WO + 49152 + 8192);
        float* s_red = (float*)(sp + KF_OFF_WO + 49152 + 8192 + 4096);
        if (mwarp == 2) {
            named_sync(1, 512);
            uint32_t done = 0;
            int n = 0, spins = 0;
            while (done != 0xFFu && ++spins < (1 << 22)) {
                const bool rdy = lane < 8 && ld_acquire(&g_oflag[mt * 32 + lane * 4]) >= 4u;
                uint32_t todo = __ballot_sync(0xffffffffu, rdy) & ~done;
                done |= todo;
                if (todo && lane == 0) {
                    asm volatile("fence.proxy.async.global;" ::: "memory");
                    while (todo) {
                        const int kb = __ffs(todo) - 1;
                        todo &= todo - 1;
                        s_order[n] = kb;
                        mbar_expect_tx(obar + 8 * n, 8192);
                        tma_load_3d(sb + (4 + (kb >> 1)) * KF_CH_S + (kb & 1) * 8192, &tm_o, 0, mt * 64, kb, obar + 8 * n);
                        n++;
                    }
                }
                n = __shfl_sync(0xffffffffu, n, 0);
                if (done != 0xFFu) __nanosleep(POLL_NS);
            }
            if (lane == 0) TSTAMP0(2, 1);
            if (lane == 0 && worker) {
                mbar_expect_tx(gbar, 32768);
                for (int i = 0; i < 4; i++) {
                    tma_load_2d(sb + i * KF_CH_S + 16384, &tm_g, blockIdx.x * 16, i * 128, gbar);
                    tma_load_2d(sb + (4 + i) * KF_CH_S + 16384, &tm_u, blockIdx.x * 16, i * 128, gbar);
                }
            }
        }
        if (mwarp == 1) {
            named_sync(8, 288);
            if (lane == 0) {
                red_release_add(&g_hflag[mt]);
                if (downer) {
                    mbar_expect_tx(dbar, 7 * 4096);
                    for (int i = 0; i < 7; i++) tma_load_2d(sb + (4 + (i >> 2)) * KF_CH_S + (i & 3) * 4096, &tm_d, c0, i * 256, dbar);
                }
            }
            __syncwarp();
        }
        if (mtid == 0) TSTAMP0(3, 0);
        named_sync(3, 512);
        if (mwarp == 0) {
            uint4 ca, cb4;
            int spins = 0;
            while (true) {
                asm volatile("ld.relaxed.gpu.global.v4.u32 {%0, %1, %2, %3}, [%4];" : "=r"(ca.x), "=r"(ca.y), "=r"(ca.z), "=r"(ca.w) : "l"(g_cand + 2 * lane) : "memory");
                asm volatile("ld.relaxed.gpu.global.v4.u32 {%0, %1, %2, %3}, [%4];" : "=r"(cb4.x), "=r"(cb4.y), "=r"(cb4.z), "=r"(cb4.w) : "l"(g_cand + 2 * lane + 1) : "memory");
                const unsigned int hf = ld_acquire(&g_hflag[lane]);
                const bool ok = ca.y != 0 && cb4.y != 0 && hf >= 4u;
                if (__all_sync(0xffffffffu, ok) || ++spins > (1 << 22)) break;
            }
            uint32_t k1, k2;
            warp_top2(ca.x, cb4.x, k1, k2);
            if (ca.x == k1) s_sel[0] = ca;
            if (cb4.x == k1) s_sel[0] = cb4;
            if (ca.x == k2) s_sel[1] = ca;
            if (cb4.x == k2) s_sel[1] = cb4;
        }
        named_sync(2, 256);
        if (mtid == 0) TSTAMP0(3, 1);
        int idx[2];
        float mean[2], inv[2], rv[2];
#pragma unroll
        for (int u = 0; u < 2; u++) {
            const uint4 c = s_sel[u];
            idx[u] = key_token(c.x);
            rv[u] = key_value(c.x);
            mean[u] = __uint_as_float(c.z);
            inv[u] = 1.f / __uint_as_float(c.w);
        }
        float hfin = 0.f;
        if (downer && mtid < 16) hfin = __bfloat162float(__ldcg((const __nv_bfloat16*)(g_h + (size_t)((mtid >> 3) ? idx[1] : idx[0]) * DM + c0 + (mtid & 7))));
        if (worker) {
            {
                const uint32_t h0 = __ldcg((const uint32_t*)(g_h + (size_t)idx[0] * DM + 2 * mtid));
                const uint32_t h1 = __ldcg((const uint32_t*)(g_h + (size_t)idx[1] * DM + 2 * mtid));
                const uint32_t u0 = pack_bf16(bf_lo(h0) - mean[0], bf_hi(h0) - mean[0]), u1 = pack_bf16(bf_lo(h1) - mean[1], bf_hi(h1) - mean[1]);
                const uint32_t n0 = pack_bf16(bf_lo(u0) * inv[0], bf_hi(u0) * inv[0]), n1 = pack_bf16(bf_lo(u1) * inv[1], bf_hi(u1) * inv[1]);
                *(float4*)(s_x + 4 * mtid) = make_float4(bf_lo(n0), bf_lo(n1), bf_hi(n0), bf_hi(n1));
            }
            if (mtid == 0) TSTAMP0(3, 5);
            mbar_wait(gbar, 0);
            named_sync(2, 256);
            if (mtid == 0) TSTAMP0(3, 6);
            float acc[16];
#pragma unroll
            for (int i = 0; i < 16; i++) acc[i] = 0.f;
            const uint8_t* wbase = sp + ((mwarp >> 2) * 4 + (mwarp & 3)) * KF_CH_S + 16384 + lane * 16;
            const float* xb = s_x + 2 * (128 * (mwarp & 3) + (lane >> 1));
#pragma unroll
            for (int j = 0; j < 8; j++) {
                const uint4 w = *(const uint4*)(wbase + j * 512);
                const float2 xx = *(const float2*)(xb + 32 * j);
                const uint32_t ww[4] = {w.x, w.y, w.z, w.w};
#pragma unroll
                for (int q = 0; q < 4; q++) {
                    const float wl = bf_lo(ww[q]), wh = bf_hi(ww[q]);
                    acc[2 * q] = fmaf(xx.x, wl, acc[2 * q]); acc[2 * q + 1] = fmaf(xx.x, wh, acc[2 * q + 1]);
                    acc[8 + 2 * q] = fmaf(xx.y, wl, acc[8 + 2 * q]); acc[8 + 2 * q + 1] = fmaf(xx.y, wh, acc[8 + 2 * q + 1]);
                }
            }
#define KF_STEP(O, N)                                                          \
            {                                                                  \
                const bool up = (lane & (O)) != 0;                             \
                _Pragma("unroll") for (int i = 0; i < (N); i++) {              \
                    const float send = up ? acc[i] : acc[i + (N)];             \
                    const float keep = up ? acc[i + (N)] : acc[i];             \
                    acc[i] = keep + __shfl_xor_sync(0xffffffffu, send, (O));   \
                }                                                              \
            }
            KF_STEP(16, 8) KF_STEP(8, 4) KF_STEP(4, 2) KF_STEP(2, 1)
            {
                const int v = ((lane & 16) ? 8 : 0) + ((lane & 8) ? 4 : 0) + ((lane & 4) ? 2 : 0) + ((lane & 2) ? 1 : 0);
                s_gu[mwarp * 32 + (v >> 3) * 16 + (lane & 1) * 8 + (v & 7)] = acc[0];
            }
            named_sync(2, 256);
            if (mtid < 16) {
                uint32_t a2 = 0;
#pragma unroll
                for (int u = 0; u < 2; u++) {
                    const float* pg = s_gu + u * 16 + mtid;
                    const float gb = rbf((pg[0] + pg[32]) + (pg[64] + pg[96]));
                    const float ub = rbf((pg[128] + pg[160]) + (pg[192] + pg[224]));
                    const float sg = rbf(gb / (1.f + __expf(-gb)));
                    const float a = sg * ub;
                    uint32_t ab = (uint32_t)__bfloat16_as_ushort(__float2bfloat16_rn(a));
                    if (ab == 0xFFFFu) ab = 0x7FFFu;
                    a2 |= ab << (16 * u);
                }
                asm volatile("st.relaxed.gpu.global.u32 [%0], %1;" ::"l"(g_act + blockIdx.x * 16 + mtid), "r"(a2) : "memory");
            }
            if (mtid == 0) TSTAMP0(3, 2);
        }
        if (downer) {
            uint32_t av[7];
            {
                int spins = 0;
                while (true) {
                    bool ok = true;
#pragma unroll
                    for (int j = 0; j < 7; j++) {
                        asm volatile("ld.relaxed.gpu.global.u32 %0, [%1];" : "=r"(av[j]) : "l"(g_act + mtid + 256 * j) : "memory");
                        ok = ok && ((av[j] & 0xFFFFu) != 0xFFFFu) && ((av[j] >> 16) != 0xFFFFu);
                    }
                    if (mtid < 2) ok = ok && (ld_acquire(&g_sflag[(mtid ? idx[1] : idx[0]) >> 6]) >= 8u);
                    if (__all_sync(0xffffffffu, ok) || ++spins > (1 << 20)) break;
                    __nanosleep(20);
                }
            }
            if (mtid == 0) TSTAMP0(3, 3);
            mbar_wait(dbar, 0);
            float acc[16];
#pragma unroll
            for (int i = 0; i < 16; i++) acc[i] = 0.f;
#pragma unroll
            for (int j = 0; j < 7; j++) {
                const uint4 w = *(const uint4*)(sp + (4 + (j >> 2)) * KF_CH_S + (j & 3) * 4096 + mtid * 16);
                const float a0 = bf_lo(av[j]), a1 = bf_hi(av[j]);
                const uint32_t ww[4] = {w.x, w.y, w.z, w.w};
#pragma unroll
                for (int q = 0; q < 4; q++) {
                    const float wl = bf_lo(ww[q]), wh = bf_hi(ww[q]);
                    acc[2 * q] = fmaf(a0, wl, acc[2 * q]); acc[2 * q + 1] = fmaf(a0, wh, acc[2 * q + 1]);
                    acc[8 + 2 * q] = fmaf(a1, wl, acc[8 + 2 * q]); acc[8 + 2 * q + 1] = fmaf(a1, wh, acc[8 + 2 * q + 1]);
                }
            }
            KF_STEP(16, 8) KF_STEP(8, 4) KF_STEP(4, 2) KF_STEP(2, 1)
            acc[0] += __shfl_xor_sync(0xffffffffu, acc[0], 1);
            if ((lane & 1) == 0) {
                const int v = ((lane & 16) ? 8 : 0) + ((lane & 8) ? 4 : 0) + ((lane & 4) ? 2 : 0) + ((lane & 2) ? 1 : 0);
                s_red[mwarp * 16 + v] = acc[0];
            }
            named_sync(2, 256);
            if (mtid < 16) {
                const int u = mtid >> 3;
                float y = 0.f;
#pragma unroll
                for (int w = 0; w < 8; w++) y += s_red[w * 16 + mtid];
                const float sig = rbf(1.f / (1.f + __expf(-(u ? rv[1] : rv[0]))));
                const float xn = rbf(rbf(hfin - (u ? mean[1] : mean[0])) * (u ? inv[1] : inv[0]));
                const float ov = hfin + rbf(xn + rbf(rbf(y) * sig));
                out[(size_t)(u ? idx[1] : idx[0]) * DM + c0 + (mtid & 7)] = __float2bfloat16_rn(ov);
            }
            if (blockIdx.x == gridDim.x - 1 && mtid == 0) g_epoch = g_epoch + 1u;
            if (mtid == 0) TSTAMP0(3, 4);
        }
    }
}

typedef CUresult (*PFN_encodeTiled)(CUtensorMap*, CUtensorMapDataType, cuuint32_t, void*, const cuuint64_t*, const cuuint64_t*,
                                    const cuuint32_t*, const cuuint32_t*, CUtensorMapInterleave, CUtensorMapSwizzle,
                                    CUtensorMapL2promotion, CUtensorMapFloatOOBfill);

void make_map(PFN_encodeTiled enc, CUtensorMap* m, const void* ptr, uint64_t cols, uint64_t rows, uint32_t bcols, uint32_t brows) {
    cuuint64_t dims[2] = {cols, rows};
    cuuint64_t strides[1] = {cols * 2};
    cuuint32_t box[2] = {bcols, brows};
    cuuint32_t es[2] = {1, 1};
    enc(m, CU_TENSOR_MAP_DATA_TYPE_BFLOAT16, 2, const_cast<void*>(ptr), dims, strides, box, es, CU_TENSOR_MAP_INTERLEAVE_NONE,
        CU_TENSOR_MAP_SWIZZLE_128B, CU_TENSOR_MAP_L2_PROMOTION_L2_256B, CU_TENSOR_MAP_FLOAT_OOB_FILL_NONE);
}

void make_map3(PFN_encodeTiled enc, CUtensorMap* m, const void* ptr, uint64_t d0, uint64_t rows, uint64_t d2, uint64_t row_stride_bytes,
               uint64_t d2_stride_bytes, uint32_t b0, uint32_t b1, uint32_t b2) {
    cuuint64_t dims[3] = {d0, rows, d2};
    cuuint64_t strides[2] = {row_stride_bytes, d2_stride_bytes};
    cuuint32_t box[3] = {b0, b1, b2};
    cuuint32_t es[3] = {1, 1, 1};
    enc(m, CU_TENSOR_MAP_DATA_TYPE_BFLOAT16, 3, const_cast<void*>(ptr), dims, strides, box, es, CU_TENSOR_MAP_INTERLEAVE_NONE,
        CU_TENSOR_MAP_SWIZZLE_128B, CU_TENSOR_MAP_L2_PROMOTION_L2_256B, CU_TENSOR_MAP_FLOAT_OOB_FILL_NONE);
}

void make_map_plain(PFN_encodeTiled enc, CUtensorMap* m, const void* ptr, uint64_t cols, uint64_t rows, uint32_t bcols, uint32_t brows) {
    cuuint64_t dims[2] = {cols, rows};
    cuuint64_t strides[1] = {cols * 2};
    cuuint32_t box[2] = {bcols, brows};
    cuuint32_t es[2] = {1, 1};
    enc(m, CU_TENSOR_MAP_DATA_TYPE_BFLOAT16, 2, const_cast<void*>(ptr), dims, strides, box, es, CU_TENSOR_MAP_INTERLEAVE_NONE,
        CU_TENSOR_MAP_SWIZZLE_NONE, CU_TENSOR_MAP_L2_PROMOTION_NONE, CU_TENSOR_MAP_FLOAT_OOB_FILL_NONE);
}

template <typename... KArgs, typename... Args>
void launch(void (*kern)(KArgs...), int grid, int block, int smem, bool pdl, Args... args) {
    cudaLaunchConfig_t cfg = {};
    cfg.gridDim = dim3(grid);
    cfg.blockDim = dim3(block);
    cfg.dynamicSmemBytes = smem;
    cfg.stream = cudaStreamPerThread;
    cudaLaunchAttribute at[1];
    at[0].id = cudaLaunchAttributeProgrammaticStreamSerialization;
    at[0].val.programmaticStreamSerializationAllowed = 1;
    cfg.attrs = at;
    cfg.numAttrs = pdl ? 1 : 0;
    cudaLaunchKernelEx(&cfg, kern, KArgs(args)...);
}

}

extern "C" void kernel_launch(void* const* d_in, const int* in_sizes, int n_in, void* d_out, int out_size) {
    const __nv_bfloat16* x = (const __nv_bfloat16*)d_in[0];
    const __nv_bfloat16* wqkv = (const __nv_bfloat16*)d_in[1];
    const __nv_bfloat16* wo = (const __nv_bfloat16*)d_in[2];
    const __nv_bfloat16* w_r = (const __nv_bfloat16*)d_in[4];
    const __nv_bfloat16* w_gate = (const __nv_bfloat16*)d_in[5];
    const __nv_bfloat16* w_up = (const __nv_bfloat16*)d_in[6];
    const __nv_bfloat16* w_down = (const __nv_bfloat16*)d_in[7];
    __nv_bfloat16* out = (__nv_bfloat16*)d_out;

    static PFN_encodeTiled enc = nullptr;
    static void* g_o_ptr = nullptr;
    if (!enc) {
        cudaDriverEntryPointQueryResult qres;
        void* fn = nullptr;
        cudaGetDriverEntryPoint("cuTensorMapEncodeTiled", &fn, cudaEnableDefault, &qres);
        enc = (PFN_encodeTiled)fn;
        cudaGetSymbolAddress(&g_o_ptr, g_o);
        cudaFuncSetAttribute(k1_qkv, cudaFuncAttributeMaxDynamicSharedMemorySize, K1_SMEM);
        cudaFuncSetAttribute(kf_main, cudaFuncAttributeMaxDynamicSharedMemorySize, KF_SMEM);
    }
    CUtensorMap tm_x, tm_w, tm_o, tm_wo, tm_g, tm_u, tm_d;
    make_map_plain(enc, &tm_d, w_down, DM, FF, 8, 256);
    make_map_plain(enc, &tm_g, w_gate, FF, DM, 16, 128);
    make_map_plain(enc, &tm_u, w_up, FF, DM, 16, 128);
    make_map(enc, &tm_x, x, DM, SEQ, 64, 128);
    make_map3(enc, &tm_w, wqkv, DM, DM, 3, 3 * DM * 2, DM * 2, 64, 64, 3);
    make_map3(enc, &tm_o, g_o_ptr, 64, SEQ, 8, DM * 2, 128, 64, 64, 1);
    make_map3(enc, &tm_wo, wo, 64, DM, 8, DM * 2, 128, 64, 64, 2);

    const bool pdl = true;
    launch(k1_qkv, 128, 544, K1_SMEM, false, tm_x, tm_w, x);
    launch(kf_main, 128, 512, KF_SMEM, pdl, tm_o, tm_wo, tm_g, tm_u, tm_d, x, wo, w_r, w_gate, w_up, w_down, out);
}
```

```cpp
#include <cuda_runtime.h>
#include <cuda_bf16.h>
#include <cuda.h>
#include <stdint.h>

namespace {

constexpr int SEQ = 2048, DM = 512, NH = 32, FF = 1792;

__device__ __align__(1024) uint8_t g_q[NH * 2 * SEQ * 16];
__device__ __align__(1024) uint8_t g_kv[NH * 8 * 16384];
__device__ float g_norm[16 * NH * 3];
__device__ __align__(1024) __nv_bfloat16 g_o[SEQ * DM];
__device__ __align__(1024) __nv_bfloat16 g_h[SEQ * DM];
__device__ __align__(16) uint4 g_cand[64];
__device__ unsigned int g_oflag[32 * 32];
__device__ unsigned int g_hflag[32];
__device__ unsigned int g_sflag[32];
__device__ unsigned int g_act[FF];
__device__ unsigned int g_epoch;
__device__ __align__(16) float4 g_ln1[SEQ];
__device__ __align__(16) float4 g_part[32 * 8 * 64];

#define TSTAMP(K, I)
#define TSTAMP0(K, I)
__device__ __forceinline__ uint32_t smem_u32(const void* p) { return (uint32_t)__cvta_generic_to_shared(p); }
__device__ __forceinline__ void wg_fence() { asm volatile("wgmma.fence.sync.aligned;" ::: "memory"); }
__device__ __forceinline__ void wg_commit() { asm volatile("wgmma.commit_group.sync.aligned;" ::: "memory"); }
template <int N> __device__ __forceinline__ void wg_wait() { asm volatile("wgmma.wait_group.sync.aligned %0;" ::"n"(N) : "memory"); }
template <int N> __device__ __forceinline__ void fence_regs(float (&r)[N]) {
#pragma unroll
    for (int i = 0; i < N; i++) asm volatile("" : "+f"(r[i])::"memory");
}
__device__ __forceinline__ uint64_t make_desc(uint32_t addr, uint32_t lbo, uint32_t sbo, uint32_t swz) {
    uint64_t d = 0;
    d |= (uint64_t)((addr & 0x3FFFF) >> 4);
    d |= (uint64_t)((lbo & 0x3FFFF) >> 4) << 16;
    d |= (uint64_t)((sbo & 0x3FFFF) >> 4) << 32;
    d |= (uint64_t)swz << 62;
    return d;
}
__device__ __forceinline__ void mbar_init(uint32_t bar, uint32_t cnt) {
    asm volatile("mbarrier.init.shared::cta.b64 [%0], %1;" ::"r"(bar), "r"(cnt) : "memory");
}
__device__ __forceinline__ void mbar_expect_tx(uint32_t bar, uint32_t bytes) {
    asm volatile("mbarrier.arrive.expect_tx.shared::cta.b64 _, [%0], %1;" ::"r"(bar), "r"(bytes) : "memory");
}
__device__ __forceinline__ void mbar_arrive(uint32_t bar) {
    asm volatile("mbarrier.arrive.shared::cta.b64 _, [%0];" ::"r"(bar) : "memory");
}
__device__ __forceinline__ void mbar_wait(uint32_t bar, uint32_t parity) {
    asm volatile(
        "{\n.reg .pred p;\nWAIT_%=:\n"
        "mbarrier.try_wait.parity.shared::cta.b64 p, [%0], %1;\n"
        "@p bra DONE_%=;\nbra WAIT_%=;\nDONE_%=:\n}\n" ::"r"(bar), "r"(parity) : "memory");
}
__device__ __forceinline__ void bulk_g2s(uint32_t dst, const void* src, uint32_t bytes, uint32_t bar) {
    asm volatile("cp.async.bulk.shared::cluster.global.mbarrier::complete_tx::bytes [%0], [%1], %2, [%3];" ::"r"(dst),
                 "l"(src), "r"(bytes), "r"(bar) : "memory");
}
__device__ __forceinline__ void bulk_s2g(void* dst, uint32_t src, uint32_t bytes) {
    asm volatile("cp.async.bulk.global.shared::cta.bulk_group [%0], [%1], %2;" ::"l"(dst), "r"(src), "r"(bytes) : "memory");
}
__device__ __forceinline__ void tma_load_2d(uint32_t dst, const CUtensorMap* tm, int c0, int c1, uint32_t bar) {
    asm volatile("cp.async.bulk.tensor.2d.shared::cluster.global.mbarrier::complete_tx::bytes [%0], [%1, {%3, %4}], [%2];" ::"r"(dst),
                 "l"(tm), "r"(bar), "r"(c0), "r"(c1) : "memory");
}
__device__ __forceinline__ void tma_load_3d(uint32_t dst, const CUtensorMap* tm, int c0, int c1, int c2, uint32_t bar) {
    asm volatile("cp.async.bulk.tensor.3d.shared::cluster.global.mbarrier::complete_tx::bytes [%0], [%1, {%3, %4, %5}], [%2];" ::"r"(dst),
                 "l"(tm), "r"(bar), "r"(c0), "r"(c1), "r"(c2) : "memory");
}
__device__ __forceinline__ void tma_load_2d_mc(uint32_t dst, const CUtensorMap* tm, int c0, int c1, uint32_t bar, uint16_t mask) {
    asm volatile("cp.async.bulk.tensor.2d.shared::cluster.global.mbarrier::complete_tx::bytes.multicast::cluster [%0], [%1, {%3, %4}], [%2], %5;" ::"r"(dst),
                 "l"(tm), "r"(bar), "r"(c0), "r"(c1), "h"(mask) : "memory");
}
__device__ __forceinline__ void mbar_arrive_cluster(uint32_t bar, uint32_t cta) {
    asm volatile("{\n.reg .b32 ra;\nmapa.shared::cluster.u32 ra, %0, %1;\nmbarrier.arrive.release.cluster.shared::cluster.b64 _, [ra];\n}" ::"r"(bar), "r"(cta) : "memory");
}
__device__ __forceinline__ void cluster_sync() {
    asm volatile("barrier.cluster.arrive.release.aligned;\nbarrier.cluster.wait.acquire.aligned;" ::: "memory");
}
__device__ __forceinline__ void prefetch_l2(const void* p, uint32_t bytes) {
    asm volatile("cp.async.bulk.prefetch.L2.global [%0], %1;" ::"l"(p), "r"(bytes) : "memory");
}
__device__ __forceinline__ void fence_proxy_async() { asm volatile("fence.proxy.async.shared::cta;" ::: "memory"); }
__device__ __forceinline__ void fence_barrier_init() { asm volatile("fence.mbarrier_init.release.cluster;" ::: "memory"); }
__device__ __forceinline__ void pdl_launch() { asm volatile("griddepcontrol.launch_dependents;" ::: "memory"); }
__device__ __forceinline__ void pdl_wait() { asm volatile("griddepcontrol.wait;" ::: "memory"); }
__device__ __forceinline__ void named_sync(int id, int n) { asm volatile("bar.sync %0, %1;" ::"r"(id), "r"(n) : "memory"); }
__device__ __forceinline__ void named_arrive(int id, int n) { asm volatile("bar.arrive %0, %1;" ::"r"(id), "r"(n) : "memory"); }

__device__ __forceinline__ float ex2f(float x) { float y; asm("ex2.approx.ftz.f32 %0, %1;" : "=f"(y) : "f"(x)); return y; }
__device__ __forceinline__ uint32_t pack_bf16(float lo, float hi) {
    uint32_t r; asm("cvt.rn.bf16x2.f32 %0, %1, %2;" : "=r"(r) : "f"(hi), "f"(lo)); return r;
}
__device__ __forceinline__ float bf_lo(uint32_t v) { return __uint_as_float(v << 16); }
__device__ __forceinline__ float bf_hi(uint32_t v) { return __uint_as_float(v & 0xFFFF0000u); }
__device__ __forceinline__ float rbf(float x) { return __bfloat162float(__float2bfloat16_rn(x)); }
__device__ __forceinline__ uint32_t fma_bf16x2(uint32_t a, uint32_t b, uint32_t c) {
    uint32_t r; asm("fma.rn.bf16x2 %0, %1, %2, %3;" : "=r"(r) : "r"(a), "r"(b), "r"(c)); return r;
}
__device__ __forceinline__ void stmatrix_x4(uint32_t addr, uint32_t r0, uint32_t r1, uint32_t r2, uint32_t r3) {
    asm volatile("stmatrix.sync.aligned.m8n8.x4.shared.b16 [%0], {%1, %2, %3, %4};" ::"r"(addr), "r"(r0), "r"(r1), "r"(r2), "r"(r3) : "memory");
}
__device__ __forceinline__ void stmatrix_x4_trans(uint32_t addr, uint32_t r0, uint32_t r1, uint32_t r2, uint32_t r3) {
    asm volatile("stmatrix.sync.aligned.m8n8.x4.trans.shared.b16 [%0], {%1, %2, %3, %4};" ::"r"(addr), "r"(r0), "r"(r1), "r"(r2), "r"(r3) : "memory");
}

__device__ __forceinline__ void wgmma_k1_n136(float (&d)[68], uint64_t desca, uint64_t descb, int scale_d) {
  asm volatile("{\n.reg .pred p;\nsetp.ne.b32 p, %70, 0;\n"
    "wgmma.mma_async.sync.aligned.m64n136k16.f32.bf16.bf16 "
    "{%0, %1, %2, %3, %4, %5, %6, %7, %8, %9, %10, %11, %12, %13, %14, %15, %16, %17, %18, %19, %20, %21, %22, %23, %24, %25, %26, %27, %28, %29, %30, %31, %32, %33, %34, %35, %36, %37, %38, %39, %40, %41, %42, %43, %44, %45, %46, %47, %48, %49, %50, %51, %52, %53, %54, %55, %56, %57, %58, %59, %60, %61, %62, %63, %64, %65, %66, %67}, "
    "%68, %69, p, 1, 1, 1, 0;\n}\n"
    : "+f"(d[0]), "+f"(d[1]), "+f"(d[2]), "+f"(d[3]), "+f"(d[4]), "+f"(d[5]), "+f"(d[6]), "+f"(d[7]), "+f"(d[8]), "+f"(d[9]), "+f"(d[10]), "+f"(d[11]), "+f"(d[12]), "+f"(d[13]), "+f"(d[14]), "+f"(d[15]), "+f"(d[16]), "+f"(d[17]), "+f"(d[18]), "+f"(d[19]), "+f"(d[20]), "+f"(d[21]), "+f"(d[22]), "+f"(d[23]), "+f"(d[24]), "+f"(d[25]), "+f"(d[26]), "+f"(d[27]), "+f"(d[28]), "+f"(d[29]), "+f"(d[30]), "+f"(d[31]), "+f"(d[32]), "+f"(d[33]), "+f"(d[34]), "+f"(d[35]), "+f"(d[36]), "+f"(d[37]), "+f"(d[38]), "+f"(d[39]), "+f"(d[40]), "+f"(d[41]), "+f"(d[42]), "+f"(d[43]), "+f"(d[44]), "+f"(d[45]), "+f"(d[46]), "+f"(d[47]), "+f"(d[48]), "+f"(d[49]), "+f"(d[50]), "+f"(d[51]), "+f"(d[52]), "+f"(d[53]), "+f"(d[54]), "+f"(d[55]), "+f"(d[56]), "+f"(d[57]), "+f"(d[58]), "+f"(d[59]), "+f"(d[60]), "+f"(d[61]), "+f"(d[62]), "+f"(d[63]), "+f"(d[64]), "+f"(d[65]), "+f"(d[66]), "+f"(d[67])
    : "l"(desca), "l"(descb), "r"(scale_d));
}
__device__ __forceinline__ void wgmma_qk_n64(float (&d)[32], uint32_t a0, uint32_t a1, uint32_t a2, uint32_t a3, uint64_t descb) {
  asm volatile("{\n.reg .pred p;\nsetp.ne.b32 p, 0, 0;\n"
    "wgmma.mma_async.sync.aligned.m64n64k16.f32.bf16.bf16 "
    "{%0, %1, %2, %3, %4, %5, %6, %7, %8, %9, %10, %11, %12, %13, %14, %15, %16, %17, %18, %19, %20, %21, %22, %23, %24, %25, %26, %27, %28, %29, %30, %31}, "
    "{%32, %33, %34, %35}, %36, p, 1, 1, 0;\n}\n"
    : "=f"(d[0]), "=f"(d[1]), "=f"(d[2]), "=f"(d[3]), "=f"(d[4]), "=f"(d[5]), "=f"(d[6]), "=f"(d[7]), "=f"(d[8]), "=f"(d[9]), "=f"(d[10]), "=f"(d[11]), "=f"(d[12]), "=f"(d[13]), "=f"(d[14]), "=f"(d[15]), "=f"(d[16]), "=f"(d[17]), "=f"(d[18]), "=f"(d[19]), "=f"(d[20]), "=f"(d[21]), "=f"(d[22]), "=f"(d[23]), "=f"(d[24]), "=f"(d[25]), "=f"(d[26]), "=f"(d[27]), "=f"(d[28]), "=f"(d[29]), "=f"(d[30]), "=f"(d[31])
    : "r"(a0), "r"(a1), "r"(a2), "r"(a3), "l"(descb));
}
__device__ __forceinline__ void wgmma_pv_n24(float (&d)[12], uint32_t a0, uint32_t a1, uint32_t a2, uint32_t a3, uint64_t descb) {
  asm volatile("{\n.reg .pred p;\nsetp.eq.b32 p, 0, 0;\n"
    "wgmma.mma_async.sync.aligned.m64n24k16.f32.bf16.bf16 "
    "{%0, %1, %2, %3, %4, %5, %6, %7, %8, %9, %10, %11}, "
    "{%12, %13, %14, %15}, %16, p, 1, 1, 1;\n}\n"
    : "+f"(d[0]), "+f"(d[1]), "+f"(d[2]), "+f"(d[3]), "+f"(d[4]), "+f"(d[5]), "+f"(d[6]), "+f"(d[7]), "+f"(d[8]), "+f"(d[9]), "+f"(d[10]), "+f"(d[11])
    : "r"(a0), "r"(a1), "r"(a2), "r"(a3), "l"(descb));
}
__device__ __forceinline__ void wgmma_k3_n64(float (&d)[32], uint64_t desca, uint64_t descb, int scale_d) {
  asm volatile("{\n.reg .pred p;\nsetp.ne.b32 p, %34, 0;\n"
    "wgmma.mma_async.sync.aligned.m64n64k16.f32.bf16.bf16 "
    "{%0, %1, %2, %3, %4, %5, %6, %7, %8, %9, %10, %11, %12, %13, %14, %15, %16, %17, %18, %19, %20, %21, %22, %23, %24, %25, %26, %27, %28, %29, %30, %31}, "
    "%32, %33, p, 1, 1, 0, 1;\n}\n"
    : "+f"(d[0]), "+f"(d[1]), "+f"(d[2]), "+f"(d[3]), "+f"(d[4]), "+f"(d[5]), "+f"(d[6]), "+f"(d[7]), "+f"(d[8]), "+f"(d[9]), "+f"(d[10]), "+f"(d[11]), "+f"(d[12]), "+f"(d[13]), "+f"(d[14]), "+f"(d[15]), "+f"(d[16]), "+f"(d[17]), "+f"(d[18]), "+f"(d[19]), "+f"(d[20]), "+f"(d[21]), "+f"(d[22]), "+f"(d[23]), "+f"(d[24]), "+f"(d[25]), "+f"(d[26]), "+f"(d[27]), "+f"(d[28]), "+f"(d[29]), "+f"(d[30]), "+f"(d[31])
    : "l"(desca), "l"(descb), "r"(scale_d));
}
__device__ __forceinline__ void wgmma_bias_n40(float (&d)[32], uint64_t desca, uint64_t descb) {
  asm volatile("{\n.reg .pred p;\nsetp.eq.b32 p, 0, 0;\n"
    "wgmma.mma_async.sync.aligned.m64n40k16.f32.bf16.bf16 "
    "{%0, %1, %2, %3, %4, %5, %6, %7, %8, %9, %10, %11, %12, %13, %14, %15, %16, %17, %18, %19}, "
    "%20, %21, p, 1, 1, 0, 0;\n}\n"
    : "+f"(d[0]), "+f"(d[1]), "+f"(d[2]), "+f"(d[3]), "+f"(d[4]), "+f"(d[5]), "+f"(d[6]), "+f"(d[7]), "+f"(d[8]), "+f"(d[9]), "+f"(d[10]), "+f"(d[11]), "+f"(d[12]), "+f"(d[13]), "+f"(d[14]), "+f"(d[15]), "+f"(d[16]), "+f"(d[17]), "+f"(d[18]), "+f"(d[19])
    : "l"(desca), "l"(descb));
}

constexpr int K1_XS = 17408;
constexpr int K1_WS = 24576;
constexpr int K1_ST = K1_XS + K1_WS;
constexpr int K1_NST = 5;
constexpr int K1_OFF_MISC = K1_NST * K1_ST;
constexpr int K1_SMEM = K1_OFF_MISC + 2048 + 1024;
constexpr float QSCALE = 0.25f * 1.4426950408889634f;

__global__ void __launch_bounds__(544, 1)
k1_qkv(const __grid_constant__ CUtensorMap tm_x, const __grid_constant__ CUtensorMap tm_w, const __nv_bfloat16* __restrict__ x) {
    extern __shared__ uint8_t smem_raw[];
    const uint32_t sraw = smem_u32(smem_raw);
    const uint32_t sb = (sraw + 1023) & ~1023u;
    uint8_t* sp = smem_raw + (sb - sraw);
    const uint32_t full = sb + K1_OFF_MISC;
    const uint32_t empty = full + 64;
    float* s_mr = (float*)(sp + K1_OFF_MISC + 256);

    const int tid = threadIdx.x, warp = tid >> 5, lane = tid & 31;
    const int mt = blockIdx.x >> 3, nt = blockIdx.x & 7;
    if (tid == 0) TSTAMP0(0, 0);
    pdl_launch();
    if (tid == 512) {
        for (int i = 0; i < K1_NST; i++) { mbar_init(full + 8 * i, 1); mbar_init(empty + 8 * i, 3); }
        fence_barrier_init();
        for (int kb = 0; kb < K1_NST; kb++) {
            mbar_expect_tx(full + 8 * kb, 16384 + K1_WS);
            tma_load_2d(sb + kb * K1_ST, &tm_x, kb * 64, mt * 128, full + 8 * kb);
            tma_load_3d(sb + kb * K1_ST + K1_XS, &tm_w, nt * 64, kb * 64, 0, full + 8 * kb);
        }
    }
    if (tid < K1_NST * 64) {
        *(uint4*)(sp + (tid >> 6) * K1_ST + 16384 + (tid & 63) * 16) =
            make_uint4(0x3F803F80u, 0x3F803F80u, 0x3F803F80u, 0x3F803F80u);
    }
    fence_proxy_async();
    __syncthreads();

    if (warp == 16) {
        if (lane == 0) {
            for (int kb = K1_NST; kb < 8; kb++) {
                const int s = kb % K1_NST;
                mbar_wait(empty + 8 * s, 0);
                mbar_expect_tx(full + 8 * s, 16384 + K1_WS);
                tma_load_2d(sb + s * K1_ST, &tm_x, kb * 64, mt * 128, full + 8 * s);
                tma_load_3d(sb + s * K1_ST + K1_XS, &tm_w, nt * 64, kb * 64, 0, full + 8 * s);
            }
        }
        __syncwarp();
        if (lane < FF / 128) g_act[blockIdx.x * (FF / 128) + lane] = 0xFFFFFFFFu;
        for (int i = lane; i < 128; i += 32) g_part[blockIdx.x * 128 + i] = make_float4(0.f, 0.f, 0.f, 0.f);
        if (blockIdx.x == 1) { g_cand[lane] = make_uint4(0, 0, 0, 0); g_cand[lane + 32] = make_uint4(0, 0, 0, 0); g_hflag[lane] = 0; g_sflag[lane] = 0; }
        if (blockIdx.x == 2) for (int i = lane; i < 1024; i += 32) g_oflag[i] = 0;
    } else if (warp >= 12) {
        const int r = tid - 384;
        const unsigned int tag = *(volatile unsigned int*)&g_epoch + 1u;
        {
            const int row = mt * 128 + nt * 16 + (r >> 3);
            const uint4* xp = (const uint4*)(x + (size_t)row * DM) + (r & 7);
            uint4 v[8];
#pragma unroll
            for (int i = 0; i < 8; i++) v[i] = __ldg(xp + i * 8);
            float s1 = 0.f;
#pragma unroll
            for (int i = 0; i < 8; i++)
                s1 += ((bf_lo(v[i].x) + bf_hi(v[i].x)) + (bf_lo(v[i].y) + bf_hi(v[i].y))) + ((bf_lo(v[i].z) + bf_hi(v[i].z)) + (bf_lo(v[i].w) + bf_hi(v[i].w)));
#pragma unroll
            for (int o = 1; o < 8; o <<= 1) s1 += __shfl_xor_sync(0xffffffffu, s1, o);
            const float mean = s1 * (1.f / DM);
            float q0 = 0.f, q1 = 0.f;
#pragma unroll
            for (int i = 0; i < 8; i++) {
                const uint32_t w[4] = {v[i].x, v[i].y, v[i].z, v[i].w};
#pragma unroll
                for (int j = 0; j < 4; j++) {
                    const float a = bf_lo(w[j]) - mean, b = bf_hi(w[j]) - mean;
                    q0 = fmaf(a, a, q0); q1 = fmaf(b, b, q1);
                }
            }
            float q = q0 + q1;
#pragma unroll
            for (int o = 1; o < 8; o <<= 1) q += __shfl_xor_sync(0xffffffffu, q, o);
            const float den = rbf(sqrtf(rbf(rbf(q * (1.f / DM)) + 1e-5f)));
            if ((r & 7) == 0)
                asm volatile("st.relaxed.gpu.global.v4.f32 [%0], {%1, %2, %3, %4};" ::"l"(g_ln1 + row), "f"(rbf(mean)), "f"(1.f / den),
                             "f"(__uint_as_float(tag)), "f"(0.f) : "memory");
        }
        if (r == 0) TSTAMP0(0, 6);
        {
            float4 v;
            int spins = 0;
            do {
                asm volatile("ld.relaxed.gpu.global.v4.f32 {%0, %1, %2, %3}, [%4];" : "=f"(v.x), "=f"(v.y), "=f"(v.z), "=f"(v.w) : "l"(g_ln1 + mt * 128 + r) : "memory");
            } while (__float_as_uint(v.z) != tag && ++spins < (1 << 22));
            s_mr[(r >> 1) * 4 + (r & 1)] = v.x;
            s_mr[(r >> 1) * 4 + 2 + (r & 1)] = v.y;
        }
        if (r == 0) TSTAMP0(0, 7);
        named_arrive(1, 512);
    } else {
        const int part = warp >> 2, hw = warp & 3;
        float acc[68];
#pragma unroll
        for (int i = 0; i < 68; i++) acc[i] = 0.f;
        fence_regs(acc);
#pragma unroll 1
        for (int kb = 0; kb < 8; kb++) {
            const int s = kb % K1_NST;
            mbar_wait(full + 8 * s, (kb / K1_NST) & 1);
            const uint64_t da = make_desc(sb + s * K1_ST + K1_XS + part * 8192, 1024, 1024, 1);
            const uint64_t db = make_desc(sb + s * K1_ST, 16, 1024, 1);
            wg_fence();
#pragma unroll
            for (int k = 0; k < 4; k++) wgmma_k1_n136(acc, da + k * 128, db + k * 2, (kb | k) != 0);
            wg_commit();
            if (kb > 0 && kb <= 8 - K1_NST) {
                wg_wait<1>();
                if ((tid & 127) == 0) mbar_arrive(empty + 8 * (kb - 1));
            }
        }
        wg_wait<0>();
        fence_regs(acc);
        if (tid == 0) TSTAMP0(0, 1);
        named_sync(1, 512);
        if (tid == 0) TSTAMP0(0, 2);

        const int t = lane & 3;
        const float cs0 = acc[64], cs1 = acc[66];
        const float sc = (part == 0) ? QSCALE : 1.f;
        const uint32_t stg = sb + (hw >> 1) * K1_ST + K1_XS + part * 8192 + (hw & 1) * 4096;
        const uint32_t st_addr = stg + ((lane >> 3) & 1) * 2048 + ((lane >> 4) * 8 + (lane & 7)) * 16;
#pragma unroll
        for (int j = 0; j < 16; j += 2) {
            uint32_t rr[4];
#pragma unroll
            for (int u = 0; u < 2; u++) {
                const int jj = j + u;
                const float4 mr = *(const float4*)(s_mr + (4 * jj + t) * 4);
                const float2 m2 = make_float2(mr.x, mr.y);
                const float ra = mr.z * sc, rb = mr.w * sc;
                rr[2 * u] = pack_bf16((acc[4 * jj] - m2.x * cs0) * ra, (acc[4 * jj + 1] - m2.y * cs0) * rb);
                rr[2 * u + 1] = pack_bf16((acc[4 * jj + 2] - m2.x * cs1) * ra, (acc[4 * jj + 3] - m2.y * cs1) * rb);
            }
            stmatrix_x4_trans(st_addr + j * 128, rr[0], rr[1], rr[2], rr[3]);
        }
        fence_proxy_async();
        __syncwarp();
        if (tid == 0) TSTAMP0(0, 4);
        const int head = nt * 4 + hw;
        if (lane == 0) {
            uint8_t* dst;
            uint32_t hstride;
            if (part == 0) { dst = g_q + (size_t)head * 65536 + mt * 2048; hstride = 32768; }
            else { dst = g_kv + (size_t)head * 131072 + (mt >> 1) * 16384 + (part - 1) * 8192 + (mt & 1) * 2048; hstride = 4096; }
            bulk_s2g(dst, stg, 2048);
            bulk_s2g(dst + hstride, stg + 2048, 2048);
            asm volatile("cp.async.bulk.commit_group;" ::: "memory");
        }
        float nmax = 0.f;
#pragma unroll
        for (int i = 0; i < 4; i++) {
            const int tok = lane + 32 * i;
            const uint4 a = *(const uint4*)(sp + (stg - sb) + tok * 16);
            const uint4 b = *(const uint4*)(sp + (stg - sb) + 2048 + tok * 16);
            uint32_t n0 = fma_bf16x2(a.x, a.x, 0u), n1 = fma_bf16x2(b.x, b.x, 0u);
            n0 = fma_bf16x2(a.y, a.y, n0); n1 = fma_bf16x2(b.y, b.y, n1);
            n0 = fma_bf16x2(a.z, a.z, n0); n1 = fma_bf16x2(b.z, b.z, n1);
            n0 = fma_bf16x2(a.w, a.w, n0); n1 = fma_bf16x2(b.w, b.w, n1);
            const float n2 = ((bf_lo(n0) + bf_hi(n0)) + (bf_lo(n1) + bf_hi(n1))) * 1.125f;
            nmax = (n2 > nmax || n2 != n2) ? n2 : nmax;
        }
#pragma unroll
        for (int o = 16; o > 0; o >>= 1) {
            const float v = __shfl_xor_sync(0xffffffffu, nmax, o);
            nmax = (v > nmax || v != v) ? v : nmax;
        }
        if (tid == 0) TSTAMP0(0, 5);
        if (lane == 0) {
            g_norm[(head * 16 + mt) * 3 + part] = nmax;
            asm volatile("cp.async.bulk.wait_group.read 0;" ::: "memory");
            if (tid == 0) TSTAMP0(0, 3);
        }
    }
}

#define POLL_NS 50
constexpr int KF_CH_G = 16384, KF_CH_S = 20480, KF_NCH = 8;
constexpr int KF_OFF_WO = KF_NCH * KF_CH_S;
constexpr int KF_OFF_MISC = KF_OFF_WO + 65536;
constexpr int KF_SMEM = KF_OFF_MISC + 1536 + 1024;

__device__ __forceinline__ uint32_t exp2_pair_poly(float t0, float t1) {
    const uint32_t w = __byte_perm(__float_as_uint(t0), __float_as_uint(t1), 0x5410);
    uint32_t z;
    asm("lop3.b32 %0, %1, %2, %3, 0xEA;" : "=r"(z) : "r"(w), "r"(0x007F007Fu), "r"(0x3F803F80u));
    uint32_t p = fma_bf16x2(0x3eab3eabu, z, 0xbc73bc73u);
    p = fma_bf16x2(p, z, 0x3f2f3f2fu);
    return p + w - z;
}
constexpr uint32_t KF_EMASK = 0x03FFu;
template <int LO, int HI>
__device__ __forceinline__ void softmax_part(const float (&s)[32], uint32_t (&p)[16]) {
#pragma unroll
    for (int i = LO; i < HI; i++) {
        if ((KF_EMASK >> i) & 1) p[i] = exp2_pair_poly(s[2 * i], s[2 * i + 1]);
        else p[i] = pack_bf16(ex2f(s[2 * i]), ex2f(s[2 * i + 1]));
    }
}
#define KF_PV(P, OFF)                                                                              \
    _Pragma("unroll") for (int kk = 0; kk < 4; kk++)                                               \
        wgmma_pv_n24(o, P[4 * kk], P[4 * kk + 1], P[4 * kk + 2], P[4 * kk + 3], dv + ((OFF) + kk * 16));

__device__ __forceinline__ uint32_t make_key(float r_bf16, int token) {
    const uint32_t u = __float_as_uint(r_bf16) >> 16;
    const uint32_t o = (u & 0x8000u) ? (~u & 0xFFFFu) : (u | 0x8000u);
    return (o << 16) | (uint32_t)(0xFFFF - token);
}
__device__ __forceinline__ float key_value(uint32_t k) {
    const uint32_t o = k >> 16;
    const uint32_t u = (o & 0x8000u) ? (o & 0x7FFFu) : (~o & 0xFFFFu);
    return __uint_as_float(u << 16);
}
__device__ __forceinline__ int key_token(uint32_t k) { return 0xFFFF - (int)(k & 0xFFFFu); }
__device__ __forceinline__ void warp_top2(uint32_t a, uint32_t b, uint32_t& k1, uint32_t& k2) {
    k1 = __reduce_max_sync(0xffffffffu, a > b ? a : b);
    const uint32_t a2 = (a == k1) ? 0u : a, b2 = (b == k1) ? 0u : b;
    k2 = __reduce_max_sync(0xffffffffu, a2 > b2 ? a2 : b2);
}
__device__ __forceinline__ unsigned int ld_acquire(const unsigned int* p) {
    unsigned int v; asm volatile("ld.acquire.gpu.global.u32 %0, [%1];" : "=r"(v) : "l"(p) : "memory"); return v;
}
__device__ __forceinline__ void red_release_add(unsigned int* p) {
    asm volatile("red.release.gpu.global.add.u32 [%0], 1;" ::"l"(p) : "memory");
}

__global__ void __launch_bounds__(512, 1)
kf_main(const __grid_constant__ CUtensorMap tm_o, const __grid_constant__ CUtensorMap tm_wo,
        const __grid_constant__ CUtensorMap tm_g, const __grid_constant__ CUtensorMap tm_u, const __grid_constant__ CUtensorMap tm_d,
        const __nv_bfloat16* __restrict__ x, const __nv_bfloat16* __restrict__ wo, const __nv_bfloat16* __restrict__ w_r,
        const __nv_bfloat16* __restrict__ w_gate, const __nv_bfloat16* __restrict__ w_up, const __nv_bfloat16* __restrict__ w_down,
        __nv_bfloat16* __restrict__ out) {
    extern __shared__ uint8_t smem_raw[];
    const uint32_t sraw = smem_u32(smem_raw);
    const uint32_t sb = (sraw + 1023) & ~1023u;
    uint8_t* sp = smem_raw + (sb - sraw);
    const uint32_t kvbar = sb + KF_OFF_MISC;
    const uint32_t wbar = kvbar + 64;
    const uint32_t obar = wbar + 64;
    const uint32_t gbar = obar + 64;
    const uint32_t dbar = gbar + 8;
    unsigned int* s_cnt = (unsigned int*)(sp + KF_OFF_MISC + 208);
    volatile unsigned int* s_order = (volatile unsigned int*)(sp + KF_OFF_MISC + 1056);
    uint32_t* s_key = (uint32_t*)(sp + KF_OFF_MISC + 256);
    float* s_gu = (float*)(sp + KF_OFF_WO + 49152 + 8192 + 4608);
    uint4* s_sel = (uint4*)(sp + KF_OFF_MISC + 1024);
    const int tid = threadIdx.x;
    const int head = blockIdx.x >> 2, quarter = blockIdx.x & 3;
    const int mt = blockIdx.x >> 2, nt = blockIdx.x & 3;
    if (tid == 0) TSTAMP0(1, 0);
    if (tid == 0) {
        for (int c = 0; c < 26; c++) mbar_init(kvbar + 8 * c, 1);
        for (int c = 0; c < 6; c++) s_cnt[c] = 0;
        fence_barrier_init();
        for (int kb = 0; kb < 4; kb++) {
            mbar_expect_tx(wbar + 8 * kb, 16384);
            tma_load_3d(sb + KF_OFF_WO + kb * 16384, &tm_wo, 0, kb * 64, nt * 2, wbar + 8 * kb);
        }
    }
    if (tid == 32) {
        prefetch_l2((const uint8_t*)wo + blockIdx.x * 4096, 4096);
        prefetch_l2((const uint8_t*)w_gate + blockIdx.x * 14336, 14336);
        prefetch_l2((const uint8_t*)w_up + blockIdx.x * 14336, 14336);
        prefetch_l2((const uint8_t*)w_down + blockIdx.x * 14336, 14336);
    }
    if (tid < 24) *(uint4*)(sp + KF_OFF_MISC + 1152 + tid * 16) =
        tid < 8 ? make_uint4(0x42FE4380u, 0x00003D80u, 0u, 0u) : (tid < 16 ? make_uint4(0x3F804380u, 0x00003E00u, 0u, 0u) : make_uint4(0u, 0u, 0u, 0u));
    for (int i = tid; i < KF_NCH * 256; i += 512)
        *(uint4*)(sp + (i >> 8) * KF_CH_S + 16384 + (i & 255) * 16) =
            make_uint4(0x3F803F80u, 0x3F803F80u, 0x3F803F80u, 0x3F803F80u);
    fence_proxy_async();
    __syncthreads();
    pdl_wait();
    if (tid == 0) TSTAMP0(1, 1);
    const uint8_t* kvsrc = g_kv + (size_t)head * (KF_NCH * KF_CH_G);
    if (tid == 32) {
        mbar_expect_tx(kvbar, KF_CH_G);
        bulk_g2s(sb, kvsrc, KF_CH_G, kvbar);
    }
    const int wg = tid >> 7, warp = (tid >> 5) & 3, lane = tid & 31, g = lane >> 2, t = lane & 3;
    if (tid < 32) {
        const int m16 = lane & 15;
        float kn = g_norm[(head * 16 + m16) * 3 + 1];
        float vn = g_norm[(head * 16 + m16) * 3 + 2];
        float qn = g_norm[(head * 16 + quarter * 4 + (lane & 3)) * 3 + 0];
        const bool bad = !(kn < 1e30f) || !(vn < 1e9f) || !(qn < 1e30f);
#pragma unroll
        for (int o = 8; o > 0; o >>= 1) {
            kn = fmaxf(kn, __shfl_xor_sync(0xffffffffu, kn, o));
            qn = fmaxf(qn, __shfl_xor_sync(0xffffffffu, qn, o));
        }
        const bool ok = __all_sync(0xffffffffu, !bad && (qn * kn <= 9000.f));
        if (lane == 0) s_cnt[4] = ok ? 1u : 0u;
    }
    uint32_t qn2[2][4];
#pragma unroll
    for (int ps = 0; ps < 2; ps++) {
        const uint8_t* qb = g_q + (size_t)head * 65536 + (quarter * 512 + ps * 256 + wg * 64 + warp * 16 + g) * 16 + t * 4;
        qn2[ps][0] = *(const uint32_t*)(qb);
        qn2[ps][1] = *(const uint32_t*)(qb + 128);
        qn2[ps][2] = *(const uint32_t*)(qb + 32768);
        qn2[ps][3] = *(const uint32_t*)(qb + 32768 + 128);
    }

    __syncthreads();
    const bool fast = __all_sync(0xffffffffu, s_cnt[4] != 0u);
    if (tid == 32) {
        for (int c = 1; c < KF_NCH; c++) {
            mbar_expect_tx(kvbar + 8 * c, KF_CH_G);
            bulk_g2s(sb + c * KF_CH_S, kvsrc + c * KF_CH_G, KF_CH_G, kvbar + 8 * c);
        }
    }
    if (tid == 0) TSTAMP0(1, 8);
    const uint64_t dbias_a = make_desc(sb + KF_OFF_MISC + 1152, 0, 0, 0);
    const uint64_t dbias_b = make_desc(sb + KF_OFF_MISC + 1280, 128, 0, 0);
    const uint64_t dk0 = make_desc(sb, 4096, 128, 0);
    const uint64_t dv0 = make_desc(sb + 8192, 128, 4096, 0);

#pragma unroll 1
    for (int pass = 0; pass < 2; pass++) {
        const int row0 = quarter * 512 + pass * 256 + wg * 64 + warp * 16 + g;
        uint32_t qa[4];
#pragma unroll
        for (int i = 0; i < 4; i++) qa[i] = pass ? qn2[1][i] : qn2[0][i];
        float o[12];
#pragma unroll
        for (int i = 0; i < 12; i++) o[i] = 0.f;
        fence_regs(o);
#define KF_RELEASE_CHUNK(c)                                                                          \
        if (pass == 1 && (c) >= 1 && (c) <= 4) {                                                     \
            named_sync(4 + wg, 128);            \
            if ((tid & 127) == 0 && atomicAdd(&s_cnt[(c) - 1], 1u) == 3u) {                          \
                mbar_expect_tx(wbar + 8 * (3 + (c)), 16384);                                         \
                tma_load_3d(sb + ((c) - 1) * KF_CH_S, &tm_wo, 0, (3 + (c)) * 64, nt * 2, wbar + 8 * (3 + (c))); \
            }                                                                                        \
        }
        if (fast) {
#pragma unroll 1
            for (int c = 0; c < KF_NCH; c++) {
                const uint64_t dk = dk0 + (uint64_t)(c * (KF_CH_S >> 4));
                const uint64_t dv = dv0 + (uint64_t)(c * (KF_CH_S >> 4));
                float s0[32], s1[32], s2[32], s3[32];
                uint32_t p0[16], p1[16], p2[16], p3[16];
                mbar_wait(kvbar + 8 * c, 0);
                wg_wait<1>();
                wg_fence();
                wgmma_qk_n64(s0, qa[0], qa[1], qa[2], qa[3], dk);
                wgmma_bias_n40(s0, dbias_a, dbias_b);
                wg_commit();
                wg_wait<1>();
                KF_RELEASE_CHUNK(c);
                wg_fence();
                wgmma_qk_n64(s1, qa[0], qa[1], qa[2], qa[3], dk + 64);
                wgmma_bias_n40(s1, dbias_a, dbias_b);
                wg_commit();
                wg_wait<1>();
                fence_regs(s0);
                softmax_part<0, 16>(s0, p0);
                wg_fence();
                KF_PV(p0, 0);
                wg_commit();
                wg_wait<1>();
                fence_regs(s1);
                softmax_part<0, 8>(s1, p1);
                wg_wait<0>();
                wg_fence();
                wgmma_qk_n64(s2, qa[0], qa[1], qa[2], qa[3], dk + 128);
                wgmma_bias_n40(s2, dbias_a, dbias_b);
                wg_commit();
                softmax_part<8, 16>(s1, p1);
                wg_fence();
                KF_PV(p1, 64);
                wg_commit();
                wg_wait<1>();
                fence_regs(s2);
                softmax_part<0, 8>(s2, p2);
                wg_wait<0>();
                wg_fence();
                wgmma_qk_n64(s3, qa[0], qa[1], qa[2], qa[3], dk + 192);
                wgmma_bias_n40(s3, dbias_a, dbias_b);
                wg_commit();
                softmax_part<8, 16>(s2, p2);
                wg_fence();
                KF_PV(p2, 128);
                wg_commit();
                wg_wait<1>();
                fence_regs(s3);
                softmax_part<0, 16>(s3, p3);
                wg_fence();
                KF_PV(p3, 192);
                wg_commit();
            }
            wg_wait<0>();
            fence_regs(o);
        } else {
            float m0 = -INFINITY, m1 = -INFINITY;
#pragma unroll 1
            for (int b = 0; b < 32; b++) {
                const int c = b >> 2;
                const uint64_t dk = dk0 + (uint64_t)(c * (KF_CH_S >> 4) + (b & 3) * 64);
                const uint64_t dv = dv0 + (uint64_t)(c * (KF_CH_S >> 4) + (b & 3) * 64);
                float s[32];
                uint32_t p[16];
                mbar_wait(kvbar + 8 * c, 0);
                wg_fence();
                wgmma_qk_n64(s, qa[0], qa[1], qa[2], qa[3], dk);
                wg_commit();
                if ((b & 3) == 0) { KF_RELEASE_CHUNK(c); }
                wg_wait<0>();
                fence_regs(s);
                float x0 = s[0], x1 = s[2];
#pragma unroll
                for (int j = 0; j < 8; j++) {
                    x0 = fmaxf(x0, fmaxf(s[4 * j], s[4 * j + 1]));
                    x1 = fmaxf(x1, fmaxf(s[4 * j + 2], s[4 * j + 3]));
                }
                x0 = fmaxf(x0, __shfl_xor_sync(0xffffffffu, x0, 1));
                x0 = fmaxf(x0, __shfl_xor_sync(0xffffffffu, x0, 2));
                x1 = fmaxf(x1, __shfl_xor_sync(0xffffffffu, x1, 1));
                x1 = fmaxf(x1, __shfl_xor_sync(0xffffffffu, x1, 2));
                const float n0 = fmaxf(m0, x0), n1 = fmaxf(m1, x1);
                const float c0 = ex2f(m0 - n0), c1 = ex2f(m1 - n1);
                m0 = n0; m1 = n1;
#pragma unroll
                for (int j = 0; j < 3; j++) {
                    o[4 * j] *= c0; o[4 * j + 1] *= c0; o[4 * j + 2] *= c1; o[4 * j + 3] *= c1;
                }
#pragma unroll
                for (int j = 0; j < 8; j++) {
                    p[2 * j] = pack_bf16(ex2f(s[4 * j] - n0), ex2f(s[4 * j + 1] - n0));
                    p[2 * j + 1] = pack_bf16(ex2f(s[4 * j + 2] - n1), ex2f(s[4 * j + 3] - n1));
                }
                fence_regs(o);
                wg_fence();
                KF_PV(p, 0);
                wg_commit();
                wg_wait<0>();
                fence_regs(o);
            }
        }
        const float inv0 = 1.f / o[8], inv1 = 1.f / o[10];
        {
            uint32_t v0 = pack_bf16(o[0] * inv0, o[1] * inv0), v1 = pack_bf16(o[4] * inv0, o[5] * inv0);
            uint32_t v2 = pack_bf16(o[2] * inv1, o[3] * inv1), v3 = pack_bf16(o[6] * inv1, o[7] * inv1);
            const bool o1 = t & 1, o2 = t & 2;
            uint32_t s0 = o1 ? v0 : v1, s1 = o1 ? v2 : v3;
            s0 = __shfl_xor_sync(0xffffffffu, s0, 1); s1 = __shfl_xor_sync(0xffffffffu, s1, 1);
            uint32_t a0 = o1 ? s0 : v0, a1 = o1 ? v1 : s0, b0 = o1 ? s1 : v2, b1 = o1 ? v3 : s1;
            uint32_t x0 = o2 ? a0 : b0, x1 = o2 ? a1 : b1;
            x0 = __shfl_xor_sync(0xffffffffu, x0, 2); x1 = __shfl_xor_sync(0xffffffffu, x1, 2);
            uint4 r;
            r.x = o2 ? x0 : a0; r.y = o2 ? x1 : a1; r.z = o2 ? b0 : x0; r.w = o2 ? b1 : x1;
            *(uint4*)(g_o + (size_t)(row0 + (t >> 1) * 8) * DM + head * 16 + (t & 1) * 8) = r;
        }
        if (tid == 0) TSTAMP0(1, 4 + pass);
    }
    if ((tid >> 5) < 10 || (tid >> 5) > 13) named_arrive(1, 512);
    named_sync(4 + wg, 128);
    if ((tid & 127) == 0) {
        asm volatile("fence.acq_rel.gpu;" ::: "memory");
        asm volatile("red.relaxed.gpu.global.add.u32 [%0], 1;" ::"l"(&g_oflag[(quarter * 8 + 4 + wg) * 32 + (head >> 2) * 4]) : "memory");
        asm volatile("red.relaxed.gpu.global.add.u32 [%0], 1;" ::"l"(&g_oflag[(quarter * 8 + wg) * 32 + (head >> 2) * 4]) : "memory");
    }
    if (tid == 0) TSTAMP0(1, 3);

    if (wg < 2) {
        const int wi = warp;
        const int r0 = mt * 64 + wi * 16 + g;
        const int cb = nt * 128 + wg * 64;
        uint32_t xr[16], wr[8];
#pragma unroll
        for (int j = 0; j < 8; j++) {
            xr[2 * j] = __ldg((const uint32_t*)(x + (size_t)r0 * DM + cb + 8 * j + 2 * t));
            xr[2 * j + 1] = __ldg((const uint32_t*)(x + (size_t)(r0 + 8) * DM + cb + 8 * j + 2 * t));
            wr[j] = __ldg((const uint32_t*)(w_r + cb + 8 * j + 2 * t));
        }
        float wsum = 0.f;
        {
            const uint4 a = __ldg((const uint4*)(w_r + lane * 16)), b = __ldg((const uint4*)(w_r + lane * 16 + 8));
            const uint32_t w[8] = {a.x, a.y, a.z, a.w, b.x, b.y, b.z, b.w};
#pragma unroll
            for (int i = 0; i < 8; i++) wsum += bf_lo(w[i]) + bf_hi(w[i]);
#pragma unroll
            for (int o = 16; o > 0; o >>= 1) wsum += __shfl_xor_sync(0xffffffffu, wsum, o);
        }
        float acc[32];
#pragma unroll
        for (int i = 0; i < 32; i++) acc[i] = 0.f;
        fence_regs(acc);
#pragma unroll 1
        for (int i = 0; i < 8; i++) {
            mbar_wait(obar + 8 * i, 0);
            const int kb = __shfl_sync(0xffffffffu, (int)s_order[i], 0);
            mbar_wait(wbar + 8 * kb, 0);
            const uint32_t wa = (kb < 4) ? (KF_OFF_WO + kb * 16384) : ((kb - 4) * KF_CH_S);
            const uint64_t da = make_desc(sb + (4 + (kb >> 1)) * KF_CH_S + (kb & 1) * 8192, 16, 1024, 1);
            const uint64_t db = make_desc(sb + wa + wg * 8192, 1024, 1024, 1);
            wg_fence();
#pragma unroll
            for (int k = 0; k < 4; k++) wgmma_k3_n64(acc, da + k * 2, db + k * 128, (i | k) != 0);
            wg_commit();
        }
        wg_wait<0>();
        fence_regs(acc);
        if (tid == 0) TSTAMP0(2, 2);
        float hv[32];
        uint32_t hp[16];
        float s0 = 0.f, s1 = 0.f, d0 = 0.f, d1 = 0.f;
#pragma unroll
        for (int j = 0; j < 8; j++) {
            const uint32_t a01 = pack_bf16(acc[4 * j], acc[4 * j + 1]), a23 = pack_bf16(acc[4 * j + 2], acc[4 * j + 3]);
            hp[2 * j] = pack_bf16(bf_lo(xr[2 * j]) + bf_lo(a01), bf_hi(xr[2 * j]) + bf_hi(a01));
            hp[2 * j + 1] = pack_bf16(bf_lo(xr[2 * j + 1]) + bf_lo(a23), bf_hi(xr[2 * j + 1]) + bf_hi(a23));
            hv[4 * j] = bf_lo(hp[2 * j]); hv[4 * j + 1] = bf_hi(hp[2 * j]);
            hv[4 * j + 2] = bf_lo(hp[2 * j + 1]); hv[4 * j + 3] = bf_hi(hp[2 * j + 1]);
            const float wl = bf_lo(wr[j]), wh = bf_hi(wr[j]);
            s0 += hv[4 * j] + hv[4 * j + 1];
            s1 += hv[4 * j + 2] + hv[4 * j + 3];
            d0 = fmaf(hv[4 * j], wl, fmaf(hv[4 * j + 1], wh, d0));
            d1 = fmaf(hv[4 * j + 2], wl, fmaf(hv[4 * j + 3], wh, d1));
        }
        float mu0 = s0 * (1.f / 16), mu1 = s1 * (1.f / 16);
        float q0 = 0.f, q1 = 0.f;
#pragma unroll
        for (int j = 0; j < 8; j++) {
            float a = hv[4 * j] - mu0, b = hv[4 * j + 1] - mu0, c = hv[4 * j + 2] - mu1, d = hv[4 * j + 3] - mu1;
            q0 = fmaf(a, a, fmaf(b, b, q0));
            q1 = fmaf(c, c, fmaf(d, d, q1));
        }
#pragma unroll
        for (int o = 1; o < 4; o <<= 1) {
            const float m0 = __shfl_xor_sync(0xffffffffu, mu0, o), m1 = __shfl_xor_sync(0xffffffffu, mu1, o);
            const float e0 = __shfl_xor_sync(0xffffffffu, q0, o), e1 = __shfl_xor_sync(0xffffffffu, q1, o);
            d0 += __shfl_xor_sync(0xffffffffu, d0, o);
            d1 += __shfl_xor_sync(0xffffffffu, d1, o);
            const float f0 = mu0 - m0, f1 = mu1 - m1;
            q0 = q0 + e0 + f0 * f0 * (8.f * o);
            q1 = q1 + e1 + f1 * f1 * (8.f * o);
            mu0 = 0.5f * (mu0 + m0); mu1 = 0.5f * (mu1 + m1);
        }
        float4* part = g_part + (size_t)mt * 512 + wi * 16 + g;
        if (t < 2) {
            float4* dst = part + (nt * 2 + wg) * 64 + t * 8;
            const float a = t ? mu1 : mu0, b = t ? q1 : q0, c = t ? d1 : d0;
            asm volatile("st.relaxed.gpu.global.v4.f32 [%0], {%1, %2, %3, %4};" ::"l"(dst), "f"(a), "f"(b), "f"(c), "f"(1.0f) : "memory");
        }
        if (tid == 0) TSTAMP0(2, 5);
        const uint32_t stg_off = KF_OFF_WO + (wi >> 1) * 16384 + wg * 8192 + (wi & 1) * 4096;
        const uint32_t stg_o = sb + stg_off, stg_h = stg_o + 2048;
        const int srow = (lane & 7) + ((lane >> 3) & 1) * 8;
        const int sj = lane >> 4;
        named_sync(4 + wg, 128);
#pragma unroll
        for (int j = 0; j < 8; j += 2) {
            const uint32_t off = srow * 128 + (((j + sj) ^ (srow & 7)) << 4);
            stmatrix_x4(stg_h + off, hp[2 * j], hp[2 * j + 1], hp[2 * j + 2], hp[2 * j + 3]);
        }
        __syncwarp();
#pragma unroll
        for (int i = 0; i < 4; i++) {
            const int row = i * 4 + (lane >> 3), ch = lane & 7;
            const uint4 vh = *(const uint4*)(sp + stg_off + 2048 + row * 128 + ((ch ^ (row & 7)) << 4));
            *(uint4*)(g_h + (size_t)(mt * 64 + wi * 16 + row) * DM + cb + ch * 8) = vh;
        }
        named_arrive(8, 288);
        if (tid == 0) TSTAMP0(2, 6);
        float mean[2], den[2], rr[2];
        {
            float4 v[4];
            int spins = 0;
            while (true) {
#pragma unroll
                for (int i = 0; i < 4; i++) {
                    const float4* p = part + (t + (i & 1) * 4) * 64 + (i >> 1) * 8;
                    asm volatile("ld.relaxed.gpu.global.v4.f32 {%0, %1, %2, %3}, [%4];" : "=f"(v[i].x), "=f"(v[i].y), "=f"(v[i].z), "=f"(v[i].w) : "l"(p) : "memory");
                }
                const bool ok = (v[0].w != 0.f) && (v[1].w != 0.f) && (v[2].w != 0.f) && (v[3].w != 0.f);
                if (__all_sync(0xffffffffu, ok) || ++spins > (1 << 22)) break;
            }
#pragma unroll
            for (int u = 0; u < 2; u++) {
                float mu = v[2 * u].x + v[2 * u + 1].x, m2 = v[2 * u].y + v[2 * u + 1].y, hw = v[2 * u].z + v[2 * u + 1].z;
#pragma unroll
                for (int o = 1; o < 4; o <<= 1) {
                    mu += __shfl_xor_sync(0xffffffffu, mu, o);
                    m2 += __shfl_xor_sync(0xffffffffu, m2, o);
                    hw += __shfl_xor_sync(0xffffffffu, hw, o);
                }
                mu *= 0.125f;
                const float da = v[2 * u].x - mu, db = v[2 * u + 1].x - mu;
                float dd = 64.f * (da * da + db * db);
#pragma unroll
                for (int o = 1; o < 4; o <<= 1) dd += __shfl_xor_sync(0xffffffffu, dd, o);
                m2 += dd;
                mean[u] = rbf(mu);
                den[u] = rbf(sqrtf(rbf(rbf(m2 * (1.f / DM)) + 1e-5f)));
                rr[u] = rbf((hw - mean[u] * wsum) / den[u]);
            }
        }
        if (tid == 0) TSTAMP0(2, 3);
        named_arrive(3, 512);
        if (nt == 0 && wg == 0) {
            float2* s_st = (float2*)(sp + KF_OFF_WO + 49152);
            if (t == 0) {
                s_key[wi * 16 + g] = make_key(rr[0], r0);
                s_key[wi * 16 + g + 8] = make_key(rr[1], r0 + 8);
                s_st[wi * 16 + g] = make_float2(mean[0], den[0]);
                s_st[wi * 16 + g + 8] = make_float2(mean[1], den[1]);
            }
            named_sync(4, 128);
            if (warp == 0) {
                uint32_t k1, k2;
                warp_top2(s_key[lane], s_key[lane + 32], k1, k2);
                if (lane < 2) {
                    const uint32_t k = lane ? k2 : k1;
                    const float2 st = s_st[key_token(k) & 63];
                    asm volatile("st.relaxed.gpu.global.v4.u32 [%0], {%1, %2, %3, %4};" ::"l"(g_cand + mt * 2 + lane), "r"(k),
                                 "r"(1u), "r"(__float_as_uint(st.x)), "r"(__float_as_uint(st.y)) : "memory");
                }
            }
        }
        const float i0 = 1.f / den[0], i1 = 1.f / den[1];
#pragma unroll
        for (int j = 0; j < 8; j += 2) {
            uint32_t ro[4];
#pragma unroll
            for (int u = 0; u < 2; u++) {
                const int jj = j + u;
                const float a = hv[4 * jj], b = hv[4 * jj + 1], c = hv[4 * jj + 2], d = hv[4 * jj + 3];
                const uint32_t u01 = pack_bf16(a - mean[0], b - mean[0]), u23 = pack_bf16(c - mean[1], d - mean[1]);
                const uint32_t n01 = pack_bf16(bf_lo(u01) * i0, bf_hi(u01) * i0), n23 = pack_bf16(bf_lo(u23) * i1, bf_hi(u23) * i1);
                ro[2 * u] = pack_bf16(a + bf_lo(n01), b + bf_hi(n01));
                ro[2 * u + 1] = pack_bf16(c + bf_lo(n23), d + bf_hi(n23));
            }
            const uint32_t off = srow * 128 + (((j + sj) ^ (srow & 7)) << 4);
            stmatrix_x4(stg_o + off, ro[0], ro[1], ro[2], ro[3]);
        }
        __syncwarp();
#pragma unroll
        for (int i = 0; i < 4; i++) {
            const int row = i * 4 + (lane >> 3), ch = lane & 7;
            const uint4 vo = *(const uint4*)(sp + stg_off + row * 128 + ((ch ^ (row & 7)) << 4));
            *(uint4*)(out + (size_t)(mt * 64 + wi * 16 + row) * DM + cb + ch * 8) = vo;
        }
        named_sync(4 + wg, 128);
        if ((tid & 127) == 0) red_release_add(&g_sflag[mt]);
        if (tid == 0) TSTAMP0(2, 4);
    } else {
        const bool worker = blockIdx.x < FF / 16;
        const bool downer = blockIdx.x >= 64;
        const int mtid = tid - 256, mwarp = mtid >> 5;
        const int c0 = (blockIdx.x - 64) * 8;
        float* s_x = (float*)(sp + KF_OFF_WO + 49152 + 8192);
        float* s_red = (float*)(sp + KF_OFF_WO + 49152 + 8192 + 4096);
        if (mwarp >= 2 && mwarp < 6) {
            named_sync(1, 512);
            const int kb0 = (mwarp - 2) * 2;
            uint32_t done = 0;
            int spins = 0;
            while (done != 3u && ++spins < (1 << 22)) {
                const bool rdy = lane < 2 && ld_acquire(&g_oflag[mt * 32 + (kb0 + lane) * 4]) >= 4u;
                uint32_t todo = __ballot_sync(0xffffffffu, rdy) & ~done;
                done |= todo;
                if (todo && lane == 0) {
                    asm volatile("fence.proxy.async.global;" ::: "memory");
                    while (todo) {
                        const int kb = kb0 + __ffs(todo) - 1;
                        todo &= todo - 1;
                        const int n = (int)atomicAdd(&s_cnt[5], 1u);
                        s_order[n] = kb;
                        mbar_expect_tx(obar + 8 * n, 8192);
                        tma_load_3d(sb + (4 + (kb >> 1)) * KF_CH_S + (kb & 1) * 8192, &tm_o, 0, mt * 64, kb, obar + 8 * n);
                    }
                }
                __syncwarp();
                if (done != 3u) __nanosleep(POLL_NS);
            }
            if (mwarp == 5 && lane == 0) TSTAMP0(2, 1);
            if (lane == 0 && worker) {
                if (mwarp == 2) mbar_expect_tx(gbar, 32768);
                __syncwarp(1u);
            }
            named_sync(9, 128);
            if (lane == 0 && worker) {
                const int i = mwarp - 2;
                tma_load_2d(sb + i * KF_CH_S + 16384, &tm_g, blockIdx.x * 16, i * 128, gbar);
                tma_load_2d(sb + (4 + i) * KF_CH_S + 16384, &tm_u, blockIdx.x * 16, i * 128, gbar);
            }
        }
        if (mwarp == 1) {
            named_sync(8, 288);
            if (lane == 0) {
                red_release_add(&g_hflag[mt]);
                if (downer) {
                    mbar_expect_tx(dbar, 7 * 4096);
                    for (int i = 0; i < 7; i++) tma_load_2d(sb + (4 + (i >> 2)) * KF_CH_S + (i & 3) * 4096, &tm_d, c0, i * 256, dbar);
                }
            }
            __syncwarp();
        }
        if (mtid == 0) TSTAMP0(3, 0);
        named_sync(3, 512);
        if (mwarp == 0) {
            uint4 ca, cb4;
            int spins = 0;
            while (true) {
                asm volatile("ld.relaxed.gpu.global.v4.u32 {%0, %1, %2, %3}, [%4];" : "=r"(ca.x), "=r"(ca.y), "=r"(ca.z), "=r"(ca.w) : "l"(g_cand + 2 * lane) : "memory");
                asm volatile("ld.relaxed.gpu.global.v4.u32 {%0, %1, %2, %3}, [%4];" : "=r"(cb4.x), "=r"(cb4.y), "=r"(cb4.z), "=r"(cb4.w) : "l"(g_cand + 2 * lane + 1) : "memory");
                const unsigned int hf = ld_acquire(&g_hflag[lane]);
                const bool ok = ca.y != 0 && cb4.y != 0 && hf >= 4u;
                if (__all_sync(0xffffffffu, ok) || ++spins > (1 << 22)) break;
            }
            uint32_t k1, k2;
            warp_top2(ca.x, cb4.x, k1, k2);
            if (ca.x == k1) s_sel[0] = ca;
            if (cb4.x == k1) s_sel[0] = cb4;
            if (ca.x == k2) s_sel[1] = ca;
            if (cb4.x == k2) s_sel[1] = cb4;
        }
        named_sync(2, 256);
        if (mtid == 0) TSTAMP0(3, 1);
        int idx[2];
        float mean[2], inv[2], rv[2];
#pragma unroll
        for (int u = 0; u < 2; u++) {
            const uint4 c = s_sel[u];
            idx[u] = key_token(c.x);
            rv[u] = key_value(c.x);
            mean[u] = __uint_as_float(c.z);
            inv[u] = 1.f / __uint_as_float(c.w);
        }
        float hfin = 0.f;
        if (downer && mtid < 16) hfin = __bfloat162float(__ldcg((const __nv_bfloat16*)(g_h + (size_t)((mtid >> 3) ? idx[1] : idx[0]) * DM + c0 + (mtid & 7))));
        if (worker) {
            {
                const uint32_t h0 = __ldcg((const uint32_t*)(g_h + (size_t)idx[0] * DM + 2 * mtid));
                const uint32_t h1 = __ldcg((const uint32_t*)(g_h + (size_t)idx[1] * DM + 2 * mtid));
                const uint32_t u0 = pack_bf16(bf_lo(h0) - mean[0], bf_hi(h0) - mean[0]), u1 = pack_bf16(bf_lo(h1) - mean[1], bf_hi(h1) - mean[1]);
                const uint32_t n0 = pack_bf16(bf_lo(u0) * inv[0], bf_hi(u0) * inv[0]), n1 = pack_bf16(bf_lo(u1) * inv[1], bf_hi(u1) * inv[1]);
                *(float4*)(s_x + 4 * mtid) = make_float4(bf_lo(n0), bf_lo(n1), bf_hi(n0), bf_hi(n1));
            }
            if (mtid == 0) TSTAMP0(3, 5);
            mbar_wait(gbar, 0);
            named_sync(2, 256);
            if (mtid == 0) TSTAMP0(3, 6);
            float acc[16];
#pragma unroll
            for (int i = 0; i < 16; i++) acc[i] = 0.f;
            const uint8_t* wbase = sp + ((mwarp >> 2) * 4 + (mwarp & 3)) * KF_CH_S + 16384 + lane * 16;
            const float* xb = s_x + 2 * (128 * (mwarp & 3) + (lane >> 1));
#pragma unroll
            for (int j = 0; j < 8; j++) {
                const uint4 w = *(const uint4*)(wbase + j * 512);
                const float2 xx = *(const float2*)(xb + 32 * j);
                const uint32_t ww[4] = {w.x, w.y, w.z, w.w};
#pragma unroll
                for (int q = 0; q < 4; q++) {
                    const float wl = bf_lo(ww[q]), wh = bf_hi(ww[q]);
                    acc[2 * q] = fmaf(xx.x, wl, acc[2 * q]); acc[2 * q + 1] = fmaf(xx.x, wh, acc[2 * q + 1]);
                    acc[8 + 2 * q] = fmaf(xx.y, wl, acc[8 + 2 * q]); acc[8 + 2 * q + 1] = fmaf(xx.y, wh, acc[8 + 2 * q + 1]);
                }
            }
#define KF_STEP(O, N)                                                          \
            {                                                                  \
                const bool up = (lane & (O)) != 0;                             \
                _Pragma("unroll") for (int i = 0; i < (N); i++) {              \
                    const float send = up ? acc[i] : acc[i + (N)];             \
                    const float keep = up ? acc[i + (N)] : acc[i];             \
                    acc[i] = keep + __shfl_xor_sync(0xffffffffu, send, (O));   \
                }                                                              \
            }
            KF_STEP(16, 8) KF_STEP(8, 4) KF_STEP(4, 2) KF_STEP(2, 1)
            {
                const int v = ((lane & 16) ? 8 : 0) + ((lane & 8) ? 4 : 0) + ((lane & 4) ? 2 : 0) + ((lane & 2) ? 1 : 0);
                s_gu[mwarp * 32 + (v >> 3) * 16 + (lane & 1) * 8 + (v & 7)] = acc[0];
            }
            named_sync(2, 256);
            if (mtid < 16) {
                uint32_t a2 = 0;
#pragma unroll
                for (int u = 0; u < 2; u++) {
                    const float* pg = s_gu + u * 16 + mtid;
                    const float gb = rbf((pg[0] + pg[32]) + (pg[64] + pg[96]));
                    const float ub = rbf((pg[128] + pg[160]) + (pg[192] + pg[224]));
                    const float sg = rbf(gb / (1.f + __expf(-gb)));
                    const float a = sg * ub;
                    uint32_t ab = (uint32_t)__bfloat16_as_ushort(__float2bfloat16_rn(a));
                    if (ab == 0xFFFFu) ab = 0x7FFFu;
                    a2 |= ab << (16 * u);
                }
                asm volatile("st.relaxed.gpu.global.u32 [%0], %1;" ::"l"(g_act + blockIdx.x * 16 + mtid), "r"(a2) : "memory");
            }
            if (mtid == 0) TSTAMP0(3, 2);
        }
        if (downer) {
            uint32_t av[7];
            {
                int spins = 0;
                while (true) {
                    bool ok = true;
#pragma unroll
                    for (int j = 0; j < 7; j++) {
                        asm volatile("ld.relaxed.gpu.global.u32 %0, [%1];" : "=r"(av[j]) : "l"(g_act + mtid + 256 * j) : "memory");
                        ok = ok && ((av[j] & 0xFFFFu) != 0xFFFFu) && ((av[j] >> 16) != 0xFFFFu);
                    }
                    if (mtid < 2) ok = ok && (ld_acquire(&g_sflag[(mtid ? idx[1] : idx[0]) >> 6]) >= 8u);
                    if (__all_sync(0xffffffffu, ok) || ++spins > (1 << 20)) break;
                    __nanosleep(20);
                }
            }
            if (mtid == 0) TSTAMP0(3, 3);
            mbar_wait(dbar, 0);
            float acc[16];
#pragma unroll
            for (int i = 0; i < 16; i++) acc[i] = 0.f;
#pragma unroll
            for (int j = 0; j < 7; j++) {
                const uint4 w = *(const uint4*)(sp + (4 + (j >> 2)) * KF_CH_S + (j & 3) * 4096 + mtid * 16);
                const float a0 = bf_lo(av[j]), a1 = bf_hi(av[j]);
                const uint32_t ww[4] = {w.x, w.y, w.z, w.w};
#pragma unroll
                for (int q = 0; q < 4; q++) {
                    const float wl = bf_lo(ww[q]), wh = bf_hi(ww[q]);
                    acc[2 * q] = fmaf(a0, wl, acc[2 * q]); acc[2 * q + 1] = fmaf(a0, wh, acc[2 * q + 1]);
                    acc[8 + 2 * q] = fmaf(a1, wl, acc[8 + 2 * q]); acc[8 + 2 * q + 1] = fmaf(a1, wh, acc[8 + 2 * q + 1]);
                }
            }
            KF_STEP(16, 8) KF_STEP(8, 4) KF_STEP(4, 2) KF_STEP(2, 1)
            acc[0] += __shfl_xor_sync(0xffffffffu, acc[0], 1);
            if ((lane & 1) == 0) {
                const int v = ((lane & 16) ? 8 : 0) + ((lane & 8) ? 4 : 0) + ((lane & 4) ? 2 : 0) + ((lane & 2) ? 1 : 0);
                s_red[mwarp * 16 + v] = acc[0];
            }
            named_sync(2, 256);
            if (mtid < 16) {
                const int u = mtid >> 3;
                float y = 0.f;
#pragma unroll
                for (int w = 0; w < 8; w++) y += s_red[w * 16 + mtid];
                const float sig = rbf(1.f / (1.f + __expf(-(u ? rv[1] : rv[0]))));
                const float xn = rbf(rbf(hfin - (u ? mean[1] : mean[0])) * (u ? inv[1] : inv[0]));
                const float ov = hfin + rbf(xn + rbf(rbf(y) * sig));
                out[(size_t)(u ? idx[1] : idx[0]) * DM + c0 + (mtid & 7)] = __float2bfloat16_rn(ov);
            }
            if (blockIdx.x == gridDim.x - 1 && mtid == 0) g_epoch = g_epoch + 1u;
            if (mtid == 0) TSTAMP0(3, 4);
        }
    }
}

typedef CUresult (*PFN_encodeTiled)(CUtensorMap*, CUtensorMapDataType, cuuint32_t, void*, const cuuint64_t*, const cuuint64_t*,
                                    const cuuint32_t*, const cuuint32_t*, CUtensorMapInterleave, CUtensorMapSwizzle,
                                    CUtensorMapL2promotion, CUtensorMapFloatOOBfill);

void make_map(PFN_encodeTiled enc, CUtensorMap* m, const void* ptr, uint64_t cols, uint64_t rows, uint32_t bcols, uint32_t brows) {
    cuuint64_t dims[2] = {cols, rows};
    cuuint64_t strides[1] = {cols * 2};
    cuuint32_t box[2] = {bcols, brows};
    cuuint32_t es[2] = {1, 1};
    enc(m, CU_TENSOR_MAP_DATA_TYPE_BFLOAT16, 2, const_cast<void*>(ptr), dims, strides, box, es, CU_TENSOR_MAP_INTERLEAVE_NONE,
        CU_TENSOR_MAP_SWIZZLE_128B, CU_TENSOR_MAP_L2_PROMOTION_L2_256B, CU_TENSOR_MAP_FLOAT_OOB_FILL_NONE);
}

void make_map3(PFN_encodeTiled enc, CUtensorMap* m, const void* ptr, uint64_t d0, uint64_t rows, uint64_t d2, uint64_t row_stride_bytes,
               uint64_t d2_stride_bytes, uint32_t b0, uint32_t b1, uint32_t b2) {
    cuuint64_t dims[3] = {d0, rows, d2};
    cuuint64_t strides[2] = {row_stride_bytes, d2_stride_bytes};
    cuuint32_t box[3] = {b0, b1, b2};
    cuuint32_t es[3] = {1, 1, 1};
    enc(m, CU_TENSOR_MAP_DATA_TYPE_BFLOAT16, 3, const_cast<void*>(ptr), dims, strides, box, es, CU_TENSOR_MAP_INTERLEAVE_NONE,
        CU_TENSOR_MAP_SWIZZLE_128B, CU_TENSOR_MAP_L2_PROMOTION_L2_256B, CU_TENSOR_MAP_FLOAT_OOB_FILL_NONE);
}

void make_map_plain(PFN_encodeTiled enc, CUtensorMap* m, const void* ptr, uint64_t cols, uint64_t rows, uint32_t bcols, uint32_t brows) {
    cuuint64_t dims[2] = {cols, rows};
    cuuint64_t strides[1] = {cols * 2};
    cuuint32_t box[2] = {bcols, brows};
    cuuint32_t es[2] = {1, 1};
    enc(m, CU_TENSOR_MAP_DATA_TYPE_BFLOAT16, 2, const_cast<void*>(ptr), dims, strides, box, es, CU_TENSOR_MAP_INTERLEAVE_NONE,
        CU_TENSOR_MAP_SWIZZLE_NONE, CU_TENSOR_MAP_L2_PROMOTION_NONE, CU_TENSOR_MAP_FLOAT_OOB_FILL_NONE);
}

template <typename... KArgs, typename... Args>
void launch(void (*kern)(KArgs...), int grid, int block, int smem, bool pdl, Args... args) {
    cudaLaunchConfig_t cfg = {};
    cfg.gridDim = dim3(grid);
    cfg.blockDim = dim3(block);
    cfg.dynamicSmemBytes = smem;
    cfg.stream = cudaStreamPerThread;
    cudaLaunchAttribute at[1];
    at[0].id = cudaLaunchAttributeProgrammaticStreamSerialization;
    at[0].val.programmaticStreamSerializationAllowed = 1;
    cfg.attrs = at;
    cfg.numAttrs = pdl ? 1 : 0;
    cudaLaunchKernelEx(&cfg, kern, KArgs(args)...);
}

}

extern "C" void kernel_launch(void* const* d_in, const int* in_sizes, int n_in, void* d_out, int out_size) {
    const __nv_bfloat16* x = (const __nv_bfloat16*)d_in[0];
    const __nv_bfloat16* wqkv = (const __nv_bfloat16*)d_in[1];
    const __nv_bfloat16* wo = (const __nv_bfloat16*)d_in[2];
    const __nv_bfloat16* w_r = (const __nv_bfloat16*)d_in[4];
    const __nv_bfloat16* w_gate = (const __nv_bfloat16*)d_in[5];
    const __nv_bfloat16* w_up = (const __nv_bfloat16*)d_in[6];
    const __nv_bfloat16* w_down = (const __nv_bfloat16*)d_in[7];
    __nv_bfloat16* out = (__nv_bfloat16*)d_out;

    static PFN_encodeTiled enc = nullptr;
    static void* g_o_ptr = nullptr;
    if (!enc) {
        cudaDriverEntryPointQueryResult qres;
        void* fn = nullptr;
        cudaGetDriverEntryPoint("cuTensorMapEncodeTiled", &fn, cudaEnableDefault, &qres);
        enc = (PFN_encodeTiled)fn;
        cudaGetSymbolAddress(&g_o_ptr, g_o);
        cudaFuncSetAttribute(k1_qkv, cudaFuncAttributeMaxDynamicSharedMemorySize, K1_SMEM);
        cudaFuncSetAttribute(kf_main, cudaFuncAttributeMaxDynamicSharedMemorySize, KF_SMEM);
    }
    CUtensorMap tm_x, tm_w, tm_o, tm_wo, tm_g, tm_u, tm_d;
    make_map_plain(enc, &tm_d, w_down, DM, FF, 8, 256);
    make_map_plain(enc, &tm_g, w_gate, FF, DM, 16, 128);
    make_map_plain(enc, &tm_u, w_up, FF, DM, 16, 128);
    make_map(enc, &tm_x, x, DM, SEQ, 64, 128);
    make_map3(enc, &tm_w, wqkv, DM, DM, 3, 3 * DM * 2, DM * 2, 64, 64, 3);
    make_map3(enc, &tm_o, g_o_ptr, 64, SEQ, 8, DM * 2, 128, 64, 64, 1);
    make_map3(enc, &tm_wo, wo, 64, DM, 8, DM * 2, 128, 64, 64, 2);

    const bool pdl = true;
    launch(k1_qkv, 128, 544, K1_SMEM, false, tm_x, tm_w, x);
    launch(kf_main, 128, 512, KF_SMEM, pdl, tm_o, tm_wo, tm_g, tm_u, tm_d, x, wo, w_r, w_gate, w_up, w_down, out);
}
```

```cpp
#include <cuda_runtime.h>
#include <cuda_bf16.h>
#include <cuda.h>
#include <stdint.h>

namespace {

constexpr int SEQ = 2048, DM = 512, NH = 32, FF = 1792;

__device__ __align__(1024) uint8_t g_q[NH * 2 * SEQ * 16];
__device__ __align__(1024) uint8_t g_kv[NH * 8 * 16384];
__device__ float g_norm[16 * NH * 3];
__device__ __align__(1024) __nv_bfloat16 g_o[SEQ * DM];
__device__ __align__(1024) __nv_bfloat16 g_h[SEQ * DM];
__device__ __align__(16) uint4 g_cand[64];
__device__ unsigned int g_oflag[32 * 32];
__device__ unsigned int g_hflag[32];
__device__ unsigned int g_sflag[32];
__device__ unsigned int g_act[FF];
__device__ unsigned int g_epoch;
__device__ __align__(16) float4 g_ln1[SEQ];
__device__ __align__(16) float4 g_part[32 * 8 * 64];

__device__ __forceinline__ uint32_t smem_u32(const void* p) { return (uint32_t)__cvta_generic_to_shared(p); }
__device__ __forceinline__ void wg_fence() { asm volatile("wgmma.fence.sync.aligned;" ::: "memory"); }
__device__ __forceinline__ void wg_commit() { asm volatile("wgmma.commit_group.sync.aligned;" ::: "memory"); }
template <int N> __device__ __forceinline__ void wg_wait() { asm volatile("wgmma.wait_group.sync.aligned %0;" ::"n"(N) : "memory"); }
template <int N> __device__ __forceinline__ void fence_regs(float (&r)[N]) {
#pragma unroll
    for (int i = 0; i < N; i++) asm volatile("" : "+f"(r[i])::"memory");
}
__device__ __forceinline__ uint64_t make_desc(uint32_t addr, uint32_t lbo, uint32_t sbo, uint32_t swz) {
    uint64_t d = 0;
    d |= (uint64_t)((addr & 0x3FFFF) >> 4);
    d |= (uint64_t)((lbo & 0x3FFFF) >> 4) << 16;
    d |= (uint64_t)((sbo & 0x3FFFF) >> 4) << 32;
    d |= (uint64_t)swz << 62;
    return d;
}
__device__ __forceinline__ void mbar_init(uint32_t bar, uint32_t cnt) {
    asm volatile("mbarrier.init.shared::cta.b64 [%0], %1;" ::"r"(bar), "r"(cnt) : "memory");
}
__device__ __forceinline__ void mbar_expect_tx(uint32_t bar, uint32_t bytes) {
    asm volatile("mbarrier.arrive.expect_tx.shared::cta.b64 _, [%0], %1;" ::"r"(bar), "r"(bytes) : "memory");
}
__device__ __forceinline__ void mbar_arrive(uint32_t bar) {
    asm volatile("mbarrier.arrive.shared::cta.b64 _, [%0];" ::"r"(bar) : "memory");
}
__device__ __forceinline__ void mbar_wait(uint32_t bar, uint32_t parity) {
    asm volatile(
        "{\n.reg .pred p;\nWAIT_%=:\n"
        "mbarrier.try_wait.parity.shared::cta.b64 p, [%0], %1;\n"
        "@p bra DONE_%=;\nbra WAIT_%=;\nDONE_%=:\n}\n" ::"r"(bar), "r"(parity) : "memory");
}
__device__ __forceinline__ void bulk_g2s(uint32_t dst, const void* src, uint32_t bytes, uint32_t bar) {
    asm volatile("cp.async.bulk.shared::cluster.global.mbarrier::complete_tx::bytes [%0], [%1], %2, [%3];" ::"r"(dst),
                 "l"(src), "r"(bytes), "r"(bar) : "memory");
}
__device__ __forceinline__ void bulk_s2g(void* dst, uint32_t src, uint32_t bytes) {
    asm volatile("cp.async.bulk.global.shared::cta.bulk_group [%0], [%1], %2;" ::"l"(dst), "r"(src), "r"(bytes) : "memory");
}
__device__ __forceinline__ void tma_load_2d(uint32_t dst, const CUtensorMap* tm, int c0, int c1, uint32_t bar) {
    asm volatile("cp.async.bulk.tensor.2d.shared::cluster.global.mbarrier::complete_tx::bytes [%0], [%1, {%3, %4}], [%2];" ::"r"(dst),
                 "l"(tm), "r"(bar), "r"(c0), "r"(c1) : "memory");
}
__device__ __forceinline__ void tma_load_3d(uint32_t dst, const CUtensorMap* tm, int c0, int c1, int c2, uint32_t bar) {
    asm volatile("cp.async.bulk.tensor.3d.shared::cluster.global.mbarrier::complete_tx::bytes [%0], [%1, {%3, %4, %5}], [%2];" ::"r"(dst),
                 "l"(tm), "r"(bar), "r"(c0), "r"(c1), "r"(c2) : "memory");
}
__device__ __forceinline__ void prefetch_l2(const void* p, uint32_t bytes) {
    asm volatile("cp.async.bulk.prefetch.L2.global [%0], %1;" ::"l"(p), "r"(bytes) : "memory");
}
__device__ __forceinline__ void fence_proxy_async() { asm volatile("fence.proxy.async.shared::cta;" ::: "memory"); }
__device__ __forceinline__ void fence_barrier_init() { asm volatile("fence.mbarrier_init.release.cluster;" ::: "memory"); }
__device__ __forceinline__ void pdl_launch() { asm volatile("griddepcontrol.launch_dependents;" ::: "memory"); }
__device__ __forceinline__ void pdl_wait() { asm volatile("griddepcontrol.wait;" ::: "memory"); }
__device__ __forceinline__ void named_sync(int id, int n) { asm volatile("bar.sync %0, %1;" ::"r"(id), "r"(n) : "memory"); }
__device__ __forceinline__ void named_arrive(int id, int n) { asm volatile("bar.arrive %0, %1;" ::"r"(id), "r"(n) : "memory"); }

__device__ __forceinline__ float ex2f(float x) { float y; asm("ex2.approx.ftz.f32 %0, %1;" : "=f"(y) : "f"(x)); return y; }
__device__ __forceinline__ uint32_t pack_bf16(float lo, float hi) {
    uint32_t r; asm("cvt.rn.bf16x2.f32 %0, %1, %2;" : "=r"(r) : "f"(hi), "f"(lo)); return r;
}
__device__ __forceinline__ float bf_lo(uint32_t v) { return __uint_as_float(v << 16); }
__device__ __forceinline__ float bf_hi(uint32_t v) { return __uint_as_float(v & 0xFFFF0000u); }
__device__ __forceinline__ float rbf(float x) { return __bfloat162float(__float2bfloat16_rn(x)); }
__device__ __forceinline__ uint32_t fma_bf16x2(uint32_t a, uint32_t b, uint32_t c) {
    uint32_t r; asm("fma.rn.bf16x2 %0, %1, %2, %3;" : "=r"(r) : "r"(a), "r"(b), "r"(c)); return r;
}
__device__ __forceinline__ void stmatrix_x4(uint32_t addr, uint32_t r0, uint32_t r1, uint32_t r2, uint32_t r3) {
    asm volatile("stmatrix.sync.aligned.m8n8.x4.shared.b16 [%0], {%1, %2, %3, %4};" ::"r"(addr), "r"(r0), "r"(r1), "r"(r2), "r"(r3) : "memory");
}
__device__ __forceinline__ void stmatrix_x4_trans(uint32_t addr, uint32_t r0, uint32_t r1, uint32_t r2, uint32_t r3) {
    asm volatile("stmatrix.sync.aligned.m8n8.x4.trans.shared.b16 [%0], {%1, %2, %3, %4};" ::"r"(addr), "r"(r0), "r"(r1), "r"(r2), "r"(r3) : "memory");
}

__device__ __forceinline__ void wgmma_k1_n136(float (&d)[68], uint64_t desca, uint64_t descb, int scale_d) {
  asm volatile("{\n.reg .pred p;\nsetp.ne.b32 p, %70, 0;\n"
    "wgmma.mma_async.sync.aligned.m64n136k16.f32.bf16.bf16 "
    "{%0, %1, %2, %3, %4, %5, %6, %7, %8, %9, %10, %11, %12, %13, %14, %15, %16, %17, %18, %19, %20, %21, %22, %23, %24, %25, %26, %27, %28, %29, %30, %31, %32, %33, %34, %35, %36, %37, %38, %39, %40, %41, %42, %43, %44, %45, %46, %47, %48, %49, %50, %51, %52, %53, %54, %55, %56, %57, %58, %59, %60, %61, %62, %63, %64, %65, %66, %67}, "
    "%68, %69, p, 1, 1, 1, 0;\n}\n"
    : "+f"(d[0]), "+f"(d[1]), "+f"(d[2]), "+f"(d[3]), "+f"(d[4]), "+f"(d[5]), "+f"(d[6]), "+f"(d[7]), "+f"(d[8]), "+f"(d[9]), "+f"(d[10]), "+f"(d[11]), "+f"(d[12]), "+f"(d[13]), "+f"(d[14]), "+f"(d[15]), "+f"(d[16]), "+f"(d[17]), "+f"(d[18]), "+f"(d[19]), "+f"(d[20]), "+f"(d[21]), "+f"(d[22]), "+f"(d[23]), "+f"(d[24]), "+f"(d[25]), "+f"(d[26]), "+f"(d[27]), "+f"(d[28]), "+f"(d[29]), "+f"(d[30]), "+f"(d[31]), "+f"(d[32]), "+f"(d[33]), "+f"(d[34]), "+f"(d[35]), "+f"(d[36]), "+f"(d[37]), "+f"(d[38]), "+f"(d[39]), "+f"(d[40]), "+f"(d[41]), "+f"(d[42]), "+f"(d[43]), "+f"(d[44]), "+f"(d[45]), "+f"(d[46]), "+f"(d[47]), "+f"(d[48]), "+f"(d[49]), "+f"(d[50]), "+f"(d[51]), "+f"(d[52]), "+f"(d[53]), "+f"(d[54]), "+f"(d[55]), "+f"(d[56]), "+f"(d[57]), "+f"(d[58]), "+f"(d[59]), "+f"(d[60]), "+f"(d[61]), "+f"(d[62]), "+f"(d[63]), "+f"(d[64]), "+f"(d[65]), "+f"(d[66]), "+f"(d[67])
    : "l"(desca), "l"(descb), "r"(scale_d));
}
__device__ __forceinline__ void wgmma_qk_n64(float (&d)[32], uint32_t a0, uint32_t a1, uint32_t a2, uint32_t a3, uint64_t descb) {
  asm volatile("{\n.reg .pred p;\nsetp.ne.b32 p, 0, 0;\n"
    "wgmma.mma_async.sync.aligned.m64n64k16.f32.bf16.bf16 "
    "{%0, %1, %2, %3, %4, %5, %6, %7, %8, %9, %10, %11, %12, %13, %14, %15, %16, %17, %18, %19, %20, %21, %22, %23, %24, %25, %26, %27, %28, %29, %30, %31}, "
    "{%32, %33, %34, %35}, %36, p, 1, 1, 0;\n}\n"
    : "=f"(d[0]), "=f"(d[1]), "=f"(d[2]), "=f"(d[3]), "=f"(d[4]), "=f"(d[5]), "=f"(d[6]), "=f"(d[7]), "=f"(d[8]), "=f"(d[9]), "=f"(d[10]), "=f"(d[11]), "=f"(d[12]), "=f"(d[13]), "=f"(d[14]), "=f"(d[15]), "=f"(d[16]), "=f"(d[17]), "=f"(d[18]), "=f"(d[19]), "=f"(d[20]), "=f"(d[21]), "=f"(d[22]), "=f"(d[23]), "=f"(d[24]), "=f"(d[25]), "=f"(d[26]), "=f"(d[27]), "=f"(d[28]), "=f"(d[29]), "=f"(d[30]), "=f"(d[31])
    : "r"(a0), "r"(a1), "r"(a2), "r"(a3), "l"(descb));
}
__device__ __forceinline__ void wgmma_pv_n24(float (&d)[12], uint32_t a0, uint32_t a1, uint32_t a2, uint32_t a3, uint64_t descb) {
  asm volatile("{\n.reg .pred p;\nsetp.eq.b32 p, 0, 0;\n"
    "wgmma.mma_async.sync.aligned.m64n24k16.f32.bf16.bf16 "
    "{%0, %1, %2, %3, %4, %5, %6, %7, %8, %9, %10, %11}, "
    "{%12, %13, %14, %15}, %16, p, 1, 1, 1;\n}\n"
    : "+f"(d[0]), "+f"(d[1]), "+f"(d[2]), "+f"(d[3]), "+f"(d[4]), "+f"(d[5]), "+f"(d[6]), "+f"(d[7]), "+f"(d[8]), "+f"(d[9]), "+f"(d[10]), "+f"(d[11])
    : "r"(a0), "r"(a1), "r"(a2), "r"(a3), "l"(descb));
}
__device__ __forceinline__ void wgmma_k3_n64(float (&d)[32], uint64_t desca, uint64_t descb, int scale_d) {
  asm volatile("{\n.reg .pred p;\nsetp.ne.b32 p, %34, 0;\n"
    "wgmma.mma_async.sync.aligned.m64n64k16.f32.bf16.bf16 "
    "{%0, %1, %2, %3, %4, %5, %6, %7, %8, %9, %10, %11, %12, %13, %14, %15, %16, %17, %18, %19, %20, %21, %22, %23, %24, %25, %26, %27, %28, %29, %30, %31}, "
    "%32, %33, p, 1, 1, 0, 1;\n}\n"
    : "+f"(d[0]), "+f"(d[1]), "+f"(d[2]), "+f"(d[3]), "+f"(d[4]), "+f"(d[5]), "+f"(d[6]), "+f"(d[7]), "+f"(d[8]), "+f"(d[9]), "+f"(d[10]), "+f"(d[11]), "+f"(d[12]), "+f"(d[13]), "+f"(d[14]), "+f"(d[15]), "+f"(d[16]), "+f"(d[17]), "+f"(d[18]), "+f"(d[19]), "+f"(d[20]), "+f"(d[21]), "+f"(d[22]), "+f"(d[23]), "+f"(d[24]), "+f"(d[25]), "+f"(d[26]), "+f"(d[27]), "+f"(d[28]), "+f"(d[29]), "+f"(d[30]), "+f"(d[31])
    : "l"(desca), "l"(descb), "r"(scale_d));
}
__device__ __forceinline__ void wgmma_bias_n40(float (&d)[32], uint64_t desca, uint64_t descb) {
  asm volatile("{\n.reg .pred p;\nsetp.eq.b32 p, 0, 0;\n"
    "wgmma.mma_async.sync.aligned.m64n40k16.f32.bf16.bf16 "
    "{%0, %1, %2, %3, %4, %5, %6, %7, %8, %9, %10, %11, %12, %13, %14, %15, %16, %17, %18, %19}, "
    "%20, %21, p, 1, 1, 0, 0;\n}\n"
    : "+f"(d[0]), "+f"(d[1]), "+f"(d[2]), "+f"(d[3]), "+f"(d[4]), "+f"(d[5]), "+f"(d[6]), "+f"(d[7]), "+f"(d[8]), "+f"(d[9]), "+f"(d[10]), "+f"(d[11]), "+f"(d[12]), "+f"(d[13]), "+f"(d[14]), "+f"(d[15]), "+f"(d[16]), "+f"(d[17]), "+f"(d[18]), "+f"(d[19])
    : "l"(desca), "l"(descb));
}
__device__ __forceinline__ void wgmma_bias_n48(float (&d)[32], uint64_t desca, uint64_t descb) {
  asm volatile("{\n.reg .pred p;\nsetp.eq.b32 p, 0, 0;\n"
    "wgmma.mma_async.sync.aligned.m64n48k16.f32.bf16.bf16 "
    "{%0, %1, %2, %3, %4, %5, %6, %7, %8, %9, %10, %11, %12, %13, %14, %15, %16, %17, %18, %19, %20, %21, %22, %23}, "
    "%24, %25, p, 1, 1, 0, 0;\n}\n"
    : "+f"(d[0]), "+f"(d[1]), "+f"(d[2]), "+f"(d[3]), "+f"(d[4]), "+f"(d[5]), "+f"(d[6]), "+f"(d[7]), "+f"(d[8]), "+f"(d[9]), "+f"(d[10]), "+f"(d[11]), "+f"(d[12]), "+f"(d[13]), "+f"(d[14]), "+f"(d[15]), "+f"(d[16]), "+f"(d[17]), "+f"(d[18]), "+f"(d[19]), "+f"(d[20]), "+f"(d[21]), "+f"(d[22]), "+f"(d[23])
    : "l"(desca), "l"(descb));
}
__device__ __forceinline__ void wgmma_bias_n32(float (&d)[32], uint64_t desca, uint64_t descb) {
  asm volatile("{\n.reg .pred p;\nsetp.eq.b32 p, 0, 0;\n"
    "wgmma.mma_async.sync.aligned.m64n32k16.f32.bf16.bf16 "
    "{%0, %1, %2, %3, %4, %5, %6, %7, %8, %9, %10, %11, %12, %13, %14, %15}, "
    "%16, %17, p, 1, 1, 0, 0;\n}\n"
    : "+f"(d[0]), "+f"(d[1]), "+f"(d[2]), "+f"(d[3]), "+f"(d[4]), "+f"(d[5]), "+f"(d[6]), "+f"(d[7]), "+f"(d[8]), "+f"(d[9]), "+f"(d[10]), "+f"(d[11]), "+f"(d[12]), "+f"(d[13]), "+f"(d[14]), "+f"(d[15])
    : "l"(desca), "l"(descb));
}

constexpr int K1_XS = 17408;
constexpr int K1_WS = 24576;
constexpr int K1_ST = K1_XS + K1_WS;
constexpr int K1_NST = 5;
constexpr int K1_OFF_MISC = K1_NST * K1_ST;
constexpr int K1_SMEM = K1_OFF_MISC + 2048 + 1024;
constexpr float QSCALE = 0.25f * 1.4426950408889634f;

__global__ void __launch_bounds__(544, 1)
k1_qkv(const __grid_constant__ CUtensorMap tm_x, const __grid_constant__ CUtensorMap tm_w, const __nv_bfloat16* __restrict__ x) {
    extern __shared__ uint8_t smem_raw[];
    const uint32_t sraw = smem_u32(smem_raw);
    const uint32_t sb = (sraw + 1023) & ~1023u;
    uint8_t* sp = smem_raw + (sb - sraw);
    const uint32_t full = sb + K1_OFF_MISC;
    const uint32_t empty = full + 64;
    float* s_mr = (float*)(sp + K1_OFF_MISC + 256);

    const int tid = threadIdx.x, warp = tid >> 5, lane = tid & 31;
    const int mt = blockIdx.x >> 3, nt = blockIdx.x & 7;
    pdl_launch();
    if (tid == 512) {
        for (int i = 0; i < K1_NST; i++) { mbar_init(full + 8 * i, 1); mbar_init(empty + 8 * i, 3); }
        fence_barrier_init();
        for (int kb = 0; kb < K1_NST; kb++) {
            mbar_expect_tx(full + 8 * kb, 16384 + K1_WS);
            tma_load_2d(sb + kb * K1_ST, &tm_x, kb * 64, mt * 128, full + 8 * kb);
            tma_load_3d(sb + kb * K1_ST + K1_XS, &tm_w, nt * 64, kb * 64, 0, full + 8 * kb);
        }
    }
    if (tid < K1_NST * 64) {
        *(uint4*)(sp + (tid >> 6) * K1_ST + 16384 + (tid & 63) * 16) =
            make_uint4(0x3F803F80u, 0x3F803F80u, 0x3F803F80u, 0x3F803F80u);
    }
    fence_proxy_async();
    __syncthreads();

    if (warp == 16) {
        if (lane == 0) {
            for (int kb = K1_NST; kb < 8; kb++) {
                const int s = kb % K1_NST;
                mbar_wait(empty + 8 * s, 0);
                mbar_expect_tx(full + 8 * s, 16384 + K1_WS);
                tma_load_2d(sb + s * K1_ST, &tm_x, kb * 64, mt * 128, full + 8 * s);
                tma_load_3d(sb + s * K1_ST + K1_XS, &tm_w, nt * 64, kb * 64, 0, full + 8 * s);
            }
        }
        __syncwarp();
        if (lane < FF / 128) g_act[blockIdx.x * (FF / 128) + lane] = 0xFFFFFFFFu;
        for (int i = lane; i < 128; i += 32) g_part[blockIdx.x * 128 + i] = make_float4(0.f, 0.f, 0.f, 0.f);
        if (blockIdx.x == 1) { g_cand[lane] = make_uint4(0, 0, 0, 0); g_cand[lane + 32] = make_uint4(0, 0, 0, 0); g_hflag[lane] = 0; g_sflag[lane] = 0; }
        if (blockIdx.x == 2) for (int i = lane; i < 1024; i += 32) g_oflag[i] = 0;
    } else if (warp >= 12) {
        const int r = tid - 384;
        const unsigned int tag = *(volatile unsigned int*)&g_epoch + 1u;
        {
            const int row = mt * 128 + nt * 16 + (r >> 3);
            const uint4* xp = (const uint4*)(x + (size_t)row * DM) + (r & 7);
            uint4 v[8];
#pragma unroll
            for (int i = 0; i < 8; i++) v[i] = __ldg(xp + i * 8);
            float s1 = 0.f;
#pragma unroll
            for (int i = 0; i < 8; i++)
                s1 += ((bf_lo(v[i].x) + bf_hi(v[i].x)) + (bf_lo(v[i].y) + bf_hi(v[i].y))) + ((bf_lo(v[i].z) + bf_hi(v[i].z)) + (bf_lo(v[i].w) + bf_hi(v[i].w)));
#pragma unroll
            for (int o = 1; o < 8; o <<= 1) s1 += __shfl_xor_sync(0xffffffffu, s1, o);
            const float mean = s1 * (1.f / DM);
            float q0 = 0.f, q1 = 0.f;
#pragma unroll
            for (int i = 0; i < 8; i++) {
                const uint32_t w[4] = {v[i].x, v[i].y, v[i].z, v[i].w};
#pragma unroll
                for (int j = 0; j < 4; j++) {
                    const float a = bf_lo(w[j]) - mean, b = bf_hi(w[j]) - mean;
                    q0 = fmaf(a, a, q0); q1 = fmaf(b, b, q1);
                }
            }
            float q = q0 + q1;
#pragma unroll
            for (int o = 1; o < 8; o <<= 1) q += __shfl_xor_sync(0xffffffffu, q, o);
            const float den = rbf(sqrtf(rbf(rbf(q * (1.f / DM)) + 1e-5f)));
            if ((r & 7) == 0)
                asm volatile("st.relaxed.gpu.global.v4.f32 [%0], {%1, %2, %3, %4};" ::"l"(g_ln1 + row), "f"(rbf(mean)), "f"(1.f / den),
                             "f"(__uint_as_float(tag)), "f"(0.f) : "memory");
        }
        {
            float4 v;
            int spins = 0;
            do {
                asm volatile("ld.relaxed.gpu.global.v4.f32 {%0, %1, %2, %3}, [%4];" : "=f"(v.x), "=f"(v.y), "=f"(v.z), "=f"(v.w) : "l"(g_ln1 + mt * 128 + r) : "memory");
            } while (__float_as_uint(v.z) != tag && ++spins < (1 << 22));
            s_mr[(r >> 1) * 4 + (r & 1)] = v.x;
            s_mr[(r >> 1) * 4 + 2 + (r & 1)] = v.y;
        }
        named_arrive(1, 512);
    } else {
        const int part = warp >> 2, hw = warp & 3;
        float acc[68];
#pragma unroll
        for (int i = 0; i < 68; i++) acc[i] = 0.f;
        fence_regs(acc);
#pragma unroll 1
        for (int kb = 0; kb < 8; kb++) {
            const int s = kb % K1_NST;
            mbar_wait(full + 8 * s, (kb / K1_NST) & 1);
            const uint64_t da = make_desc(sb + s * K1_ST + K1_XS + part * 8192, 1024, 1024, 1);
            const uint64_t db = make_desc(sb + s * K1_ST, 16, 1024, 1);
            wg_fence();
#pragma unroll
            for (int k = 0; k < 4; k++) wgmma_k1_n136(acc, da + k * 128, db + k * 2, (kb | k) != 0);
            wg_commit();
            if (kb > 0 && kb <= 8 - K1_NST) {
                wg_wait<1>();
                if ((tid & 127) == 0) mbar_arrive(empty + 8 * (kb - 1));
            }
        }
        wg_wait<0>();
        fence_regs(acc);
        named_sync(1, 512);

        const int t = lane & 3;
        const float cs0 = acc[64], cs1 = acc[66];
        const float sc = (part == 0) ? QSCALE : 1.f;
        const uint32_t stg = sb + (hw >> 1) * K1_ST + K1_XS + part * 8192 + (hw & 1) * 4096;
        const uint32_t st_addr = stg + ((lane >> 3) & 1) * 2048 + ((lane >> 4) * 8 + (lane & 7)) * 16;
#pragma unroll
        for (int j = 0; j < 16; j += 2) {
            uint32_t rr[4];
#pragma unroll
            for (int u = 0; u < 2; u++) {
                const int jj = j + u;
                const float4 mr = *(const float4*)(s_mr + (4 * jj + t) * 4);
                const float2 m2 = make_float2(mr.x, mr.y);
                const float ra = mr.z * sc, rb = mr.w * sc;
                rr[2 * u] = pack_bf16((acc[4 * jj] - m2.x * cs0) * ra, (acc[4 * jj + 1] - m2.y * cs0) * rb);
                rr[2 * u + 1] = pack_bf16((acc[4 * jj + 2] - m2.x * cs1) * ra, (acc[4 * jj + 3] - m2.y * cs1) * rb);
            }
            stmatrix_x4_trans(st_addr + j * 128, rr[0], rr[1], rr[2], rr[3]);
        }
        fence_proxy_async();
        __syncwarp();
        const int head = nt * 4 + hw;
        if (lane == 0) {
            uint8_t* dst;
            uint32_t hstride;
            if (part == 0) { dst = g_q + (size_t)head * 65536 + mt * 2048; hstride = 32768; }
            else { dst = g_kv + (size_t)head * 131072 + (mt >> 1) * 16384 + (part - 1) * 8192 + (mt & 1) * 2048; hstride = 4096; }
            bulk_s2g(dst, stg, 2048);
            bulk_s2g(dst + hstride, stg + 2048, 2048);
            asm volatile("cp.async.bulk.commit_group;" ::: "memory");
        }
        float nmax = 0.f;
#pragma unroll
        for (int i = 0; i < 4; i++) {
            const int tok = lane + 32 * i;
            const uint4 a = *(const uint4*)(sp + (stg - sb) + tok * 16);
            const uint4 b = *(const uint4*)(sp + (stg - sb) + 2048 + tok * 16);
            uint32_t n0 = fma_bf16x2(a.x, a.x, 0u), n1 = fma_bf16x2(b.x, b.x, 0u);
            n0 = fma_bf16x2(a.y, a.y, n0); n1 = fma_bf16x2(b.y, b.y, n1);
            n0 = fma_bf16x2(a.z, a.z, n0); n1 = fma_bf16x2(b.z, b.z, n1);
            n0 = fma_bf16x2(a.w, a.w, n0); n1 = fma_bf16x2(b.w, b.w, n1);
            const float n2 = ((bf_lo(n0) + bf_hi(n0)) + (bf_lo(n1) + bf_hi(n1))) * 1.125f;
            nmax = (n2 > nmax || n2 != n2) ? n2 : nmax;
        }
#pragma unroll
        for (int o = 16; o > 0; o >>= 1) {
            const float v = __shfl_xor_sync(0xffffffffu, nmax, o);
            nmax = (v > nmax || v != v) ? v : nmax;
        }
        if (lane == 0) {
            g_norm[(head * 16 + mt) * 3 + part] = nmax;
            asm volatile("cp.async.bulk.wait_group.read 0;" ::: "memory");
        }
    }
}

#define POLL_NS 50
constexpr int KF_CH_G = 16384, KF_CH_S = 20480, KF_NCH = 8;
constexpr int KF_OFF_WO = KF_NCH * KF_CH_S;
constexpr int KF_OFF_MISC = KF_OFF_WO + 65536;
constexpr int KF_SMEM = KF_OFF_MISC + 1536 + 1024;

__device__ __forceinline__ uint32_t exp2_pair_poly(float t0, float t1, uint32_t c2) {
    const uint32_t w = __byte_perm(__float_as_uint(t0), __float_as_uint(t1), 0x5410);
    uint32_t z;
    asm("lop3.b32 %0, %1, %2, %3, 0xEA;" : "=r"(z) : "r"(w), "r"(0x007F007Fu), "r"(0x3F803F80u));
    uint32_t p = fma_bf16x2(c2, z, 0xbc73bc73u);
    p = fma_bf16x2(p, z, 0x3f2f3f2fu);
    return p + w - z;
}
#define NEA 40
#define NEB 40
#define BIAS_(n) wgmma_bias_n##n
#define BIAS(n) BIAS_(n)
template <int LO, int HI, int NE>
__device__ __forceinline__ void softmax_part(const float (&s)[32], uint32_t (&p)[16], uint32_t c2) {
#pragma unroll
    for (int i = LO; i < HI; i++) {
        if (i < NE / 4) p[i] = exp2_pair_poly(s[2 * i], s[2 * i + 1], c2);
        else p[i] = pack_bf16(ex2f(s[2 * i]), ex2f(s[2 * i + 1]));
    }
}
#define KF_PV(P, OFF)                                                                              \
    _Pragma("unroll") for (int kk = 0; kk < 4; kk++)                                               \
        wgmma_pv_n24(o, P[4 * kk], P[4 * kk + 1], P[4 * kk + 2], P[4 * kk + 3], dv + ((OFF) + kk * 16));

__device__ __forceinline__ uint32_t make_key(float r_bf16, int token) {
    const uint32_t u = __float_as_uint(r_bf16) >> 16;
    const uint32_t o = (u & 0x8000u) ? (~u & 0xFFFFu) : (u | 0x8000u);
    return (o << 16) | (uint32_t)(0xFFFF - token);
}
__device__ __forceinline__ float key_value(uint32_t k) {
    const uint32_t o = k >> 16;
    const uint32_t u = (o & 0x8000u) ? (o & 0x7FFFu) : (~o & 0xFFFFu);
    return __uint_as_float(u << 16);
}
__device__ __forceinline__ int key_token(uint32_t k) { return 0xFFFF - (int)(k & 0xFFFFu); }
__device__ __forceinline__ void warp_top2(uint32_t a, uint32_t b, uint32_t& k1, uint32_t& k2) {
    k1 = __reduce_max_sync(0xffffffffu, a > b ? a : b);
    const uint32_t a2 = (a == k1) ? 0u : a, b2 = (b == k1) ? 0u : b;
    k2 = __reduce_max_sync(0xffffffffu, a2 > b2 ? a2 : b2);
}
__device__ __forceinline__ unsigned int ld_acquire(const unsigned int* p) {
    unsigned int v; asm volatile("ld.acquire.gpu.global.u32 %0, [%1];" : "=r"(v) : "l"(p) : "memory"); return v;
}
__device__ __forceinline__ void red_release_add(unsigned int* p) {
    asm volatile("red.release.gpu.global.add.u32 [%0], 1;" ::"l"(p) : "memory");
}

__global__ void __launch_bounds__(512, 1)
kf_main(const __grid_constant__ CUtensorMap tm_o, const __grid_constant__ CUtensorMap tm_wo,
        const __grid_constant__ CUtensorMap tm_g, const __grid_constant__ CUtensorMap tm_u, const __grid_constant__ CUtensorMap tm_d,
        const __nv_bfloat16* __restrict__ x, const __nv_bfloat16* __restrict__ wo, const __nv_bfloat16* __restrict__ w_r,
        const __nv_bfloat16* __restrict__ w_gate, const __nv_bfloat16* __restrict__ w_up, const __nv_bfloat16* __restrict__ w_down,
        __nv_bfloat16* __restrict__ out) {
    extern __shared__ uint8_t smem_raw[];
    const uint32_t sraw = smem_u32(smem_raw);
    const uint32_t sb = (sraw + 1023) & ~1023u;
    uint8_t* sp = smem_raw + (sb - sraw);
    const uint32_t kvbar = sb + KF_OFF_MISC;
    const uint32_t wbar = kvbar + 64;
    const uint32_t obar = wbar + 64;
    const uint32_t gbar = obar + 64;
    const uint32_t dbar = gbar + 8;
    unsigned int* s_cnt = (unsigned int*)(sp + KF_OFF_MISC + 208);
    volatile unsigned int* s_order = (volatile unsigned int*)(sp + KF_OFF_MISC + 1056);
    uint32_t* s_key = (uint32_t*)(sp + KF_OFF_MISC + 256);
    float* s_gu = (float*)(sp + KF_OFF_WO + 49152 + 8192 + 4608);
    uint4* s_sel = (uint4*)(sp + KF_OFF_MISC + 1024);
    const int tid = threadIdx.x;
    const int head = blockIdx.x >> 2, quarter = blockIdx.x & 3;
    const int mt = blockIdx.x >> 2, nt = blockIdx.x & 3;
    if (tid == 0) {
        for (int c = 0; c < 26; c++) mbar_init(kvbar + 8 * c, 1);
        for (int c = 0; c < 6; c++) s_cnt[c] = 0;
        fence_barrier_init();
        for (int kb = 0; kb < 4; kb++) {
            mbar_expect_tx(wbar + 8 * kb, 16384);
            tma_load_3d(sb + KF_OFF_WO + kb * 16384, &tm_wo, 0, kb * 64, nt * 2, wbar + 8 * kb);
        }
    }
    if (tid == 32) {
        prefetch_l2((const uint8_t*)wo + blockIdx.x * 4096, 4096);
        prefetch_l2((const uint8_t*)w_gate + blockIdx.x * 14336, 14336);
        prefetch_l2((const uint8_t*)w_up + blockIdx.x * 14336, 14336);
        prefetch_l2((const uint8_t*)w_down + blockIdx.x * 14336, 14336);
    }
    if (tid < 24) *(uint4*)(sp + KF_OFF_MISC + 1152 + tid * 16) =
        tid < 8 ? make_uint4(0x42FE4380u, 0x00003D80u, 0u, 0u) : (tid < 16 ? make_uint4(0x3F804380u, 0x00003E00u, 0u, 0u) : make_uint4(0u, 0u, 0u, 0u));
    for (int i = tid; i < KF_NCH * 256; i += 512)
        *(uint4*)(sp + (i >> 8) * KF_CH_S + 16384 + (i & 255) * 16) =
            make_uint4(0x3F803F80u, 0x3F803F80u, 0x3F803F80u, 0x3F803F80u);
    fence_proxy_async();
    __syncthreads();
    pdl_wait();
    const uint8_t* kvsrc = g_kv + (size_t)head * (KF_NCH * KF_CH_G);
    if (tid == 32) {
        mbar_expect_tx(kvbar, KF_CH_G);
        bulk_g2s(sb, kvsrc, KF_CH_G, kvbar);
    }
    const int wg = tid >> 7, warp = (tid >> 5) & 3, lane = tid & 31, g = lane >> 2, t = lane & 3;
    if (tid < 32) {
        const int m16 = lane & 15;
        float kn = g_norm[(head * 16 + m16) * 3 + 1];
        float vn = g_norm[(head * 16 + m16) * 3 + 2];
        float qn = g_norm[(head * 16 + quarter * 4 + (lane & 3)) * 3 + 0];
        const bool bad = !(kn < 1e30f) || !(vn < 1e9f) || !(qn < 1e30f);
#pragma unroll
        for (int o = 8; o > 0; o >>= 1) {
            kn = fmaxf(kn, __shfl_xor_sync(0xffffffffu, kn, o));
            qn = fmaxf(qn, __shfl_xor_sync(0xffffffffu, qn, o));
        }
        const bool ok = __all_sync(0xffffffffu, !bad && (qn * kn <= 9000.f));
        if (lane == 0) s_cnt[4] = ok ? 1u : 0u;
    }
    uint32_t qn2[2][4];
#pragma unroll
    for (int ps = 0; ps < 2; ps++) {
        const uint8_t* qb = g_q + (size_t)head * 65536 + (quarter * 512 + ps * 256 + wg * 64 + warp * 16 + g) * 16 + t * 4;
        qn2[ps][0] = *(const uint32_t*)(qb);
        qn2[ps][1] = *(const uint32_t*)(qb + 128);
        qn2[ps][2] = *(const uint32_t*)(qb + 32768);
        qn2[ps][3] = *(const uint32_t*)(qb + 32768 + 128);
    }

    __syncthreads();
    const bool fast = __all_sync(0xffffffffu, s_cnt[4] != 0u);
    if (tid == 32) {
        for (int c = 1; c < KF_NCH; c++) {
            mbar_expect_tx(kvbar + 8 * c, KF_CH_G);
            bulk_g2s(sb + c * KF_CH_S, kvsrc + c * KF_CH_G, KF_CH_G, kvbar + 8 * c);
        }
    }
    const uint64_t dbias_a = make_desc(sb + KF_OFF_MISC + 1152, 0, 0, 0);
    const uint64_t dbias_b = make_desc(sb + KF_OFF_MISC + 1280, 128, 0, 0);
    const uint32_t c2reg = 0x3eab3eabu;
    const uint64_t dk0 = make_desc(sb, 4096, 128, 0);
    const uint64_t dv0 = make_desc(sb + 8192, 128, 4096, 0);

#pragma unroll 1
    for (int pass = 0; pass < 2; pass++) {
        const int row0 = quarter * 512 + pass * 256 + wg * 64 + warp * 16 + g;
        uint32_t qa[4];
#pragma unroll
        for (int i = 0; i < 4; i++) qa[i] = pass ? qn2[1][i] : qn2[0][i];
        float o[12];
#pragma unroll
        for (int i = 0; i < 12; i++) o[i] = 0.f;
        fence_regs(o);
#define KF_RELEASE_CHUNK(c)                                                                          \
        if (pass == 1 && (c) >= 1 && (c) <= 4) {                                                     \
            named_sync(4 + wg, 128);            \
            if ((tid & 127) == 0 && atomicAdd(&s_cnt[(c) - 1], 1u) == 3u) {                          \
                mbar_expect_tx(wbar + 8 * (3 + (c)), 16384);                                         \
                tma_load_3d(sb + ((c) - 1) * KF_CH_S, &tm_wo, 0, (3 + (c)) * 64, nt * 2, wbar + 8 * (3 + (c))); \
            }                                                                                        \
        }
        if (fast) {
#pragma unroll 1
            for (int c = 0; c < KF_NCH; c++) {
                const uint64_t dk = dk0 + (uint64_t)(c * (KF_CH_S >> 4));
                const uint64_t dv = dv0 + (uint64_t)(c * (KF_CH_S >> 4));
                float s0[32], s1[32], s2[32], s3[32];
                uint32_t p0[16], p1[16], p2[16], p3[16];
                mbar_wait(kvbar + 8 * c, 0);
                wg_wait<1>();
                wg_fence();
                wgmma_qk_n64(s0, qa[0], qa[1], qa[2], qa[3], dk);
                BIAS(NEA)(s0, dbias_a, dbias_b);
                wg_commit();
                wg_wait<1>();
                KF_RELEASE_CHUNK(c);
                wg_fence();
                wgmma_qk_n64(s1, qa[0], qa[1], qa[2], qa[3], dk + 64);
                BIAS(NEB)(s1, dbias_a, dbias_b);
                wg_commit();
                wg_wait<1>();
                fence_regs(s0);
                softmax_part<0, 16, NEA>(s0, p0, c2reg);
                wg_fence();
                KF_PV(p0, 0);
                wg_commit();
                wg_wait<1>();
                fence_regs(s1);
                softmax_part<0, 8, NEB>(s1, p1, c2reg);
                wg_wait<0>();
                wg_fence();
                wgmma_qk_n64(s2, qa[0], qa[1], qa[2], qa[3], dk + 128);
                BIAS(NEA)(s2, dbias_a, dbias_b);
                wg_commit();
                softmax_part<8, 16, NEB>(s1, p1, c2reg);
                wg_fence();
                KF_PV(p1, 64);
                wg_commit();
                wg_wait<1>();
                fence_regs(s2);
                softmax_part<0, 8, NEA>(s2, p2, c2reg);
                wg_wait<0>();
                wg_fence();
                wgmma_qk_n64(s3, qa[0], qa[1], qa[2], qa[3], dk + 192);
                BIAS(NEB)(s3, dbias_a, dbias_b);
                wg_commit();
                softmax_part<8, 16, NEA>(s2, p2, c2reg);
                wg_fence();
                KF_PV(p2, 128);
                wg_commit();
                wg_wait<1>();
                fence_regs(s3);
                softmax_part<0, 16, NEB>(s3, p3, c2reg);
                wg_fence();
                KF_PV(p3, 192);
                wg_commit();
            }
            wg_wait<0>();
            fence_regs(o);
        } else {
            float m0 = -INFINITY, m1 = -INFINITY;
#pragma unroll 1
            for (int b = 0; b < 32; b++) {
                const int c = b >> 2;
                const uint64_t dk = dk0 + (uint64_t)(c * (KF_CH_S >> 4) + (b & 3) * 64);
                const uint64_t dv = dv0 + (uint64_t)(c * (KF_CH_S >> 4) + (b & 3) * 64);
                float s[32];
                uint32_t p[16];
                mbar_wait(kvbar + 8 * c, 0);
                wg_fence();
                wgmma_qk_n64(s, qa[0], qa[1], qa[2], qa[3], dk);
                wg_commit();
                if ((b & 3) == 0) { KF_RELEASE_CHUNK(c); }
                wg_wait<0>();
                fence_regs(s);
                float x0 = s[0], x1 = s[2];
#pragma unroll
                for (int j = 0; j < 8; j++) {
                    x0 = fmaxf(x0, fmaxf(s[4 * j], s[4 * j + 1]));
                    x1 = fmaxf(x1, fmaxf(s[4 * j + 2], s[4 * j + 3]));
                }
                x0 = fmaxf(x0, __shfl_xor_sync(0xffffffffu, x0, 1));
                x0 = fmaxf(x0, __shfl_xor_sync(0xffffffffu, x0, 2));
                x1 = fmaxf(x1, __shfl_xor_sync(0xffffffffu, x1, 1));
                x1 = fmaxf(x1, __shfl_xor_sync(0xffffffffu, x1, 2));
                const float n0 = fmaxf(m0, x0), n1 = fmaxf(m1, x1);
                const float c0 = ex2f(m0 - n0), c1 = ex2f(m1 - n1);
                m0 = n0; m1 = n1;
#pragma unroll
                for (int j = 0; j < 3; j++) {
                    o[4 * j] *= c0; o[4 * j + 1] *= c0; o[4 * j + 2] *= c1; o[4 * j + 3] *= c1;
                }
#pragma unroll
                for (int j = 0; j < 8; j++) {
                    p[2 * j] = pack_bf16(ex2f(s[4 * j] - n0), ex2f(s[4 * j + 1] - n0));
                    p[2 * j + 1] = pack_bf16(ex2f(s[4 * j + 2] - n1), ex2f(s[4 * j + 3] - n1));
                }
                fence_regs(o);
                wg_fence();
                KF_PV(p, 0);
                wg_commit();
                wg_wait<0>();
                fence_regs(o);
            }
        }
        const float inv0 = 1.f / o[8], inv1 = 1.f / o[10];
        {
            uint32_t v0 = pack_bf16(o[0] * inv0, o[1] * inv0), v1 = pack_bf16(o[4] * inv0, o[5] * inv0);
            uint32_t v2 = pack_bf16(o[2] * inv1, o[3] * inv1), v3 = pack_bf16(o[6] * inv1, o[7] * inv1);
            const bool o1 = t & 1, o2 = t & 2;
            uint32_t s0 = o1 ? v0 : v1, s1 = o1 ? v2 : v3;
            s0 = __shfl_xor_sync(0xffffffffu, s0, 1); s1 = __shfl_xor_sync(0xffffffffu, s1, 1);
            uint32_t a0 = o1 ? s0 : v0, a1 = o1 ? v1 : s0, b0 = o1 ? s1 : v2, b1 = o1 ? v3 : s1;
            uint32_t x0 = o2 ? a0 : b0, x1 = o2 ? a1 : b1;
            x0 = __shfl_xor_sync(0xffffffffu, x0, 2); x1 = __shfl_xor_sync(0xffffffffu, x1, 2);
            uint4 r;
            r.x = o2 ? x0 : a0; r.y = o2 ? x1 : a1; r.z = o2 ? b0 : x0; r.w = o2 ? b1 : x1;
            *(uint4*)(g_o + (size_t)(row0 + (t >> 1) * 8) * DM + head * 16 + (t & 1) * 8) = r;
        }
    }
    if ((tid >> 5) != 10) named_arrive(1, 512);
    named_sync(4 + wg, 128);
    if ((tid & 127) == 0) {
        asm volatile("fence.acq_rel.gpu;" ::: "memory");
        asm volatile("red.relaxed.gpu.global.add.u32 [%0], 1;" ::"l"(&g_oflag[(quarter * 8 + 4 + wg) * 32 + (head >> 2) * 4]) : "memory");
        asm volatile("red.relaxed.gpu.global.add.u32 [%0], 1;" ::"l"(&g_oflag[(quarter * 8 + wg) * 32 + (head >> 2) * 4]) : "memory");
    }

    if (wg < 2) {
        const int wi = warp;
        const int r0 = mt * 64 + wi * 16 + g;
        const int cb = nt * 128 + wg * 64;
        uint32_t xr[16], wr[8];
#pragma unroll
        for (int j = 0; j < 8; j++) {
            xr[2 * j] = __ldg((const uint32_t*)(x + (size_t)r0 * DM + cb + 8 * j + 2 * t));
            xr[2 * j + 1] = __ldg((const uint32_t*)(x + (size_t)(r0 + 8) * DM + cb + 8 * j + 2 * t));
            wr[j] = __ldg((const uint32_t*)(w_r + cb + 8 * j + 2 * t));
        }
        float wsum = 0.f;
        {
            const uint4 a = __ldg((const uint4*)(w_r + lane * 16)), b = __ldg((const uint4*)(w_r + lane * 16 + 8));
            const uint32_t w[8] = {a.x, a.y, a.z, a.w, b.x, b.y, b.z, b.w};
#pragma unroll
            for (int i = 0; i < 8; i++) wsum += bf_lo(w[i]) + bf_hi(w[i]);
#pragma unroll
            for (int o = 16; o > 0; o >>= 1) wsum += __shfl_xor_sync(0xffffffffu, wsum, o);
        }
        float acc[32];
#pragma unroll
        for (int i = 0; i < 32; i++) acc[i] = 0.f;
        fence_regs(acc);
#pragma unroll 1
        for (int i = 0; i < 8; i++) {
            mbar_wait(obar + 8 * i, 0);
            const int kb = __shfl_sync(0xffffffffu, (int)s_order[i], 0);
            mbar_wait(wbar + 8 * kb, 0);
            const uint32_t wa = (kb < 4) ? (KF_OFF_WO + kb * 16384) : ((kb - 4) * KF_CH_S);
            const uint64_t da = make_desc(sb + (4 + (kb >> 1)) * KF_CH_S + (kb & 1) * 8192, 16, 1024, 1);
            const uint64_t db = make_desc(sb + wa + wg * 8192, 1024, 1024, 1);
            wg_fence();
#pragma unroll
            for (int k = 0; k < 4; k++) wgmma_k3_n64(acc, da + k * 2, db + k * 128, (i | k) != 0);
            wg_commit();
        }
        wg_wait<0>();
        fence_regs(acc);
        float hv[32];
        uint32_t hp[16];
        float s0 = 0.f, s1 = 0.f, d0 = 0.f, d1 = 0.f;
#pragma unroll
        for (int j = 0; j < 8; j++) {
            const uint32_t a01 = pack_bf16(acc[4 * j], acc[4 * j + 1]), a23 = pack_bf16(acc[4 * j + 2], acc[4 * j + 3]);
            hp[2 * j] = pack_bf16(bf_lo(xr[2 * j]) + bf_lo(a01), bf_hi(xr[2 * j]) + bf_hi(a01));
            hp[2 * j + 1] = pack_bf16(bf_lo(xr[2 * j + 1]) + bf_lo(a23), bf_hi(xr[2 * j + 1]) + bf_hi(a23));
            hv[4 * j] = bf_lo(hp[2 * j]); hv[4 * j + 1] = bf_hi(hp[2 * j]);
            hv[4 * j + 2] = bf_lo(hp[2 * j + 1]); hv[4 * j + 3] = bf_hi(hp[2 * j + 1]);
            const float wl = bf_lo(wr[j]), wh = bf_hi(wr[j]);
            s0 += hv[4 * j] + hv[4 * j + 1];
            s1 += hv[4 * j + 2] + hv[4 * j + 3];
            d0 = fmaf(hv[4 * j], wl, fmaf(hv[4 * j + 1], wh, d0));
            d1 = fmaf(hv[4 * j + 2], wl, fmaf(hv[4 * j + 3], wh, d1));
        }
        float mu0 = s0 * (1.f / 16), mu1 = s1 * (1.f / 16);
        float q0 = 0.f, q1 = 0.f;
#pragma unroll
        for (int j = 0; j < 8; j++) {
            float a = hv[4 * j] - mu0, b = hv[4 * j + 1] - mu0, c = hv[4 * j + 2] - mu1, d = hv[4 * j + 3] - mu1;
            q0 = fmaf(a, a, fmaf(b, b, q0));
            q1 = fmaf(c, c, fmaf(d, d, q1));
        }
#pragma unroll
        for (int o = 1; o < 4; o <<= 1) {
            const float m0 = __shfl_xor_sync(0xffffffffu, mu0, o), m1 = __shfl_xor_sync(0xffffffffu, mu1, o);
            const float e0 = __shfl_xor_sync(0xffffffffu, q0, o), e1 = __shfl_xor_sync(0xffffffffu, q1, o);
            d0 += __shfl_xor_sync(0xffffffffu, d0, o);
            d1 += __shfl_xor_sync(0xffffffffu, d1, o);
            const float f0 = mu0 - m0, f1 = mu1 - m1;
            q0 = q0 + e0 + f0 * f0 * (8.f * o);
            q1 = q1 + e1 + f1 * f1 * (8.f * o);
            mu0 = 0.5f * (mu0 + m0); mu1 = 0.5f * (mu1 + m1);
        }
        float4* part = g_part + (size_t)mt * 512 + wi * 16 + g;
        if (t < 2) {
            float4* dst = part + (nt * 2 + wg) * 64 + t * 8;
            const float a = t ? mu1 : mu0, b = t ? q1 : q0, c = t ? d1 : d0;
            asm volatile("st.relaxed.gpu.global.v4.f32 [%0], {%1, %2, %3, %4};" ::"l"(dst), "f"(a), "f"(b), "f"(c), "f"(1.0f) : "memory");
        }
        const uint32_t stg_off = KF_OFF_WO + (wi >> 1) * 16384 + wg * 8192 + (wi & 1) * 4096;
        const uint32_t stg_o = sb + stg_off, stg_h = stg_o + 2048;
        const int srow = (lane & 7) + ((lane >> 3) & 1) * 8;
        const int sj = lane >> 4;
        named_sync(4 + wg, 128);
#pragma unroll
        for (int j = 0; j < 8; j += 2) {
            const uint32_t off = srow * 128 + (((j + sj) ^ (srow & 7)) << 4);
            stmatrix_x4(stg_h + off, hp[2 * j], hp[2 * j + 1], hp[2 * j + 2], hp[2 * j + 3]);
        }
        __syncwarp();
#pragma unroll
        for (int i = 0; i < 4; i++) {
            const int row = i * 4 + (lane >> 3), ch = lane & 7;
            const uint4 vh = *(const uint4*)(sp + stg_off + 2048 + row * 128 + ((ch ^ (row & 7)) << 4));
            *(uint4*)(g_h + (size_t)(mt * 64 + wi * 16 + row) * DM + cb + ch * 8) = vh;
        }
        named_arrive(8, 288);
        float mean[2], den[2], rr[2];
        {
            float4 v[4];
            int spins = 0;
            while (true) {
#pragma unroll
                for (int i = 0; i < 4; i++) {
                    const float4* p = part + (t + (i & 1) * 4) * 64 + (i >> 1) * 8;
                    asm volatile("ld.relaxed.gpu.global.v4.f32 {%0, %1, %2, %3}, [%4];" : "=f"(v[i].x), "=f"(v[i].y), "=f"(v[i].z), "=f"(v[i].w) : "l"(p) : "memory");
                }
                const bool ok = (v[0].w != 0.f) && (v[1].w != 0.f) && (v[2].w != 0.f) && (v[3].w != 0.f);
                if (__all_sync(0xffffffffu, ok) || ++spins > (1 << 22)) break;
            }
#pragma unroll
            for (int u = 0; u < 2; u++) {
                float mu = v[2 * u].x + v[2 * u + 1].x, m2 = v[2 * u].y + v[2 * u + 1].y, hw = v[2 * u].z + v[2 * u + 1].z;
#pragma unroll
                for (int o = 1; o < 4; o <<= 1) {
                    mu += __shfl_xor_sync(0xffffffffu, mu, o);
                    m2 += __shfl_xor_sync(0xffffffffu, m2, o);
                    hw += __shfl_xor_sync(0xffffffffu, hw, o);
                }
                mu *= 0.125f;
                const float da = v[2 * u].x - mu, db = v[2 * u + 1].x - mu;
                float dd = 64.f * (da * da + db * db);
#pragma unroll
                for (int o = 1; o < 4; o <<= 1) dd += __shfl_xor_sync(0xffffffffu, dd, o);
                m2 += dd;
                mean[u] = rbf(mu);
                den[u] = rbf(sqrtf(rbf(rbf(m2 * (1.f / DM)) + 1e-5f)));
                rr[u] = rbf((hw - mean[u] * wsum) / den[u]);
            }
        }
        named_arrive(3, 512);
        if (nt == 0 && wg == 0) {
            float2* s_st = (float2*)(sp + KF_OFF_WO + 49152);
            if (t == 0) {
                s_key[wi * 16 + g] = make_key(rr[0], r0);
                s_key[wi * 16 + g + 8] = make_key(rr[1], r0 + 8);
                s_st[wi * 16 + g] = make_float2(mean[0], den[0]);
                s_st[wi * 16 + g + 8] = make_float2(mean[1], den[1]);
            }
            named_sync(4, 128);
            if (warp == 0) {
                uint32_t k1, k2;
                warp_top2(s_key[lane], s_key[lane + 32], k1, k2);
                if (lane < 2) {
                    const uint32_t k = lane ? k2 : k1;
                    const float2 st = s_st[key_token(k) & 63];
                    asm volatile("st.relaxed.gpu.global.v4.u32 [%0], {%1, %2, %3, %4};" ::"l"(g_cand + mt * 2 + lane), "r"(k),
                                 "r"(1u), "r"(__float_as_uint(st.x)), "r"(__float_as_uint(st.y)) : "memory");
                }
            }
        }
        const float i0 = 1.f / den[0], i1 = 1.f / den[1];
#pragma unroll
        for (int j = 0; j < 8; j += 2) {
            uint32_t ro[4];
#pragma unroll
            for (int u = 0; u < 2; u++) {
                const int jj = j + u;
                const float a = hv[4 * jj], b = hv[4 * jj + 1], c = hv[4 * jj + 2], d = hv[4 * jj + 3];
                const uint32_t u01 = pack_bf16(a - mean[0], b - mean[0]), u23 = pack_bf16(c - mean[1], d - mean[1]);
                const uint32_t n01 = pack_bf16(bf_lo(u01) * i0, bf_hi(u01) * i0), n23 = pack_bf16(bf_lo(u23) * i1, bf_hi(u23) * i1);
                ro[2 * u] = pack_bf16(a + bf_lo(n01), b + bf_hi(n01));
                ro[2 * u + 1] = pack_bf16(c + bf_lo(n23), d + bf_hi(n23));
            }
            const uint32_t off = srow * 128 + (((j + sj) ^ (srow & 7)) << 4);
            stmatrix_x4(stg_o + off, ro[0], ro[1], ro[2], ro[3]);
        }
        __syncwarp();
#pragma unroll
        for (int i = 0; i < 4; i++) {
            const int row = i * 4 + (lane >> 3), ch = lane & 7;
            const uint4 vo = *(const uint4*)(sp + stg_off + row * 128 + ((ch ^ (row & 7)) << 4));
            *(uint4*)(out + (size_t)(mt * 64 + wi * 16 + row) * DM + cb + ch * 8) = vo;
        }
        named_sync(4 + wg, 128);
        if ((tid & 127) == 0) red_release_add(&g_sflag[mt]);
    } else {
        const bool worker = blockIdx.x < FF / 16;
        const bool downer = blockIdx.x >= 64;
        const int mtid = tid - 256, mwarp = mtid >> 5;
        const int c0 = (blockIdx.x - 64) * 8;
        float* s_x = (float*)(sp + KF_OFF_WO + 49152 + 8192);
        float* s_red = (float*)(sp + KF_OFF_WO + 49152 + 8192 + 4096);
        if (mwarp == 2) {
            named_sync(1, 512);
            uint32_t done = 0;
            int n = 0, spins = 0;
            while (done != 0xFFu && ++spins < (1 << 22)) {
                const bool rdy = lane < 8 && ld_acquire(&g_oflag[mt * 32 + lane * 4]) >= 4u;
                uint32_t todo = __ballot_sync(0xffffffffu, rdy) & ~done;
                done |= todo;
                if (todo && lane == 0) {
                    asm volatile("fence.proxy.async.global;" ::: "memory");
                    while (todo) {
                        const int kb = __ffs(todo) - 1;
                        todo &= todo - 1;
                        s_order[n] = kb;
                        mbar_expect_tx(obar + 8 * n, 8192);
                        tma_load_3d(sb + (4 + (kb >> 1)) * KF_CH_S + (kb & 1) * 8192, &tm_o, 0, mt * 64, kb, obar + 8 * n);
                        n++;
                    }
                }
                n = __shfl_sync(0xffffffffu, n, 0);
                if (done != 0xFFu) __nanosleep(POLL_NS);
            }
            if (lane == 0 && worker) {
                mbar_expect_tx(gbar, 32768);
                for (int i = 0; i < 4; i++) {
                    tma_load_2d(sb + i * KF_CH_S + 16384, &tm_g, blockIdx.x * 16, i * 128, gbar);
                    tma_load_2d(sb + (4 + i) * KF_CH_S + 16384, &tm_u, blockIdx.x * 16, i * 128, gbar);
                }
            }
        }
        if (mwarp == 1) {
            named_sync(8, 288);
            if (lane == 0) {
                red_release_add(&g_hflag[mt]);
                if (downer) {
                    mbar_expect_tx(dbar, 7 * 4096);
                    for (int i = 0; i < 7; i++) tma_load_2d(sb + (4 + (i >> 2)) * KF_CH_S + (i & 3) * 4096, &tm_d, c0, i * 256, dbar);
                }
            }
            __syncwarp();
        }
        named_sync(3, 512);
        if (mwarp == 0) {
            uint4 ca, cb4;
            int spins = 0;
            while (true) {
                asm volatile("ld.relaxed.gpu.global.v4.u32 {%0, %1, %2, %3}, [%4];" : "=r"(ca.x), "=r"(ca.y), "=r"(ca.z), "=r"(ca.w) : "l"(g_cand + 2 * lane) : "memory");
                asm volatile("ld.relaxed.gpu.global.v4.u32 {%0, %1, %2, %3}, [%4];" : "=r"(cb4.x), "=r"(cb4.y), "=r"(cb4.z), "=r"(cb4.w) : "l"(g_cand + 2 * lane + 1) : "memory");
                const unsigned int hf = ld_acquire(&g_hflag[lane]);
                const bool ok = ca.y != 0 && cb4.y != 0 && hf >= 4u;
                if (__all_sync(0xffffffffu, ok) || ++spins > (1 << 22)) break;
            }
            uint32_t k1, k2;
            warp_top2(ca.x, cb4.x, k1, k2);
            if (ca.x == k1) s_sel[0] = ca;
            if (cb4.x == k1) s_sel[0] = cb4;
            if (ca.x == k2) s_sel[1] = ca;
            if (cb4.x == k2) s_sel[1] = cb4;
        }
        named_sync(2, 256);
        int idx[2];
        float mean[2], inv[2], rv[2];
#pragma unroll
        for (int u = 0; u < 2; u++) {
            const uint4 c = s_sel[u];
            idx[u] = key_token(c.x);
            rv[u] = key_value(c.x);
            mean[u] = __uint_as_float(c.z);
            inv[u] = 1.f / __uint_as_float(c.w);
        }
        float hfin = 0.f;
        if (downer && mtid < 16) hfin = __bfloat162float(__ldcg((const __nv_bfloat16*)(g_h + (size_t)((mtid >> 3) ? idx[1] : idx[0]) * DM + c0 + (mtid & 7))));
        if (worker) {
            {
                const uint32_t h0 = __ldcg((const uint32_t*)(g_h + (size_t)idx[0] * DM + 2 * mtid));
                const uint32_t h1 = __ldcg((const uint32_t*)(g_h + (size_t)idx[1] * DM + 2 * mtid));
                const uint32_t u0 = pack_bf16(bf_lo(h0) - mean[0], bf_hi(h0) - mean[0]), u1 = pack_bf16(bf_lo(h1) - mean[1], bf_hi(h1) - mean[1]);
                const uint32_t n0 = pack_bf16(bf_lo(u0) * inv[0], bf_hi(u0) * inv[0]), n1 = pack_bf16(bf_lo(u1) * inv[1], bf_hi(u1) * inv[1]);
                *(float4*)(s_x + 4 * mtid) = make_float4(bf_lo(n0), bf_lo(n1), bf_hi(n0), bf_hi(n1));
            }
            mbar_wait(gbar, 0);
            named_sync(2, 256);
            float acc[16];
#pragma unroll
            for (int i = 0; i < 16; i++) acc[i] = 0.f;
            const uint8_t* wbase = sp + ((mwarp >> 2) * 4 + (mwarp & 3)) * KF_CH_S + 16384 + lane * 16;
            const float* xb = s_x + 2 * (128 * (mwarp & 3) + (lane >> 1));
#pragma unroll
            for (int j = 0; j < 8; j++) {
                const uint4 w = *(const uint4*)(wbase + j * 512);
                const float2 xx = *(const float2*)(xb + 32 * j);
                const uint32_t ww[4] = {w.x, w.y, w.z, w.w};
#pragma unroll
                for (int q = 0; q < 4; q++) {
                    const float wl = bf_lo(ww[q]), wh = bf_hi(ww[q]);
                    acc[2 * q] = fmaf(xx.x, wl, acc[2 * q]); acc[2 * q + 1] = fmaf(xx.x, wh, acc[2 * q + 1]);
                    acc[8 + 2 * q] = fmaf(xx.y, wl, acc[8 + 2 * q]); acc[8 + 2 * q + 1] = fmaf(xx.y, wh, acc[8 + 2 * q + 1]);
                }
            }
#define KF_STEP(O, N)                                                          \
            {                                                                  \
                const bool up = (lane & (O)) != 0;                             \
                _Pragma("unroll") for (int i = 0; i < (N); i++) {              \
                    const float send = up ? acc[i] : acc[i + (N)];             \
                    const float keep = up ? acc[i + (N)] : acc[i];             \
                    acc[i] = keep + __shfl_xor_sync(0xffffffffu, send, (O));   \
                }                                                              \
            }
            KF_STEP(16, 8) KF_STEP(8, 4) KF_STEP(4, 2) KF_STEP(2, 1)
            {
                const int v = ((lane & 16) ? 8 : 0) + ((lane & 8) ? 4 : 0) + ((lane & 4) ? 2 : 0) + ((lane & 2) ? 1 : 0);
                s_gu[mwarp * 32 + (v >> 3) * 16 + (lane & 1) * 8 + (v & 7)] = acc[0];
            }
            named_sync(2, 256);
            if (mtid < 16) {
                uint32_t a2 = 0;
#pragma unroll
                for (int u = 0; u < 2; u++) {
                    const float* pg = s_gu + u * 16 + mtid;
                    const float gb = rbf((pg[0] + pg[32]) + (pg[64] + pg[96]));
                    const float ub = rbf((pg[128] + pg[160]) + (pg[192] + pg[224]));
                    const float sg = rbf(gb / (1.f + __expf(-gb)));
                    const float a = sg * ub;
                    uint32_t ab = (uint32_t)__bfloat16_as_ushort(__float2bfloat16_rn(a));
                    if (ab == 0xFFFFu) ab = 0x7FFFu;
                    a2 |= ab << (16 * u);
                }
                asm volatile("st.relaxed.gpu.global.u32 [%0], %1;" ::"l"(g_act + blockIdx.x * 16 + mtid), "r"(a2) : "memory");
            }
        }
        if (downer) {
            uint32_t av[7];
            {
                int spins = 0;
                while (true) {
                    bool ok = true;
#pragma unroll
                    for (int j = 0; j < 7; j++) {
                        asm volatile("ld.relaxed.gpu.global.u32 %0, [%1];" : "=r"(av[j]) : "l"(g_act + mtid + 256 * j) : "memory");
                        ok = ok && ((av[j] & 0xFFFFu) != 0xFFFFu) && ((av[j] >> 16) != 0xFFFFu);
                    }
                    if (mtid < 2) ok = ok && (ld_acquire(&g_sflag[(mtid ? idx[1] : idx[0]) >> 6]) >= 8u);
                    if (__all_sync(0xffffffffu, ok) || ++spins > (1 << 20)) break;
                    __nanosleep(20);
                }
            }
            mbar_wait(dbar, 0);
            float acc[16];
#pragma unroll
            for (int i = 0; i < 16; i++) acc[i] = 0.f;
#pragma unroll
            for (int j = 0; j < 7; j++) {
                const uint4 w = *(const uint4*)(sp + (4 + (j >> 2)) * KF_CH_S + (j & 3) * 4096 + mtid * 16);
                const float a0 = bf_lo(av[j]), a1 = bf_hi(av[j]);
                const uint32_t ww[4] = {w.x, w.y, w.z, w.w};
#pragma unroll
                for (int q = 0; q < 4; q++) {
                    const float wl = bf_lo(ww[q]), wh = bf_hi(ww[q]);
                    acc[2 * q] = fmaf(a0, wl, acc[2 * q]); acc[2 * q + 1] = fmaf(a0, wh, acc[2 * q + 1]);
                    acc[8 + 2 * q] = fmaf(a1, wl, acc[8 + 2 * q]); acc[8 + 2 * q + 1] = fmaf(a1, wh, acc[8 + 2 * q + 1]);
                }
            }
            KF_STEP(16, 8) KF_STEP(8, 4) KF_STEP(4, 2) KF_STEP(2, 1)
            acc[0] += __shfl_xor_sync(0xffffffffu, acc[0], 1);
            if ((lane & 1) == 0) {
                const int v = ((lane & 16) ? 8 : 0) + ((lane & 8) ? 4 : 0) + ((lane & 4) ? 2 : 0) + ((lane & 2) ? 1 : 0);
                s_red[mwarp * 16 + v] = acc[0];
            }
            named_sync(2, 256);
            if (mtid < 16) {
                const int u = mtid >> 3;
                float y = 0.f;
#pragma unroll
                for (int w = 0; w < 8; w++) y += s_red[w * 16 + mtid];
                const float sig = rbf(1.f / (1.f + __expf(-(u ? rv[1] : rv[0]))));
                const float xn = rbf(rbf(hfin - (u ? mean[1] : mean[0])) * (u ? inv[1] : inv[0]));
                const float ov = hfin + rbf(xn + rbf(rbf(y) * sig));
                out[(size_t)(u ? idx[1] : idx[0]) * DM + c0 + (mtid & 7)] = __float2bfloat16_rn(ov);
            }
            if (blockIdx.x == gridDim.x - 1 && mtid == 0) g_epoch = g_epoch + 1u;
        }
    }
}

typedef CUresult (*PFN_encodeTiled)(CUtensorMap*, CUtensorMapDataType, cuuint32_t, void*, const cuuint64_t*, const cuuint64_t*,
                                    const cuuint32_t*, const cuuint32_t*, CUtensorMapInterleave, CUtensorMapSwizzle,
                                    CUtensorMapL2promotion, CUtensorMapFloatOOBfill);

void make_map(PFN_encodeTiled enc, CUtensorMap* m, const void* ptr, uint64_t cols, uint64_t rows, uint32_t bcols, uint32_t brows) {
    cuuint64_t dims[2] = {cols, rows};
    cuuint64_t strides[1] = {cols * 2};
    cuuint32_t box[2] = {bcols, brows};
    cuuint32_t es[2] = {1, 1};
    enc(m, CU_TENSOR_MAP_DATA_TYPE_BFLOAT16, 2, const_cast<void*>(ptr), dims, strides, box, es, CU_TENSOR_MAP_INTERLEAVE_NONE,
        CU_TENSOR_MAP_SWIZZLE_128B, CU_TENSOR_MAP_L2_PROMOTION_L2_256B, CU_TENSOR_MAP_FLOAT_OOB_FILL_NONE);
}

void make_map3(PFN_encodeTiled enc, CUtensorMap* m, const void* ptr, uint64_t d0, uint64_t rows, uint64_t d2, uint64_t row_stride_bytes,
               uint64_t d2_stride_bytes, uint32_t b0, uint32_t b1, uint32_t b2) {
    cuuint64_t dims[3] = {d0, rows, d2};
    cuuint64_t strides[2] = {row_stride_bytes, d2_stride_bytes};
    cuuint32_t box[3] = {b0, b1, b2};
    cuuint32_t es[3] = {1, 1, 1};
    enc(m, CU_TENSOR_MAP_DATA_TYPE_BFLOAT16, 3, const_cast<void*>(ptr), dims, strides, box, es, CU_TENSOR_MAP_INTERLEAVE_NONE,
        CU_TENSOR_MAP_SWIZZLE_128B, CU_TENSOR_MAP_L2_PROMOTION_L2_256B, CU_TENSOR_MAP_FLOAT_OOB_FILL_NONE);
}

void make_map_plain(PFN_encodeTiled enc, CUtensorMap* m, const void* ptr, uint64_t cols, uint64_t rows, uint32_t bcols, uint32_t brows) {
    cuuint64_t dims[2] = {cols, rows};
    cuuint64_t strides[1] = {cols * 2};
    cuuint32_t box[2] = {bcols, brows};
    cuuint32_t es[2] = {1, 1};
    enc(m, CU_TENSOR_MAP_DATA_TYPE_BFLOAT16, 2, const_cast<void*>(ptr), dims, strides, box, es, CU_TENSOR_MAP_INTERLEAVE_NONE,
        CU_TENSOR_MAP_SWIZZLE_NONE, CU_TENSOR_MAP_L2_PROMOTION_NONE, CU_TENSOR_MAP_FLOAT_OOB_FILL_NONE);
}

template <typename... KArgs, typename... Args>
void launch(void (*kern)(KArgs...), int grid, int block, int smem, bool pdl, Args... args) {
    cudaLaunchConfig_t cfg = {};
    cfg.gridDim = dim3(grid);
    cfg.blockDim = dim3(block);
    cfg.dynamicSmemBytes = smem;
    cfg.stream = cudaStreamPerThread;
    cudaLaunchAttribute at[1];
    at[0].id = cudaLaunchAttributeProgrammaticStreamSerialization;
    at[0].val.programmaticStreamSerializationAllowed = 1;
    cfg.attrs = at;
    cfg.numAttrs = pdl ? 1 : 0;
    cudaLaunchKernelEx(&cfg, kern, KArgs(args)...);
}

}

extern "C" void kernel_launch(void* const* d_in, const int* in_sizes, int n_in, void* d_out, int out_size) {
    const __nv_bfloat16* x = (const __nv_bfloat16*)d_in[0];
    const __nv_bfloat16* wqkv = (const __nv_bfloat16*)d_in[1];
    const __nv_bfloat16* wo = (const __nv_bfloat16*)d_in[2];
    const __nv_bfloat16* w_r = (const __nv_bfloat16*)d_in[4];
    const __nv_bfloat16* w_gate = (const __nv_bfloat16*)d_in[5];
    const __nv_bfloat16* w_up = (const __nv_bfloat16*)d_in[6];
    const __nv_bfloat16* w_down = (const __nv_bfloat16*)d_in[7];
    __nv_bfloat16* out = (__nv_bfloat16*)d_out;

    static PFN_encodeTiled enc = nullptr;
    static void* g_o_ptr = nullptr;
    if (!enc) {
        cudaDriverEntryPointQueryResult qres;
        void* fn = nullptr;
        cudaGetDriverEntryPoint("cuTensorMapEncodeTiled", &fn, cudaEnableDefault, &qres);
        enc = (PFN_encodeTiled)fn;
        cudaGetSymbolAddress(&g_o_ptr, g_o);
        cudaFuncSetAttribute(k1_qkv, cudaFuncAttributeMaxDynamicSharedMemorySize, K1_SMEM);
        cudaFuncSetAttribute(kf_main, cudaFuncAttributeMaxDynamicSharedMemorySize, KF_SMEM);
    }
    CUtensorMap tm_x, tm_w, tm_o, tm_wo, tm_g, tm_u, tm_d;
    make_map_plain(enc, &tm_d, w_down, DM, FF, 8, 256);
    make_map_plain(enc, &tm_g, w_gate, FF, DM, 16, 128);
    make_map_plain(enc, &tm_u, w_up, FF, DM, 16, 128);
    make_map(enc, &tm_x, x, DM, SEQ, 64, 128);
    make_map3(enc, &tm_w, wqkv, DM, DM, 3, 3 * DM * 2, DM * 2, 64, 64, 3);
    make_map3(enc, &tm_o, g_o_ptr, 64, SEQ, 8, DM * 2, 128, 64, 64, 1);
    make_map3(enc, &tm_wo, wo, 64, DM, 8, DM * 2, 128, 64, 64, 2);

    const bool pdl = true;
    launch(k1_qkv, 128, 544, K1_SMEM, false, tm_x, tm_w, x);
    launch(kf_main, 128, 512, KF_SMEM, pdl, tm_o, tm_wo, tm_g, tm_u, tm_d, x, wo, w_r, w_gate, w_up, w_down, out);
}
```

```cpp
#include <cuda_runtime.h>
#include <cuda_bf16.h>
#include <cuda.h>
#include <stdint.h>

namespace {

constexpr int SEQ = 2048, DM = 512, NH = 32, FF = 1792;

__device__ __align__(1024) uint8_t g_q[NH * 2 * SEQ * 16];
__device__ __align__(1024) uint8_t g_kv[NH * 8 * 16384];
__device__ float g_norm[16 * NH * 3];
__device__ __align__(1024) __nv_bfloat16 g_o[SEQ * DM];
__device__ __align__(1024) __nv_bfloat16 g_h[SEQ * DM];
__device__ __align__(16) uint4 g_cand[64];
__device__ unsigned int g_oflag[32 * 32];
__device__ unsigned int g_hflag[32];
__device__ unsigned int g_sflag[32];
__device__ unsigned int g_act[FF];
__device__ unsigned int g_epoch;
__device__ __align__(16) float4 g_ln1[SEQ];
__device__ __align__(16) float4 g_part[32 * 8 * 64];

__device__ __forceinline__ uint32_t smem_u32(const void* p) { return (uint32_t)__cvta_generic_to_shared(p); }
__device__ __forceinline__ void wg_fence() { asm volatile("wgmma.fence.sync.aligned;" ::: "memory"); }
__device__ __forceinline__ void wg_commit() { asm volatile("wgmma.commit_group.sync.aligned;" ::: "memory"); }
template <int N> __device__ __forceinline__ void wg_wait() { asm volatile("wgmma.wait_group.sync.aligned %0;" ::"n"(N) : "memory"); }
template <int N> __device__ __forceinline__ void fence_regs(float (&r)[N]) {
#pragma unroll
    for (int i = 0; i < N; i++) asm volatile("" : "+f"(r[i])::"memory");
}
__device__ __forceinline__ uint64_t make_desc(uint32_t addr, uint32_t lbo, uint32_t sbo, uint32_t swz) {
    uint64_t d = 0;
    d |= (uint64_t)((addr & 0x3FFFF) >> 4);
    d |= (uint64_t)((lbo & 0x3FFFF) >> 4) << 16;
    d |= (uint64_t)((sbo & 0x3FFFF) >> 4) << 32;
    d |= (uint64_t)swz << 62;
    return d;
}
__device__ __forceinline__ void mbar_init(uint32_t bar, uint32_t cnt) {
    asm volatile("mbarrier.init.shared::cta.b64 [%0], %1;" ::"r"(bar), "r"(cnt) : "memory");
}
__device__ __forceinline__ void mbar_expect_tx(uint32_t bar, uint32_t bytes) {
    asm volatile("mbarrier.arrive.expect_tx.shared::cta.b64 _, [%0], %1;" ::"r"(bar), "r"(bytes) : "memory");
}
__device__ __forceinline__ void mbar_arrive(uint32_t bar) {
    asm volatile("mbarrier.arrive.shared::cta.b64 _, [%0];" ::"r"(bar) : "memory");
}
__device__ __forceinline__ void mbar_wait(uint32_t bar, uint32_t parity) {
    asm volatile(
        "{\n.reg .pred p;\nWAIT_%=:\n"
        "mbarrier.try_wait.parity.shared::cta.b64 p, [%0], %1;\n"
        "@p bra DONE_%=;\nbra WAIT_%=;\nDONE_%=:\n}\n" ::"r"(bar), "r"(parity) : "memory");
}
__device__ __forceinline__ void bulk_g2s(uint32_t dst, const void* src, uint32_t bytes, uint32_t bar) {
    asm volatile("cp.async.bulk.shared::cluster.global.mbarrier::complete_tx::bytes [%0], [%1], %2, [%3];" ::"r"(dst),
                 "l"(src), "r"(bytes), "r"(bar) : "memory");
}
__device__ __forceinline__ void bulk_s2g(void* dst, uint32_t src, uint32_t bytes) {
    asm volatile("cp.async.bulk.global.shared::cta.bulk_group [%0], [%1], %2;" ::"l"(dst), "r"(src), "r"(bytes) : "memory");
}
__device__ __forceinline__ void tma_load_2d(uint32_t dst, const CUtensorMap* tm, int c0, int c1, uint32_t bar) {
    asm volatile("cp.async.bulk.tensor.2d.shared::cluster.global.mbarrier::complete_tx::bytes [%0], [%1, {%3, %4}], [%2];" ::"r"(dst),
                 "l"(tm), "r"(bar), "r"(c0), "r"(c1) : "memory");
}
__device__ __forceinline__ void tma_load_3d(uint32_t dst, const CUtensorMap* tm, int c0, int c1, int c2, uint32_t bar) {
    asm volatile("cp.async.bulk.tensor.3d.shared::cluster.global.mbarrier::complete_tx::bytes [%0], [%1, {%3, %4, %5}], [%2];" ::"r"(dst),
                 "l"(tm), "r"(bar), "r"(c0), "r"(c1), "r"(c2) : "memory");
}
__device__ __forceinline__ void prefetch_l2(const void* p, uint32_t bytes) {
    asm volatile("cp.async.bulk.prefetch.L2.global [%0], %1;" ::"l"(p), "r"(bytes) : "memory");
}
__device__ __forceinline__ void fence_proxy_async() { asm volatile("fence.proxy.async.shared::cta;" ::: "memory"); }
__device__ __forceinline__ void fence_barrier_init() { asm volatile("fence.mbarrier_init.release.cluster;" ::: "memory"); }
__device__ __forceinline__ void pdl_launch() { asm volatile("griddepcontrol.launch_dependents;" ::: "memory"); }
__device__ __forceinline__ void pdl_wait() { asm volatile("griddepcontrol.wait;" ::: "memory"); }
__device__ __forceinline__ void named_sync(int id, int n) { asm volatile("bar.sync %0, %1;" ::"r"(id), "r"(n) : "memory"); }
__device__ __forceinline__ void named_arrive(int id, int n) { asm volatile("bar.arrive %0, %1;" ::"r"(id), "r"(n) : "memory"); }

__device__ __forceinline__ float ex2f(float x) { float y; asm("ex2.approx.ftz.f32 %0, %1;" : "=f"(y) : "f"(x)); return y; }
__device__ __forceinline__ uint32_t pack_bf16(float lo, float hi) {
    uint32_t r; asm("cvt.rn.bf16x2.f32 %0, %1, %2;" : "=r"(r) : "f"(hi), "f"(lo)); return r;
}
__device__ __forceinline__ float bf_lo(uint32_t v) { return __uint_as_float(v << 16); }
__device__ __forceinline__ float bf_hi(uint32_t v) { return __uint_as_float(v & 0xFFFF0000u); }
__device__ __forceinline__ float rbf(float x) { return __bfloat162float(__float2bfloat16_rn(x)); }
__device__ __forceinline__ uint32_t fma_bf16x2(uint32_t a, uint32_t b, uint32_t c) {
    uint32_t r; asm("fma.rn.bf16x2 %0, %1, %2, %3;" : "=r"(r) : "r"(a), "r"(b), "r"(c)); return r;
}
__device__ __forceinline__ void stmatrix_x4(uint32_t addr, uint32_t r0, uint32_t r1, uint32_t r2, uint32_t r3) {
    asm volatile("stmatrix.sync.aligned.m8n8.x4.shared.b16 [%0], {%1, %2, %3, %4};" ::"r"(addr), "r"(r0), "r"(r1), "r"(r2), "r"(r3) : "memory");
}
__device__ __forceinline__ void stmatrix_x4_trans(uint32_t addr, uint32_t r0, uint32_t r1, uint32_t r2, uint32_t r3) {
    asm volatile("stmatrix.sync.aligned.m8n8.x4.trans.shared.b16 [%0], {%1, %2, %3, %4};" ::"r"(addr), "r"(r0), "r"(r1), "r"(r2), "r"(r3) : "memory");
}

__device__ __forceinline__ void wgmma_k1_n136(float (&d)[68], uint64_t desca, uint64_t descb, int scale_d) {
  asm volatile("{\n.reg .pred p;\nsetp.ne.b32 p, %70, 0;\n"
    "wgmma.mma_async.sync.aligned.m64n136k16.f32.bf16.bf16 "
    "{%0, %1, %2, %3, %4, %5, %6, %7, %8, %9, %10, %11, %12, %13, %14, %15, %16, %17, %18, %19, %20, %21, %22, %23, %24, %25, %26, %27, %28, %29, %30, %31, %32, %33, %34, %35, %36, %37, %38, %39, %40, %41, %42, %43, %44, %45, %46, %47, %48, %49, %50, %51, %52, %53, %54, %55, %56, %57, %58, %59, %60, %61, %62, %63, %64, %65, %66, %67}, "
    "%68, %69, p, 1, 1, 1, 0;\n}\n"
    : "+f"(d[0]), "+f"(d[1]), "+f"(d[2]), "+f"(d[3]), "+f"(d[4]), "+f"(d[5]), "+f"(d[6]), "+f"(d[7]), "+f"(d[8]), "+f"(d[9]), "+f"(d[10]), "+f"(d[11]), "+f"(d[12]), "+f"(d[13]), "+f"(d[14]), "+f"(d[15]), "+f"(d[16]), "+f"(d[17]), "+f"(d[18]), "+f"(d[19]), "+f"(d[20]), "+f"(d[21]), "+f"(d[22]), "+f"(d[23]), "+f"(d[24]), "+f"(d[25]), "+f"(d[26]), "+f"(d[27]), "+f"(d[28]), "+f"(d[29]), "+f"(d[30]), "+f"(d[31]), "+f"(d[32]), "+f"(d[33]), "+f"(d[34]), "+f"(d[35]), "+f"(d[36]), "+f"(d[37]), "+f"(d[38]), "+f"(d[39]), "+f"(d[40]), "+f"(d[41]), "+f"(d[42]), "+f"(d[43]), "+f"(d[44]), "+f"(d[45]), "+f"(d[46]), "+f"(d[47]), "+f"(d[48]), "+f"(d[49]), "+f"(d[50]), "+f"(d[51]), "+f"(d[52]), "+f"(d[53]), "+f"(d[54]), "+f"(d[55]), "+f"(d[56]), "+f"(d[57]), "+f"(d[58]), "+f"(d[59]), "+f"(d[60]), "+f"(d[61]), "+f"(d[62]), "+f"(d[63]), "+f"(d[64]), "+f"(d[65]), "+f"(d[66]), "+f"(d[67])
    : "l"(desca), "l"(descb), "r"(scale_d));
}
__device__ __forceinline__ void wgmma_qk_n64(float (&d)[32], uint32_t a0, uint32_t a1, uint32_t a2, uint32_t a3, uint64_t descb) {
  asm volatile("{\n.reg .pred p;\nsetp.ne.b32 p, 0, 0;\n"
    "wgmma.mma_async.sync.aligned.m64n64k16.f32.bf16.bf16 "
    "{%0, %1, %2, %3, %4, %5, %6, %7, %8, %9, %10, %11, %12, %13, %14, %15, %16, %17, %18, %19, %20, %21, %22, %23, %24, %25, %26, %27, %28, %29, %30, %31}, "
    "{%32, %33, %34, %35}, %36, p, 1, 1, 0;\n}\n"
    : "=f"(d[0]), "=f"(d[1]), "=f"(d[2]), "=f"(d[3]), "=f"(d[4]), "=f"(d[5]), "=f"(d[6]), "=f"(d[7]), "=f"(d[8]), "=f"(d[9]), "=f"(d[10]), "=f"(d[11]), "=f"(d[12]), "=f"(d[13]), "=f"(d[14]), "=f"(d[15]), "=f"(d[16]), "=f"(d[17]), "=f"(d[18]), "=f"(d[19]), "=f"(d[20]), "=f"(d[21]), "=f"(d[22]), "=f"(d[23]), "=f"(d[24]), "=f"(d[25]), "=f"(d[26]), "=f"(d[27]), "=f"(d[28]), "=f"(d[29]), "=f"(d[30]), "=f"(d[31])
    : "r"(a0), "r"(a1), "r"(a2), "r"(a3), "l"(descb));
}
__device__ __forceinline__ void wgmma_pv_n24(float (&d)[12], uint32_t a0, uint32_t a1, uint32_t a2, uint32_t a3, uint64_t descb) {
  asm volatile("{\n.reg .pred p;\nsetp.eq.b32 p, 0, 0;\n"
    "wgmma.mma_async.sync.aligned.m64n24k16.f32.bf16.bf16 "
    "{%0, %1, %2, %3, %4, %5, %6, %7, %8, %9, %10, %11}, "
    "{%12, %13, %14, %15}, %16, p, 1, 1, 1;\n}\n"
    : "+f"(d[0]), "+f"(d[1]), "+f"(d[2]), "+f"(d[3]), "+f"(d[4]), "+f"(d[5]), "+f"(d[6]), "+f"(d[7]), "+f"(d[8]), "+f"(d[9]), "+f"(d[10]), "+f"(d[11])
    : "r"(a0), "r"(a1), "r"(a2), "r"(a3), "l"(descb));
}
__device__ __forceinline__ void wgmma_k3_n64(float (&d)[32], uint64_t desca, uint64_t descb, int scale_d) {
  asm volatile("{\n.reg .pred p;\nsetp.ne.b32 p, %34, 0;\n"
    "wgmma.mma_async.sync.aligned.m64n64k16.f32.bf16.bf16 "
    "{%0, %1, %2, %3, %4, %5, %6, %7, %8, %9, %10, %11, %12, %13, %14, %15, %16, %17, %18, %19, %20, %21, %22, %23, %24, %25, %26, %27, %28, %29, %30, %31}, "
    "%32, %33, p, 1, 1, 0, 1;\n}\n"
    : "+f"(d[0]), "+f"(d[1]), "+f"(d[2]), "+f"(d[3]), "+f"(d[4]), "+f"(d[5]), "+f"(d[6]), "+f"(d[7]), "+f"(d[8]), "+f"(d[9]), "+f"(d[10]), "+f"(d[11]), "+f"(d[12]), "+f"(d[13]), "+f"(d[14]), "+f"(d[15]), "+f"(d[16]), "+f"(d[17]), "+f"(d[18]), "+f"(d[19]), "+f"(d[20]), "+f"(d[21]), "+f"(d[22]), "+f"(d[23]), "+f"(d[24]), "+f"(d[25]), "+f"(d[26]), "+f"(d[27]), "+f"(d[28]), "+f"(d[29]), "+f"(d[30]), "+f"(d[31])
    : "l"(desca), "l"(descb), "r"(scale_d));
}
__device__ __forceinline__ void wgmma_bias_n40(float (&d)[32], uint64_t desca, uint64_t descb) {
  asm volatile("{\n.reg .pred p;\nsetp.eq.b32 p, 0, 0;\n"
    "wgmma.mma_async.sync.aligned.m64n40k16.f32.bf16.bf16 "
    "{%0, %1, %2, %3, %4, %5, %6, %7, %8, %9, %10, %11, %12, %13, %14, %15, %16, %17, %18, %19}, "
    "%20, %21, p, 1, 1, 0, 0;\n}\n"
    : "+f"(d[0]), "+f"(d[1]), "+f"(d[2]), "+f"(d[3]), "+f"(d[4]), "+f"(d[5]), "+f"(d[6]), "+f"(d[7]), "+f"(d[8]), "+f"(d[9]), "+f"(d[10]), "+f"(d[11]), "+f"(d[12]), "+f"(d[13]), "+f"(d[14]), "+f"(d[15]), "+f"(d[16]), "+f"(d[17]), "+f"(d[18]), "+f"(d[19])
    : "l"(desca), "l"(descb));
}

constexpr int K1_XS = 17408;
constexpr int K1_WS = 24576;
constexpr int K1_ST = K1_XS + K1_WS;
constexpr int K1_NST = 5;
constexpr int K1_OFF_MISC = K1_NST * K1_ST;
constexpr int K1_SMEM = K1_OFF_MISC + 2048 + 1024;
constexpr float QSCALE = 0.25f * 1.4426950408889634f;

__global__ void __launch_bounds__(544, 1)
k1_qkv(const __grid_constant__ CUtensorMap tm_x, const __grid_constant__ CUtensorMap tm_w, const __nv_bfloat16* __restrict__ x) {
    extern __shared__ uint8_t smem_raw[];
    const uint32_t sraw = smem_u32(smem_raw);
    const uint32_t sb = (sraw + 1023) & ~1023u;
    uint8_t* sp = smem_raw + (sb - sraw);
    const uint32_t full = sb + K1_OFF_MISC;
    const uint32_t empty = full + 64;
    float* s_mr = (float*)(sp + K1_OFF_MISC + 256);

    const int tid = threadIdx.x, warp = tid >> 5, lane = tid & 31;
    const int mt = blockIdx.x >> 3, nt = blockIdx.x & 7;
    pdl_launch();
    if (tid == 512) {
        for (int i = 0; i < K1_NST; i++) { mbar_init(full + 8 * i, 1); mbar_init(empty + 8 * i, 3); }
        fence_barrier_init();
        for (int kb = 0; kb < K1_NST; kb++) {
            mbar_expect_tx(full + 8 * kb, 16384 + K1_WS);
            tma_load_2d(sb + kb * K1_ST, &tm_x, kb * 64, mt * 128, full + 8 * kb);
            tma_load_3d(sb + kb * K1_ST + K1_XS, &tm_w, nt * 64, kb * 64, 0, full + 8 * kb);
        }
    }
    if (tid < K1_NST * 64) {
        *(uint4*)(sp + (tid >> 6) * K1_ST + 16384 + (tid & 63) * 16) =
            make_uint4(0x3F803F80u, 0x3F803F80u, 0x3F803F80u, 0x3F803F80u);
    }
    fence_proxy_async();
    __syncthreads();

    if (warp == 16) {
        if (lane == 0) {
            for (int kb = K1_NST; kb < 8; kb++) {
                const int s = kb % K1_NST;
                mbar_wait(empty + 8 * s, 0);
                mbar_expect_tx(full + 8 * s, 16384 + K1_WS);
                tma_load_2d(sb + s * K1_ST, &tm_x, kb * 64, mt * 128, full + 8 * s);
                tma_load_3d(sb + s * K1_ST + K1_XS, &tm_w, nt * 64, kb * 64, 0, full + 8 * s);
            }
        }
        __syncwarp();
        if (lane < FF / 128) g_act[blockIdx.x * (FF / 128) + lane] = 0xFFFFFFFFu;
        for (int i = lane; i < 128; i += 32) g_part[blockIdx.x * 128 + i] = make_float4(0.f, 0.f, 0.f, 0.f);
        if (blockIdx.x == 1) { g_cand[lane] = make_uint4(0, 0, 0, 0); g_cand[lane + 32] = make_uint4(0, 0, 0, 0); g_hflag[lane] = 0; g_sflag[lane] = 0; }
        if (blockIdx.x == 2) for (int i = lane; i < 1024; i += 32) g_oflag[i] = 0;
    } else if (warp >= 12) {
        const int r = tid - 384;
        const unsigned int tag = *(volatile unsigned int*)&g_epoch + 1u;
        {
            const int row = mt * 128 + nt * 16 + (r >> 3);
            const uint4* xp = (const uint4*)(x + (size_t)row * DM) + (r & 7);
            uint4 v[8];
#pragma unroll
            for (int i = 0; i < 8; i++) v[i] = __ldg(xp + i * 8);
            float s1 = 0.f;
#pragma unroll
            for (int i = 0; i < 8; i++)
                s1 += ((bf_lo(v[i].x) + bf_hi(v[i].x)) + (bf_lo(v[i].y) + bf_hi(v[i].y))) + ((bf_lo(v[i].z) + bf_hi(v[i].z)) + (bf_lo(v[i].w) + bf_hi(v[i].w)));
#pragma unroll
            for (int o = 1; o < 8; o <<= 1) s1 += __shfl_xor_sync(0xffffffffu, s1, o);
            const float mean = s1 * (1.f / DM);
            float q0 = 0.f, q1 = 0.f;
#pragma unroll
            for (int i = 0; i < 8; i++) {
                const uint32_t w[4] = {v[i].x, v[i].y, v[i].z, v[i].w};
#pragma unroll
                for (int j = 0; j < 4; j++) {
                    const float a = bf_lo(w[j]) - mean, b = bf_hi(w[j]) - mean;
                    q0 = fmaf(a, a, q0); q1 = fmaf(b, b, q1);
                }
            }
            float q = q0 + q1;
#pragma unroll
            for (int o = 1; o < 8; o <<= 1) q += __shfl_xor_sync(0xffffffffu, q, o);
            const float den = rbf(sqrtf(rbf(rbf(q * (1.f / DM)) + 1e-5f)));
            if ((r & 7) == 0)
                asm volatile("st.relaxed.gpu.global.v4.f32 [%0], {%1, %2, %3, %4};" ::"l"(g_ln1 + row), "f"(rbf(mean)), "f"(1.f / den),
                             "f"(__uint_as_float(tag)), "f"(0.f) : "memory");
        }
        {
            float4 v;
            int spins = 0;
            do {
                asm volatile("ld.relaxed.gpu.global.v4.f32 {%0, %1, %2, %3}, [%4];" : "=f"(v.x), "=f"(v.y), "=f"(v.z), "=f"(v.w) : "l"(g_ln1 + mt * 128 + r) : "memory");
            } while (__float_as_uint(v.z) != tag && ++spins < (1 << 22));
            s_mr[(r >> 1) * 4 + (r & 1)] = v.x;
            s_mr[(r >> 1) * 4 + 2 + (r & 1)] = v.y;
        }
        named_arrive(1, 512);
    } else {
        const int part = warp >> 2, hw = warp & 3;
        float acc[68];
#pragma unroll
        for (int i = 0; i < 68; i++) acc[i] = 0.f;
        fence_regs(acc);
#pragma unroll 1
        for (int kb = 0; kb < 8; kb++) {
            const int s = kb % K1_NST;
            mbar_wait(full + 8 * s, (kb / K1_NST) & 1);
            const uint64_t da = make_desc(sb + s * K1_ST + K1_XS + part * 8192, 1024, 1024, 1);
            const uint64_t db = make_desc(sb + s * K1_ST, 16, 1024, 1);
            wg_fence();
#pragma unroll
            for (int k = 0; k < 4; k++) wgmma_k1_n136(acc, da + k * 128, db + k * 2, (kb | k) != 0);
            wg_commit();
            if (kb > 0 && kb <= 8 - K1_NST) {
                wg_wait<1>();
                if ((tid & 127) == 0) mbar_arrive(empty + 8 * (kb - 1));
            }
        }
        wg_wait<0>();
        fence_regs(acc);
        named_sync(1, 512);

        const int t = lane & 3;
        const float cs0 = acc[64], cs1 = acc[66];
        const float sc = (part == 0) ? QSCALE : 1.f;
        const uint32_t stg = sb + (hw >> 1) * K1_ST + K1_XS + part * 8192 + (hw & 1) * 4096;
        const uint32_t st_addr = stg + ((lane >> 3) & 1) * 2048 + ((lane >> 4) * 8 + (lane & 7)) * 16;
#pragma unroll
        for (int j = 0; j < 16; j += 2) {
            uint32_t rr[4];
#pragma unroll
            for (int u = 0; u < 2; u++) {
                const int jj = j + u;
                const float4 mr = *(const float4*)(s_mr + (4 * jj + t) * 4);
                const float2 m2 = make_float2(mr.x, mr.y);
                const float ra = mr.z * sc, rb = mr.w * sc;
                rr[2 * u] = pack_bf16((acc[4 * jj] - m2.x * cs0) * ra, (acc[4 * jj + 1] - m2.y * cs0) * rb);
                rr[2 * u + 1] = pack_bf16((acc[4 * jj + 2] - m2.x * cs1) * ra, (acc[4 * jj + 3] - m2.y * cs1) * rb);
            }
            stmatrix_x4_trans(st_addr + j * 128, rr[0], rr[1], rr[2], rr[3]);
        }
        fence_proxy_async();
        __syncwarp();
        const int head = nt * 4 + hw;
        if (lane == 0) {
            uint8_t* dst;
            uint32_t hstride;
            if (part == 0) { dst = g_q + (size_t)head * 65536 + mt * 2048; hstride = 32768; }
            else { dst = g_kv + (size_t)head * 131072 + (mt >> 1) * 16384 + (part - 1) * 8192 + (mt & 1) * 2048; hstride = 4096; }
            bulk_s2g(dst, stg, 2048);
            bulk_s2g(dst + hstride, stg + 2048, 2048);
            asm volatile("cp.async.bulk.commit_group;" ::: "memory");
        }
        float nmax = 0.f;
#pragma unroll
        for (int i = 0; i < 4; i++) {
            const int tok = lane + 32 * i;
            const uint4 a = *(const uint4*)(sp + (stg - sb) + tok * 16);
            const uint4 b = *(const uint4*)(sp + (stg - sb) + 2048 + tok * 16);
            uint32_t n0 = fma_bf16x2(a.x, a.x, 0u), n1 = fma_bf16x2(b.x, b.x, 0u);
            n0 = fma_bf16x2(a.y, a.y, n0); n1 = fma_bf16x2(b.y, b.y, n1);
            n0 = fma_bf16x2(a.z, a.z, n0); n1 = fma_bf16x2(b.z, b.z, n1);
            n0 = fma_bf16x2(a.w, a.w, n0); n1 = fma_bf16x2(b.w, b.w, n1);
            const float n2 = ((bf_lo(n0) + bf_hi(n0)) + (bf_lo(n1) + bf_hi(n1))) * 1.125f;
            nmax = (n2 > nmax || n2 != n2) ? n2 : nmax;
        }
#pragma unroll
        for (int o = 16; o > 0; o >>= 1) {
            const float v = __shfl_xor_sync(0xffffffffu, nmax, o);
            nmax = (v > nmax || v != v) ? v : nmax;
        }
        if (lane == 0) {
            g_norm[(head * 16 + mt) * 3 + part] = nmax;
            asm volatile("cp.async.bulk.wait_group.read 0;" ::: "memory");
        }
    }
}

#define POLL_NS 50
constexpr int KF_CH_G = 16384, KF_CH_S = 20480, KF_NCH = 8;
constexpr int KF_OFF_WO = KF_NCH * KF_CH_S;
constexpr int KF_OFF_MISC = -2048;
constexpr int KF_SMEM = 2048 + KF_OFF_WO + 65536 + 1024;

__device__ __forceinline__ uint32_t exp2_pair_poly(float t0, float t1, uint32_t c2) {
    const uint32_t w = __byte_perm(__float_as_uint(t0), __float_as_uint(t1), 0x5410);
    uint32_t z;
    asm("lop3.b32 %0, %1, %2, %3, 0xEA;" : "=r"(z) : "r"(w), "r"(0x007F007Fu), "r"(0x3F803F80u));
    uint32_t p = fma_bf16x2(c2, z, 0xbc73bc73u);
    p = fma_bf16x2(p, z, 0x3f2f3f2fu);
    return p + w - z;
}
#define NEA 40
#define NEB 40
#define BIAS_(n) wgmma_bias_n##n
#define BIAS(n) BIAS_(n)
template <int LO, int HI, int NE>
__device__ __forceinline__ void softmax_part(const float (&s)[32], uint32_t (&p)[16], uint32_t c2) {
#pragma unroll
    for (int i = LO; i < HI; i++) {
        if (i < NE / 4) p[i] = exp2_pair_poly(s[2 * i], s[2 * i + 1], c2);
        else p[i] = pack_bf16(ex2f(s[2 * i]), ex2f(s[2 * i + 1]));
    }
}
#define KF_PV(P, OFF)                                                                              \
    _Pragma("unroll") for (int kk = 0; kk < 4; kk++)                                               \
        wgmma_pv_n24(o, P[4 * kk], P[4 * kk + 1], P[4 * kk + 2], P[4 * kk + 3], dv + ((OFF) + kk * 16));

__device__ __forceinline__ uint32_t make_key(float r_bf16, int token) {
    const uint32_t u = __float_as_uint(r_bf16) >> 16;
    const uint32_t o = (u & 0x8000u) ? (~u & 0xFFFFu) : (u | 0x8000u);
    return (o << 16) | (uint32_t)(0xFFFF - token);
}
__device__ __forceinline__ float key_value(uint32_t k) {
    const uint32_t o = k >> 16;
    const uint32_t u = (o & 0x8000u) ? (o & 0x7FFFu) : (~o & 0xFFFFu);
    return __uint_as_float(u << 16);
}
__device__ __forceinline__ int key_token(uint32_t k) { return 0xFFFF - (int)(k & 0xFFFFu); }
__device__ __forceinline__ void warp_top2(uint32_t a, uint32_t b, uint32_t& k1, uint32_t& k2) {
    k1 = __reduce_max_sync(0xffffffffu, a > b ? a : b);
    const uint32_t a2 = (a == k1) ? 0u : a, b2 = (b == k1) ? 0u : b;
    k2 = __reduce_max_sync(0xffffffffu, a2 > b2 ? a2 : b2);
}
__device__ __forceinline__ unsigned int ld_acquire(const unsigned int* p) {
    unsigned int v; asm volatile("ld.acquire.gpu.global.u32 %0, [%1];" : "=r"(v) : "l"(p) : "memory"); return v;
}
__device__ __forceinline__ void red_release_add(unsigned int* p) {
    asm volatile("red.release.gpu.global.add.u32 [%0], 1;" ::"l"(p) : "memory");
}

__global__ void __launch_bounds__(512, 1)
kf_main(const __grid_constant__ CUtensorMap tm_o, const __grid_constant__ CUtensorMap tm_wo,
        const __grid_constant__ CUtensorMap tm_g, const __grid_constant__ CUtensorMap tm_u, const __grid_constant__ CUtensorMap tm_d,
        const __nv_bfloat16* __restrict__ x, const __nv_bfloat16* __restrict__ wo, const __nv_bfloat16* __restrict__ w_r,
        const __nv_bfloat16* __restrict__ w_gate, const __nv_bfloat16* __restrict__ w_up, const __nv_bfloat16* __restrict__ w_down,
        __nv_bfloat16* __restrict__ out) {
    extern __shared__ uint8_t smem_raw[];
    const uint32_t sraw = smem_u32(smem_raw);
    const uint32_t sb = ((sraw + 1023) & ~1023u) + 2048;
    uint8_t* sp = smem_raw + (sb - sraw);
    const uint32_t smisc = sb - 2048u;
    const uint32_t kvbar = smisc;
    const uint32_t wbar = kvbar + 64;
    const uint32_t obar = wbar + 64;
    const uint32_t gbar = obar + 64;
    const uint32_t dbar = gbar + 8;
    unsigned int* s_cnt = (unsigned int*)(sp + KF_OFF_MISC + 208);
    volatile unsigned int* s_order = (volatile unsigned int*)(sp + KF_OFF_MISC + 1056);
    uint32_t* s_key = (uint32_t*)(sp + KF_OFF_MISC + 256);
    float* s_gu = (float*)(sp + KF_OFF_WO + 49152 + 8192 + 4608);
    uint4* s_sel = (uint4*)(sp + KF_OFF_MISC + 1024);
    const int tid = threadIdx.x;
    const int head = blockIdx.x >> 2, quarter = blockIdx.x & 3;
    const int mt = blockIdx.x >> 2, nt = blockIdx.x & 3;
    if (tid == 0) {
        for (int c = 0; c < 26; c++) mbar_init(kvbar + 8 * c, 1);
        for (int c = 0; c < 6; c++) s_cnt[c] = 0;
        fence_barrier_init();
        for (int kb = 0; kb < 4; kb++) {
            mbar_expect_tx(wbar + 8 * kb, 16384);
            tma_load_3d(sb + KF_OFF_WO + kb * 16384, &tm_wo, 0, kb * 64, nt * 2, wbar + 8 * kb);
        }
    }
    if (tid == 32) {
        prefetch_l2((const uint8_t*)wo + blockIdx.x * 4096, 4096);
        prefetch_l2((const uint8_t*)w_gate + blockIdx.x * 14336, 14336);
        prefetch_l2((const uint8_t*)w_up + blockIdx.x * 14336, 14336);
        prefetch_l2((const uint8_t*)w_down + blockIdx.x * 14336, 14336);
    }
    if (tid < 24) *(uint4*)(sp + KF_OFF_MISC + 1152 + tid * 16) =
        tid < 8 ? make_uint4(0x42FE4380u, 0x00003D80u, 0u, 0u) : (tid < 16 ? make_uint4(0x3F804380u, 0x00003E00u, 0u, 0u) : make_uint4(0u, 0u, 0u, 0u));
    for (int i = tid; i < KF_NCH * 256; i += 512)
        *(uint4*)(sp + (i >> 8) * KF_CH_S + 16384 + (i & 255) * 16) =
            make_uint4(0x3F803F80u, 0x3F803F80u, 0x3F803F80u, 0x3F803F80u);
    fence_proxy_async();
    __syncthreads();
    pdl_wait();
    const uint8_t* kvsrc = g_kv + (size_t)head * (KF_NCH * KF_CH_G);
    if (tid == 32) {
        mbar_expect_tx(kvbar, KF_CH_G);
        bulk_g2s(sb, kvsrc, KF_CH_G, kvbar);
    }
    const int wg = tid >> 7, warp = (tid >> 5) & 3, lane = tid & 31, g = lane >> 2, t = lane & 3;
    if (tid < 32) {
        const int m16 = lane & 15;
        float kn = g_norm[(head * 16 + m16) * 3 + 1];
        float vn = g_norm[(head * 16 + m16) * 3 + 2];
        float qn = g_norm[(head * 16 + quarter * 4 + (lane & 3)) * 3 + 0];
        const bool bad = !(kn < 1e30f) || !(vn < 1e9f) || !(qn < 1e30f);
#pragma unroll
        for (int o = 8; o > 0; o >>= 1) {
            kn = fmaxf(kn, __shfl_xor_sync(0xffffffffu, kn, o));
            qn = fmaxf(qn, __shfl_xor_sync(0xffffffffu, qn, o));
        }
        const bool ok = __all_sync(0xffffffffu, !bad && (qn * kn <= 9000.f));
        if (lane == 0) s_cnt[4] = ok ? 1u : 0u;
    }
    uint32_t qn2[2][4];
#pragma unroll
    for (int ps = 0; ps < 2; ps++) {
        const uint8_t* qb = g_q + (size_t)head * 65536 + (quarter * 512 + ps * 256 + wg * 64 + warp * 16 + g) * 16 + t * 4;
        qn2[ps][0] = *(const uint32_t*)(qb);
        qn2[ps][1] = *(const uint32_t*)(qb + 128);
        qn2[ps][2] = *(const uint32_t*)(qb + 32768);
        qn2[ps][3] = *(const uint32_t*)(qb + 32768 + 128);
    }

    __syncthreads();
    const bool fast = __all_sync(0xffffffffu, s_cnt[4] != 0u);
    if (tid == 32) {
        for (int c = 1; c < KF_NCH; c++) {
            mbar_expect_tx(kvbar + 8 * c, KF_CH_G);
            bulk_g2s(sb + c * KF_CH_S, kvsrc + c * KF_CH_G, KF_CH_G, kvbar + 8 * c);
        }
    }
    const uint64_t dbias_a = make_desc(smisc + 1152, 0, 0, 0);
    const uint64_t dbias_b = make_desc(smisc + 1280, 128, 0, 0);
    const uint32_t c2reg = 0x3eab3eabu;
    const uint64_t dk0 = make_desc(sb, 4096, 128, 0);
    const uint64_t dv0 = make_desc(sb + 8192, 128, 4096, 0);

#pragma unroll 1
    for (int pass = 0; pass < 2; pass++) {
        const int row0 = quarter * 512 + pass * 256 + wg * 64 + warp * 16 + g;
        uint32_t qa[4];
#pragma unroll
        for (int i = 0; i < 4; i++) qa[i] = pass ? qn2[1][i] : qn2[0][i];
        float o[12];
#pragma unroll
        for (int i = 0; i < 12; i++) o[i] = 0.f;
        fence_regs(o);
#define KF_RELEASE_CHUNK(c)                                                                          \
        if (pass == 1 && (c) >= 1 && (c) <= 4) {                                                     \
            named_sync(4 + wg, 128);            \
            if ((tid & 127) == 0 && atomicAdd(&s_cnt[(c) - 1], 1u) == 3u) {                          \
                mbar_expect_tx(wbar + 8 * (3 + (c)), 16384);                                         \
                tma_load_3d(sb + ((c) - 1) * KF_CH_S, &tm_wo, 0, (3 + (c)) * 64, nt * 2, wbar + 8 * (3 + (c))); \
            }                                                                                        \
        }
        if (fast) {
#pragma unroll 1
            for (int c = 0; c < KF_NCH; c++) {
                const uint64_t dk = dk0 + (uint64_t)(c * (KF_CH_S >> 4));
                const uint64_t dv = dv0 + (uint64_t)(c * (KF_CH_S >> 4));
                float s0[32], s1[32], s2[32], s3[32];
                uint32_t p0[16], p1[16], p2[16], p3[16];
                mbar_wait(kvbar + 8 * c, 0);
                wg_wait<1>();
                wg_fence();
                wgmma_qk_n64(s0, qa[0], qa[1], qa[2], qa[3], dk);
                BIAS(NEA)(s0, dbias_a, dbias_b);
                wg_commit();
                wg_wait<1>();
                KF_RELEASE_CHUNK(c);
                wg_fence();
                wgmma_qk_n64(s1, qa[0], qa[1], qa[2], qa[3], dk + 64);
                BIAS(NEB)(s1, dbias_a, dbias_b);
                wg_commit();
                wg_wait<1>();
                fence_regs(s0);
                softmax_part<0, 16, NEA>(s0, p0, c2reg);
                wg_fence();
                KF_PV(p0, 0);
                wg_commit();
                wg_wait<1>();
                fence_regs(s1);
                softmax_part<0, 8, NEB>(s1, p1, c2reg);
                wg_wait<0>();
                wg_fence();
                wgmma_qk_n64(s2, qa[0], qa[1], qa[2], qa[3], dk + 128);
                BIAS(NEA)(s2, dbias_a, dbias_b);
                wg_commit();
                softmax_part<8, 16, NEB>(s1, p1, c2reg);
                wg_fence();
                KF_PV(p1, 64);
                wg_commit();
                wg_wait<1>();
                fence_regs(s2);
                softmax_part<0, 8, NEA>(s2, p2, c2reg);
                wg_wait<0>();
                wg_fence();
                wgmma_qk_n64(s3, qa[0], qa[1], qa[2], qa[3], dk + 192);
                BIAS(NEB)(s3, dbias_a, dbias_b);
                wg_commit();
                softmax_part<8, 16, NEA>(s2, p2, c2reg);
                wg_fence();
                KF_PV(p2, 128);
                wg_commit();
                wg_wait<1>();
                fence_regs(s3);
                softmax_part<0, 16, NEB>(s3, p3, c2reg);
                wg_fence();
                KF_PV(p3, 192);
                wg_commit();
            }
            wg_wait<0>();
            fence_regs(o);
        } else {
            float m0 = -INFINITY, m1 = -INFINITY;
#pragma unroll 1
            for (int b = 0; b < 32; b++) {
                const int c = b >> 2;
                const uint64_t dk = dk0 + (uint64_t)(c * (KF_CH_S >> 4) + (b & 3) * 64);
                const uint64_t dv = dv0 + (uint64_t)(c * (KF_CH_S >> 4) + (b & 3) * 64);
                float s[32];
                uint32_t p[16];
                mbar_wait(kvbar + 8 * c, 0);
                wg_fence();
                wgmma_qk_n64(s, qa[0], qa[1], qa[2], qa[3], dk);
                wg_commit();
                if ((b & 3) == 0) { KF_RELEASE_CHUNK(c); }
                wg_wait<0>();
                fence_regs(s);
                float x0 = s[0], x1 = s[2];
#pragma unroll
                for (int j = 0; j < 8; j++) {
                    x0 = fmaxf(x0, fmaxf(s[4 * j], s[4 * j + 1]));
                    x1 = fmaxf(x1, fmaxf(s[4 * j + 2], s[4 * j + 3]));
                }
                x0 = fmaxf(x0, __shfl_xor_sync(0xffffffffu, x0, 1));
                x0 = fmaxf(x0, __shfl_xor_sync(0xffffffffu, x0, 2));
                x1 = fmaxf(x1, __shfl_xor_sync(0xffffffffu, x1, 1));
                x1 = fmaxf(x1, __shfl_xor_sync(0xffffffffu, x1, 2));
                const float n0 = fmaxf(m0, x0), n1 = fmaxf(m1, x1);
                const float c0 = ex2f(m0 - n0), c1 = ex2f(m1 - n1);
                m0 = n0; m1 = n1;
#pragma unroll
                for (int j = 0; j < 3; j++) {
                    o[4 * j] *= c0; o[4 * j + 1] *= c0; o[4 * j + 2] *= c1; o[4 * j + 3] *= c1;
                }
#pragma unroll
                for (int j = 0; j < 8; j++) {
                    p[2 * j] = pack_bf16(ex2f(s[4 * j] - n0), ex2f(s[4 * j + 1] - n0));
                    p[2 * j + 1] = pack_bf16(ex2f(s[4 * j + 2] - n1), ex2f(s[4 * j + 3] - n1));
                }
                fence_regs(o);
                wg_fence();
                KF_PV(p, 0);
                wg_commit();
                wg_wait<0>();
                fence_regs(o);
            }
        }
        const float inv0 = 1.f / o[8], inv1 = 1.f / o[10];
        {
            uint32_t v0 = pack_bf16(o[0] * inv0, o[1] * inv0), v1 = pack_bf16(o[4] * inv0, o[5] * inv0);
            uint32_t v2 = pack_bf16(o[2] * inv1, o[3] * inv1), v3 = pack_bf16(o[6] * inv1, o[7] * inv1);
            const bool o1 = t & 1, o2 = t & 2;
            uint32_t s0 = o1 ? v0 : v1, s1 = o1 ? v2 : v3;
            s0 = __shfl_xor_sync(0xffffffffu, s0, 1); s1 = __shfl_xor_sync(0xffffffffu, s1, 1);
            uint32_t a0 = o1 ? s0 : v0, a1 = o1 ? v1 : s0, b0 = o1 ? s1 : v2, b1 = o1 ? v3 : s1;
            uint32_t x0 = o2 ? a0 : b0, x1 = o2 ? a1 : b1;
            x0 = __shfl_xor_sync(0xffffffffu, x0, 2); x1 = __shfl_xor_sync(0xffffffffu, x1, 2);
            uint4 r;
            r.x = o2 ? x0 : a0; r.y = o2 ? x1 : a1; r.z = o2 ? b0 : x0; r.w = o2 ? b1 : x1;
            *(uint4*)(g_o + (size_t)(row0 + (t >> 1) * 8) * DM + head * 16 + (t & 1) * 8) = r;
        }
    }
    if ((tid >> 5) != 10) named_arrive(1, 512);
    named_sync(4 + wg, 128);
    if ((tid & 127) == 0) {
        asm volatile("fence.acq_rel.gpu;" ::: "memory");
        asm volatile("red.relaxed.gpu.global.add.u32 [%0], 1;" ::"l"(&g_oflag[(quarter * 8 + 4 + wg) * 32 + (head >> 2) * 4]) : "memory");
        asm volatile("red.relaxed.gpu.global.add.u32 [%0], 1;" ::"l"(&g_oflag[(quarter * 8 + wg) * 32 + (head >> 2) * 4]) : "memory");
    }

    if (wg < 2) {
        const int wi = warp;
        const int r0 = mt * 64 + wi * 16 + g;
        const int cb = nt * 128 + wg * 64;
        uint32_t xr[16], wr[8];
#pragma unroll
        for (int j = 0; j < 8; j++) {
            xr[2 * j] = __ldg((const uint32_t*)(x + (size_t)r0 * DM + cb + 8 * j + 2 * t));
            xr[2 * j + 1] = __ldg((const uint32_t*)(x + (size_t)(r0 + 8) * DM + cb + 8 * j + 2 * t));
            wr[j] = __ldg((const uint32_t*)(w_r + cb + 8 * j + 2 * t));
        }
        float wsum = 0.f;
        {
            const uint4 a = __ldg((const uint4*)(w_r + lane * 16)), b = __ldg((const uint4*)(w_r + lane * 16 + 8));
            const uint32_t w[8] = {a.x, a.y, a.z, a.w, b.x, b.y, b.z, b.w};
#pragma unroll
            for (int i = 0; i < 8; i++) wsum += bf_lo(w[i]) + bf_hi(w[i]);
#pragma unroll
            for (int o = 16; o > 0; o >>= 1) wsum += __shfl_xor_sync(0xffffffffu, wsum, o);
        }
        float acc[32];
#pragma unroll
        for (int i = 0; i < 32; i++) acc[i] = 0.f;
        fence_regs(acc);
#pragma unroll 1
        for (int i = 0; i < 8; i++) {
            mbar_wait(obar + 8 * i, 0);
            const int kb = __shfl_sync(0xffffffffu, (int)s_order[i], 0);
            mbar_wait(wbar + 8 * kb, 0);
            const uint32_t wa = (kb < 4) ? (KF_OFF_WO + kb * 16384) : ((kb - 4) * KF_CH_S);
            const uint64_t da = make_desc(sb + (4 + (kb >> 1)) * KF_CH_S + (kb & 1) * 8192, 16, 1024, 1);
            const uint64_t db = make_desc(sb + wa + wg * 8192, 1024, 1024, 1);
            wg_fence();
#pragma unroll
            for (int k = 0; k < 4; k++) wgmma_k3_n64(acc, da + k * 2, db + k * 128, (i | k) != 0);
            wg_commit();
        }
        wg_wait<0>();
        fence_regs(acc);
        float hv[32];
        uint32_t hp[16];
        float s0 = 0.f, s1 = 0.f, d0 = 0.f, d1 = 0.f;
#pragma unroll
        for (int j = 0; j < 8; j++) {
            const uint32_t a01 = pack_bf16(acc[4 * j], acc[4 * j + 1]), a23 = pack_bf16(acc[4 * j + 2], acc[4 * j + 3]);
            hp[2 * j] = pack_bf16(bf_lo(xr[2 * j]) + bf_lo(a01), bf_hi(xr[2 * j]) + bf_hi(a01));
            hp[2 * j + 1] = pack_bf16(bf_lo(xr[2 * j + 1]) + bf_lo(a23), bf_hi(xr[2 * j + 1]) + bf_hi(a23));
            hv[4 * j] = bf_lo(hp[2 * j]); hv[4 * j + 1] = bf_hi(hp[2 * j]);
            hv[4 * j + 2] = bf_lo(hp[2 * j + 1]); hv[4 * j + 3] = bf_hi(hp[2 * j + 1]);
            const float wl = bf_lo(wr[j]), wh = bf_hi(wr[j]);
            s0 += hv[4 * j] + hv[4 * j + 1];
            s1 += hv[4 * j + 2] + hv[4 * j + 3];
            d0 = fmaf(hv[4 * j], wl, fmaf(hv[4 * j + 1], wh, d0));
            d1 = fmaf(hv[4 * j + 2], wl, fmaf(hv[4 * j + 3], wh, d1));
        }
        float mu0 = s0 * (1.f / 16), mu1 = s1 * (1.f / 16);
        float q0 = 0.f, q1 = 0.f;
#pragma unroll
        for (int j = 0; j < 8; j++) {
            float a = hv[4 * j] - mu0, b = hv[4 * j + 1] - mu0, c = hv[4 * j + 2] - mu1, d = hv[4 * j + 3] - mu1;
            q0 = fmaf(a, a, fmaf(b, b, q0));
            q1 = fmaf(c, c, fmaf(d, d, q1));
        }
#pragma unroll
        for (int o = 1; o < 4; o <<= 1) {
            const float m0 = __shfl_xor_sync(0xffffffffu, mu0, o), m1 = __shfl_xor_sync(0xffffffffu, mu1, o);
            const float e0 = __shfl_xor_sync(0xffffffffu, q0, o), e1 = __shfl_xor_sync(0xffffffffu, q1, o);
            d0 += __shfl_xor_sync(0xffffffffu, d0, o);
            d1 += __shfl_xor_sync(0xffffffffu, d1, o);
            const float f0 = mu0 - m0, f1 = mu1 - m1;
            q0 = q0 + e0 + f0 * f0 * (8.f * o);
            q1 = q1 + e1 + f1 * f1 * (8.f * o);
            mu0 = 0.5f * (mu0 + m0); mu1 = 0.5f * (mu1 + m1);
        }
        float4* part = g_part + (size_t)mt * 512 + wi * 16 + g;
        if (t < 2) {
            float4* dst = part + (nt * 2 + wg) * 64 + t * 8;
            const float a = t ? mu1 : mu0, b = t ? q1 : q0, c = t ? d1 : d0;
            asm volatile("st.relaxed.gpu.global.v4.f32 [%0], {%1, %2, %3, %4};" ::"l"(dst), "f"(a), "f"(b), "f"(c), "f"(1.0f) : "memory");
        }
        const uint32_t stg_off = KF_OFF_WO + (wi >> 1) * 16384 + wg * 8192 + (wi & 1) * 4096;
        const uint32_t stg_o = sb + stg_off, stg_h = stg_o + 2048;
        const int srow = (lane & 7) + ((lane >> 3) & 1) * 8;
        const int sj = lane >> 4;
        named_sync(4 + wg, 128);
#pragma unroll
        for (int j = 0; j < 8; j += 2) {
            const uint32_t off = srow * 128 + (((j + sj) ^ (srow & 7)) << 4);
            stmatrix_x4(stg_h + off, hp[2 * j], hp[2 * j + 1], hp[2 * j + 2], hp[2 * j + 3]);
        }
        __syncwarp();
#pragma unroll
        for (int i = 0; i < 4; i++) {
            const int row = i * 4 + (lane >> 3), ch = lane & 7;
            const uint4 vh = *(const uint4*)(sp + stg_off + 2048 + row * 128 + ((ch ^ (row & 7)) << 4));
            *(uint4*)(g_h + (size_t)(mt * 64 + wi * 16 + row) * DM + cb + ch * 8) = vh;
        }
        named_arrive(8, 288);
        float mean[2], den[2], rr[2];
        {
            float4 v[4];
            int spins = 0;
            while (true) {
#pragma unroll
                for (int i = 0; i < 4; i++) {
                    const float4* p = part + (t + (i & 1) * 4) * 64 + (i >> 1) * 8;
                    asm volatile("ld.relaxed.gpu.global.v4.f32 {%0, %1, %2, %3}, [%4];" : "=f"(v[i].x), "=f"(v[i].y), "=f"(v[i].z), "=f"(v[i].w) : "l"(p) : "memory");
                }
                const bool ok = (v[0].w != 0.f) && (v[1].w != 0.f) && (v[2].w != 0.f) && (v[3].w != 0.f);
                if (__all_sync(0xffffffffu, ok) || ++spins > (1 << 22)) break;
            }
#pragma unroll
            for (int u = 0; u < 2; u++) {
                float mu = v[2 * u].x + v[2 * u + 1].x, m2 = v[2 * u].y + v[2 * u + 1].y, hw = v[2 * u].z + v[2 * u + 1].z;
#pragma unroll
                for (int o = 1; o < 4; o <<= 1) {
                    mu += __shfl_xor_sync(0xffffffffu, mu, o);
                    m2 += __shfl_xor_sync(0xffffffffu, m2, o);
                    hw += __shfl_xor_sync(0xffffffffu, hw, o);
                }
                mu *= 0.125f;
                const float da = v[2 * u].x - mu, db = v[2 * u + 1].x - mu;
                float dd = 64.f * (da * da + db * db);
#pragma unroll
                for (int o = 1; o < 4; o <<= 1) dd += __shfl_xor_sync(0xffffffffu, dd, o);
                m2 += dd;
                mean[u] = rbf(mu);
                den[u] = rbf(sqrtf(rbf(rbf(m2 * (1.f / DM)) + 1e-5f)));
                rr[u] = rbf((hw - mean[u] * wsum) / den[u]);
            }
        }
        named_arrive(3, 512);
        if (nt == 0 && wg == 0) {
            float2* s_st = (float2*)(sp + KF_OFF_WO + 49152);
            if (t == 0) {
                s_key[wi * 16 + g] = make_key(rr[0], r0);
                s_key[wi * 16 + g + 8] = make_key(rr[1], r0 + 8);
                s_st[wi * 16 + g] = make_float2(mean[0], den[0]);
                s_st[wi * 16 + g + 8] = make_float2(mean[1], den[1]);
            }
            named_sync(4, 128);
            if (warp == 0) {
                uint32_t k1, k2;
                warp_top2(s_key[lane], s_key[lane + 32], k1, k2);
                if (lane < 2) {
                    const uint32_t k = lane ? k2 : k1;
                    const float2 st = s_st[key_token(k) & 63];
                    asm volatile("st.relaxed.gpu.global.v4.u32 [%0], {%1, %2, %3, %4};" ::"l"(g_cand + mt * 2 + lane), "r"(k),
                                 "r"(1u), "r"(__float_as_uint(st.x)), "r"(__float_as_uint(st.y)) : "memory");
                }
            }
        }
        const float i0 = 1.f / den[0], i1 = 1.f / den[1];
#pragma unroll
        for (int j = 0; j < 8; j += 2) {
            uint32_t ro[4];
#pragma unroll
            for (int u = 0; u < 2; u++) {
                const int jj = j + u;
                const float a = hv[4 * jj], b = hv[4 * jj + 1], c = hv[4 * jj + 2], d = hv[4 * jj + 3];
                const uint32_t u01 = pack_bf16(a - mean[0], b - mean[0]), u23 = pack_bf16(c - mean[1], d - mean[1]);
                const uint32_t n01 = pack_bf16(bf_lo(u01) * i0, bf_hi(u01) * i0), n23 = pack_bf16(bf_lo(u23) * i1, bf_hi(u23) * i1);
                ro[2 * u] = pack_bf16(a + bf_lo(n01), b + bf_hi(n01));
                ro[2 * u + 1] = pack_bf16(c + bf_lo(n23), d + bf_hi(n23));
            }
            const uint32_t off = srow * 128 + (((j + sj) ^ (srow & 7)) << 4);
            stmatrix_x4(stg_o + off, ro[0], ro[1], ro[2], ro[3]);
        }
        __syncwarp();
#pragma unroll
        for (int i = 0; i < 4; i++) {
            const int row = i * 4 + (lane >> 3), ch = lane & 7;
            const uint4 vo = *(const uint4*)(sp + stg_off + row * 128 + ((ch ^ (row & 7)) << 4));
            *(uint4*)(out + (size_t)(mt * 64 + wi * 16 + row) * DM + cb + ch * 8) = vo;
        }
        named_sync(4 + wg, 128);
        if ((tid & 127) == 0) red_release_add(&g_sflag[mt]);
    } else {
        const bool worker = blockIdx.x < FF / 16;
        const bool downer = blockIdx.x >= 64;
        const int mtid = tid - 256, mwarp = mtid >> 5;
        const int c0 = (blockIdx.x - 64) * 8;
        float* s_x = (float*)(sp + KF_OFF_WO + 49152 + 8192);
        float* s_red = (float*)(sp + KF_OFF_WO + 49152 + 8192 + 4096);
        if (mwarp == 2) {
            named_sync(1, 512);
            uint32_t done = 0;
            int n = 0, spins = 0;
            while (done != 0xFFu && ++spins < (1 << 22)) {
                const bool rdy = lane < 8 && ld_acquire(&g_oflag[mt * 32 + lane * 4]) >= 4u;
                uint32_t todo = __ballot_sync(0xffffffffu, rdy) & ~done;
                done |= todo;
                if (todo && lane == 0) {
                    asm volatile("fence.proxy.async.global;" ::: "memory");
                    while (todo) {
                        const int kb = __ffs(todo) - 1;
                        todo &= todo - 1;
                        s_order[n] = kb;
                        mbar_expect_tx(obar + 8 * n, 8192);
                        tma_load_3d(sb + (4 + (kb >> 1)) * KF_CH_S + (kb & 1) * 8192, &tm_o, 0, mt * 64, kb, obar + 8 * n);
                        n++;
                    }
                }
                n = __shfl_sync(0xffffffffu, n, 0);
                if (done != 0xFFu) __nanosleep(POLL_NS);
            }
            if (lane == 0 && worker) {
                mbar_expect_tx(gbar, 32768);
                for (int i = 0; i < 4; i++) {
                    tma_load_2d(sb + i * KF_CH_S + 16384, &tm_g, blockIdx.x * 16, i * 128, gbar);
                    tma_load_2d(sb + (4 + i) * KF_CH_S + 16384, &tm_u, blockIdx.x * 16, i * 128, gbar);
                }
            }
        }
        if (mwarp == 1) {
            named_sync(8, 288);
            if (lane == 0) {
                red_release_add(&g_hflag[mt]);
                if (downer) {
                    mbar_expect_tx(dbar, 7 * 4096);
                    for (int i = 0; i < 7; i++) tma_load_2d(sb + (4 + (i >> 2)) * KF_CH_S + (i & 3) * 4096, &tm_d, c0, i * 256, dbar);
                }
            }
            __syncwarp();
        }
        named_sync(3, 512);
        if (mwarp == 0) {
            uint4 ca, cb4;
            int spins = 0;
            while (true) {
                asm volatile("ld.relaxed.gpu.global.v4.u32 {%0, %1, %2, %3}, [%4];" : "=r"(ca.x), "=r"(ca.y), "=r"(ca.z), "=r"(ca.w) : "l"(g_cand + 2 * lane) : "memory");
                asm volatile("ld.relaxed.gpu.global.v4.u32 {%0, %1, %2, %3}, [%4];" : "=r"(cb4.x), "=r"(cb4.y), "=r"(cb4.z), "=r"(cb4.w) : "l"(g_cand + 2 * lane + 1) : "memory");
                const unsigned int hf = ld_acquire(&g_hflag[lane]);
                const bool ok = ca.y != 0 && cb4.y != 0 && hf >= 4u;
                if (__all_sync(0xffffffffu, ok) || ++spins > (1 << 22)) break;
            }
            uint32_t k1, k2;
            warp_top2(ca.x, cb4.x, k1, k2);
            if (ca.x == k1) s_sel[0] = ca;
            if (cb4.x == k1) s_sel[0] = cb4;
            if (ca.x == k2) s_sel[1] = ca;
            if (cb4.x == k2) s_sel[1] = cb4;
        }
        named_sync(2, 256);
        int idx[2];
        float mean[2], inv[2], rv[2];
#pragma unroll
        for (int u = 0; u < 2; u++) {
            const uint4 c = s_sel[u];
            idx[u] = key_token(c.x);
            rv[u] = key_value(c.x);
            mean[u] = __uint_as_float(c.z);
            inv[u] = 1.f / __uint_as_float(c.w);
        }
        float hfin = 0.f;
        if (downer && mtid < 16) hfin = __bfloat162float(__ldcg((const __nv_bfloat16*)(g_h + (size_t)((mtid >> 3) ? idx[1] : idx[0]) * DM + c0 + (mtid & 7))));
        if (worker) {
            {
                const uint32_t h0 = __ldcg((const uint32_t*)(g_h + (size_t)idx[0] * DM + 2 * mtid));
                const uint32_t h1 = __ldcg((const uint32_t*)(g_h + (size_t)idx[1] * DM + 2 * mtid));
                const uint32_t u0 = pack_bf16(bf_lo(h0) - mean[0], bf_hi(h0) - mean[0]), u1 = pack_bf16(bf_lo(h1) - mean[1], bf_hi(h1) - mean[1]);
                const uint32_t n0 = pack_bf16(bf_lo(u0) * inv[0], bf_hi(u0) * inv[0]), n1 = pack_bf16(bf_lo(u1) * inv[1], bf_hi(u1) * inv[1]);
                *(float4*)(s_x + 4 * mtid) = make_float4(bf_lo(n0), bf_lo(n1), bf_hi(n0), bf_hi(n1));
            }
            mbar_wait(gbar, 0);
            named_sync(2, 256);
            float acc[16];
#pragma unroll
            for (int i = 0; i < 16; i++) acc[i] = 0.f;
            const uint8_t* wbase = sp + ((mwarp >> 2) * 4 + (mwarp & 3)) * KF_CH_S + 16384 + lane * 16;
            const float* xb = s_x + 2 * (128 * (mwarp & 3) + (lane >> 1));
#pragma unroll
            for (int j = 0; j < 8; j++) {
                const uint4 w = *(const uint4*)(wbase + j * 512);
                const float2 xx = *(const float2*)(xb + 32 * j);
                const uint32_t ww[4] = {w.x, w.y, w.z, w.w};
#pragma unroll
                for (int q = 0; q < 4; q++) {
                    const float wl = bf_lo(ww[q]), wh = bf_hi(ww[q]);
                    acc[2 * q] = fmaf(xx.x, wl, acc[2 * q]); acc[2 * q + 1] = fmaf(xx.x, wh, acc[2 * q + 1]);
                    acc[8 + 2 * q] = fmaf(xx.y, wl, acc[8 + 2 * q]); acc[8 + 2 * q + 1] = fmaf(xx.y, wh, acc[8 + 2 * q + 1]);
                }
            }
#define KF_STEP(O, N)                                                          \
            {                                                                  \
                const bool up = (lane & (O)) != 0;                             \
                _Pragma("unroll") for (int i = 0; i < (N); i++) {              \
                    const float send = up ? acc[i] : acc[i + (N)];             \
                    const float keep = up ? acc[i + (N)] : acc[i];             \
                    acc[i] = keep + __shfl_xor_sync(0xffffffffu, send, (O));   \
                }                                                              \
            }
            KF_STEP(16, 8) KF_STEP(8, 4) KF_STEP(4, 2) KF_STEP(2, 1)
            {
                const int v = ((lane & 16) ? 8 : 0) + ((lane & 8) ? 4 : 0) + ((lane & 4) ? 2 : 0) + ((lane & 2) ? 1 : 0);
                s_gu[mwarp * 32 + (v >> 3) * 16 + (lane & 1) * 8 + (v & 7)] = acc[0];
            }
            named_sync(2, 256);
            if (mtid < 16) {
                uint32_t a2 = 0;
#pragma unroll
                for (int u = 0; u < 2; u++) {
                    const float* pg = s_gu + u * 16 + mtid;
                    const float gb = rbf((pg[0] + pg[32]) + (pg[64] + pg[96]));
                    const float ub = rbf((pg[128] + pg[160]) + (pg[192] + pg[224]));
                    const float sg = rbf(gb / (1.f + __expf(-gb)));
                    const float a = sg * ub;
                    uint32_t ab = (uint32_t)__bfloat16_as_ushort(__float2bfloat16_rn(a));
                    if (ab == 0xFFFFu) ab = 0x7FFFu;
                    a2 |= ab << (16 * u);
                }
                asm volatile("st.relaxed.gpu.global.u32 [%0], %1;" ::"l"(g_act + blockIdx.x * 16 + mtid), "r"(a2) : "memory");
            }
        }
        if (downer) {
            uint32_t av[7];
            {
                int spins = 0;
                while (true) {
                    bool ok = true;
#pragma unroll
                    for (int j = 0; j < 7; j++) {
                        asm volatile("ld.relaxed.gpu.global.u32 %0, [%1];" : "=r"(av[j]) : "l"(g_act + mtid + 256 * j) : "memory");
                        ok = ok && ((av[j] & 0xFFFFu) != 0xFFFFu) && ((av[j] >> 16) != 0xFFFFu);
                    }
                    if (mtid < 2) ok = ok && (ld_acquire(&g_sflag[(mtid ? idx[1] : idx[0]) >> 6]) >= 8u);
                    if (__all_sync(0xffffffffu, ok) || ++spins > (1 << 20)) break;
                    __nanosleep(20);
                }
            }
            mbar_wait(dbar, 0);
            float acc[16];
#pragma unroll
            for (int i = 0; i < 16; i++) acc[i] = 0.f;
#pragma unroll
            for (int j = 0; j < 7; j++) {
                const uint4 w = *(const uint4*)(sp + (4 + (j >> 2)) * KF_CH_S + (j & 3) * 4096 + mtid * 16);
                const float a0 = bf_lo(av[j]), a1 = bf_hi(av[j]);
                const uint32_t ww[4] = {w.x, w.y, w.z, w.w};
#pragma unroll
                for (int q = 0; q < 4; q++) {
                    const float wl = bf_lo(ww[q]), wh = bf_hi(ww[q]);
                    acc[2 * q] = fmaf(a0, wl, acc[2 * q]); acc[2 * q + 1] = fmaf(a0, wh, acc[2 * q + 1]);
                    acc[8 + 2 * q] = fmaf(a1, wl, acc[8 + 2 * q]); acc[8 + 2 * q + 1] = fmaf(a1, wh, acc[8 + 2 * q + 1]);
                }
            }
            KF_STEP(16, 8) KF_STEP(8, 4) KF_STEP(4, 2) KF_STEP(2, 1)
            acc[0] += __shfl_xor_sync(0xffffffffu, acc[0], 1);
            if ((lane & 1) == 0) {
                const int v = ((lane & 16) ? 8 : 0) + ((lane & 8) ? 4 : 0) + ((lane & 4) ? 2 : 0) + ((lane & 2) ? 1 : 0);
                s_red[mwarp * 16 + v] = acc[0];
            }
            named_sync(2, 256);
            if (mtid < 16) {
                const int u = mtid >> 3;
                float y = 0.f;
#pragma unroll
                for (int w = 0; w < 8; w++) y += s_red[w * 16 + mtid];
                const float sig = rbf(1.f / (1.f + __expf(-(u ? rv[1] : rv[0]))));
                const float xn = rbf(rbf(hfin - (u ? mean[1] : mean[0])) * (u ? inv[1] : inv[0]));
                const float ov = hfin + rbf(xn + rbf(rbf(y) * sig));
                out[(size_t)(u ? idx[1] : idx[0]) * DM + c0 + (mtid & 7)] = __float2bfloat16_rn(ov);
            }
            if (blockIdx.x == gridDim.x - 1 && mtid == 0) g_epoch = g_epoch + 1u;
        }
    }
}

typedef CUresult (*PFN_encodeTiled)(CUtensorMap*, CUtensorMapDataType, cuuint32_t, void*, const cuuint64_t*, const cuuint64_t*,
                                    const cuuint32_t*, const cuuint32_t*, CUtensorMapInterleave, CUtensorMapSwizzle,
                                    CUtensorMapL2promotion, CUtensorMapFloatOOBfill);

void make_map(PFN_encodeTiled enc, CUtensorMap* m, const void* ptr, uint64_t cols, uint64_t rows, uint32_t bcols, uint32_t brows) {
    cuuint64_t dims[2] = {cols, rows};
    cuuint64_t strides[1] = {cols * 2};
    cuuint32_t box[2] = {bcols, brows};
    cuuint32_t es[2] = {1, 1};
    enc(m, CU_TENSOR_MAP_DATA_TYPE_BFLOAT16, 2, const_cast<void*>(ptr), dims, strides, box, es, CU_TENSOR_MAP_INTERLEAVE_NONE,
        CU_TENSOR_MAP_SWIZZLE_128B, CU_TENSOR_MAP_L2_PROMOTION_L2_256B, CU_TENSOR_MAP_FLOAT_OOB_FILL_NONE);
}

void make_map3(PFN_encodeTiled enc, CUtensorMap* m, const void* ptr, uint64_t d0, uint64_t rows, uint64_t d2, uint64_t row_stride_bytes,
               uint64_t d2_stride_bytes, uint32_t b0, uint32_t b1, uint32_t b2) {
    cuuint64_t dims[3] = {d0, rows, d2};
    cuuint64_t strides[2] = {row_stride_bytes, d2_stride_bytes};
    cuuint32_t box[3] = {b0, b1, b2};
    cuuint32_t es[3] = {1, 1, 1};
    enc(m, CU_TENSOR_MAP_DATA_TYPE_BFLOAT16, 3, const_cast<void*>(ptr), dims, strides, box, es, CU_TENSOR_MAP_INTERLEAVE_NONE,
        CU_TENSOR_MAP_SWIZZLE_128B, CU_TENSOR_MAP_L2_PROMOTION_L2_256B, CU_TENSOR_MAP_FLOAT_OOB_FILL_NONE);
}

void make_map_plain(PFN_encodeTiled enc, CUtensorMap* m, const void* ptr, uint64_t cols, uint64_t rows, uint32_t bcols, uint32_t brows) {
    cuuint64_t dims[2] = {cols, rows};
    cuuint64_t strides[1] = {cols * 2};
    cuuint32_t box[2] = {bcols, brows};
    cuuint32_t es[2] = {1, 1};
    enc(m, CU_TENSOR_MAP_DATA_TYPE_BFLOAT16, 2, const_cast<void*>(ptr), dims, strides, box, es, CU_TENSOR_MAP_INTERLEAVE_NONE,
        CU_TENSOR_MAP_SWIZZLE_NONE, CU_TENSOR_MAP_L2_PROMOTION_NONE, CU_TENSOR_MAP_FLOAT_OOB_FILL_NONE);
}

template <typename... KArgs, typename... Args>
void launch(void (*kern)(KArgs...), int grid, int block, int smem, bool pdl, Args... args) {
    cudaLaunchConfig_t cfg = {};
    cfg.gridDim = dim3(grid);
    cfg.blockDim = dim3(block);
    cfg.dynamicSmemBytes = smem;
    cfg.stream = cudaStreamPerThread;
    cudaLaunchAttribute at[1];
    at[0].id = cudaLaunchAttributeProgrammaticStreamSerialization;
    at[0].val.programmaticStreamSerializationAllowed = 1;
    cfg.attrs = at;
    cfg.numAttrs = pdl ? 1 : 0;
    cudaLaunchKernelEx(&cfg, kern, KArgs(args)...);
}

}

extern "C" void kernel_launch(void* const* d_in, const int* in_sizes, int n_in, void* d_out, int out_size) {
    const __nv_bfloat16* x = (const __nv_bfloat16*)d_in[0];
    const __nv_bfloat16* wqkv = (const __nv_bfloat16*)d_in[1];
    const __nv_bfloat16* wo = (const __nv_bfloat16*)d_in[2];
    const __nv_bfloat16* w_r = (const __nv_bfloat16*)d_in[4];
    const __nv_bfloat16* w_gate = (const __nv_bfloat16*)d_in[5];
    const __nv_bfloat16* w_up = (const __nv_bfloat16*)d_in[6];
    const __nv_bfloat16* w_down = (const __nv_bfloat16*)d_in[7];
    __nv_bfloat16* out = (__nv_bfloat16*)d_out;

    static PFN_encodeTiled enc = nullptr;
    static void* g_o_ptr = nullptr;
    if (!enc) {
        cudaDriverEntryPointQueryResult qres;
        void* fn = nullptr;
        cudaGetDriverEntryPoint("cuTensorMapEncodeTiled", &fn, cudaEnableDefault, &qres);
        enc = (PFN_encodeTiled)fn;
        cudaGetSymbolAddress(&g_o_ptr, g_o);
        cudaFuncSetAttribute(k1_qkv, cudaFuncAttributeMaxDynamicSharedMemorySize, K1_SMEM);
        cudaFuncSetAttribute(kf_main, cudaFuncAttributeMaxDynamicSharedMemorySize, KF_SMEM);
    }
    CUtensorMap tm_x, tm_w, tm_o, tm_wo, tm_g, tm_u, tm_d;
    make_map_plain(enc, &tm_d, w_down, DM, FF, 8, 256);
    make_map_plain(enc, &tm_g, w_gate, FF, DM, 16, 128);
    make_map_plain(enc, &tm_u, w_up, FF, DM, 16, 128);
    make_map(enc, &tm_x, x, DM, SEQ, 64, 128);
    make_map3(enc, &tm_w, wqkv, DM, DM, 3, 3 * DM * 2, DM * 2, 64, 64, 3);
    make_map3(enc, &tm_o, g_o_ptr, 64, SEQ, 8, DM * 2, 128, 64, 64, 1);
    make_map3(enc, &tm_wo, wo, 64, DM, 8, DM * 2, 128, 64, 64, 2);

    const bool pdl = true;
    launch(k1_qkv, 128, 544, K1_SMEM, false, tm_x, tm_w, x);
    launch(kf_main, 128, 512, KF_SMEM, pdl, tm_o, tm_wo, tm_g, tm_u, tm_d, x, wo, w_r, w_gate, w_up, w_down, out);
}
```

```cpp
#include <cuda_runtime.h>
#include <cuda_bf16.h>
#include <cuda.h>
#include <stdint.h>

namespace {

constexpr int SEQ = 2048, DM = 512, NH = 32, FF = 1792;

__device__ __align__(1024) uint8_t g_q[NH * 2 * SEQ * 16];
__device__ __align__(1024) uint8_t g_kv[NH * 8 * 16384];
__device__ float g_norm[16 * NH * 3];
__device__ __align__(1024) __nv_bfloat16 g_o[SEQ * DM];
__device__ __align__(1024) __nv_bfloat16 g_h[SEQ * DM];
__device__ __align__(16) uint4 g_cand[64];
__device__ unsigned int g_oflag[32 * 8 * 32];
__device__ unsigned int g_hflag[32];
__device__ unsigned int g_sflag[32];
__device__ unsigned int g_act[FF];
__device__ unsigned int g_epoch;
__device__ __align__(16) float4 g_ln1[SEQ];
__device__ __align__(16) float4 g_part[32 * 8 * 64];

__device__ __forceinline__ uint32_t smem_u32(const void* p) { return (uint32_t)__cvta_generic_to_shared(p); }
__device__ __forceinline__ void wg_fence() { asm volatile("wgmma.fence.sync.aligned;" ::: "memory"); }
__device__ __forceinline__ void wg_commit() { asm volatile("wgmma.commit_group.sync.aligned;" ::: "memory"); }
template <int N> __device__ __forceinline__ void wg_wait() { asm volatile("wgmma.wait_group.sync.aligned %0;" ::"n"(N) : "memory"); }
template <int N> __device__ __forceinline__ void fence_regs(float (&r)[N]) {
#pragma unroll
    for (int i = 0; i < N; i++) asm volatile("" : "+f"(r[i])::"memory");
}
__device__ __forceinline__ uint64_t make_desc(uint32_t addr, uint32_t lbo, uint32_t sbo, uint32_t swz) {
    uint64_t d = 0;
    d |= (uint64_t)((addr & 0x3FFFF) >> 4);
    d |= (uint64_t)((lbo & 0x3FFFF) >> 4) << 16;
    d |= (uint64_t)((sbo & 0x3FFFF) >> 4) << 32;
    d |= (uint64_t)swz << 62;
    return d;
}
__device__ __forceinline__ void mbar_init(uint32_t bar, uint32_t cnt) {
    asm volatile("mbarrier.init.shared::cta.b64 [%0], %1;" ::"r"(bar), "r"(cnt) : "memory");
}
__device__ __forceinline__ void mbar_expect_tx(uint32_t bar, uint32_t bytes) {
    asm volatile("mbarrier.arrive.expect_tx.shared::cta.b64 _, [%0], %1;" ::"r"(bar), "r"(bytes) : "memory");
}
__device__ __forceinline__ void mbar_arrive(uint32_t bar) {
    asm volatile("mbarrier.arrive.shared::cta.b64 _, [%0];" ::"r"(bar) : "memory");
}
__device__ __forceinline__ void mbar_wait(uint32_t bar, uint32_t parity) {
    asm volatile(
        "{\n.reg .pred p;\nWAIT_%=:\n"
        "mbarrier.try_wait.parity.shared::cta.b64 p, [%0], %1;\n"
        "@p bra DONE_%=;\nbra WAIT_%=;\nDONE_%=:\n}\n" ::"r"(bar), "r"(parity) : "memory");
}
__device__ __forceinline__ void bulk_g2s(uint32_t dst, const void* src, uint32_t bytes, uint32_t bar) {
    asm volatile("cp.async.bulk.shared::cluster.global.mbarrier::complete_tx::bytes [%0], [%1], %2, [%3];" ::"r"(dst),
                 "l"(src), "r"(bytes), "r"(bar) : "memory");
}
__device__ __forceinline__ void bulk_s2g(void* dst, uint32_t src, uint32_t bytes) {
    asm volatile("cp.async.bulk.global.shared::cta.bulk_group [%0], [%1], %2;" ::"l"(dst), "r"(src), "r"(bytes) : "memory");
}
__device__ __forceinline__ void tma_load_2d(uint32_t dst, const CUtensorMap* tm, int c0, int c1, uint32_t bar) {
    asm volatile("cp.async.bulk.tensor.2d.shared::cluster.global.mbarrier::complete_tx::bytes [%0], [%1, {%3, %4}], [%2];" ::"r"(dst),
                 "l"(tm), "r"(bar), "r"(c0), "r"(c1) : "memory");
}
__device__ __forceinline__ void tma_load_3d(uint32_t dst, const CUtensorMap* tm, int c0, int c1, int c2, uint32_t bar) {
    asm volatile("cp.async.bulk.tensor.3d.shared::cluster.global.mbarrier::complete_tx::bytes [%0], [%1, {%3, %4, %5}], [%2];" ::"r"(dst),
                 "l"(tm), "r"(bar), "r"(c0), "r"(c1), "r"(c2) : "memory");
}
__device__ __forceinline__ void prefetch_l2(const void* p, uint32_t bytes) {
    asm volatile("cp.async.bulk.prefetch.L2.global [%0], %1;" ::"l"(p), "r"(bytes) : "memory");
}
__device__ __forceinline__ void fence_proxy_async() { asm volatile("fence.proxy.async.shared::cta;" ::: "memory"); }
__device__ __forceinline__ void fence_barrier_init() { asm volatile("fence.mbarrier_init.release.cluster;" ::: "memory"); }
__device__ __forceinline__ void pdl_launch() { asm volatile("griddepcontrol.launch_dependents;" ::: "memory"); }
__device__ __forceinline__ void pdl_wait() { asm volatile("griddepcontrol.wait;" ::: "memory"); }
__device__ __forceinline__ void named_sync(int id, int n) { asm volatile("bar.sync %0, %1;" ::"r"(id), "r"(n) : "memory"); }
__device__ __forceinline__ void named_arrive(int id, int n) { asm volatile("bar.arrive %0, %1;" ::"r"(id), "r"(n) : "memory"); }

__device__ __forceinline__ float ex2f(float x) { float y; asm("ex2.approx.ftz.f32 %0, %1;" : "=f"(y) : "f"(x)); return y; }
__device__ __forceinline__ uint32_t pack_bf16(float lo, float hi) {
    uint32_t r; asm("cvt.rn.bf16x2.f32 %0, %1, %2;" : "=r"(r) : "f"(hi), "f"(lo)); return r;
}
__device__ __forceinline__ float bf_lo(uint32_t v) { return __uint_as_float(v << 16); }
__device__ __forceinline__ float bf_hi(uint32_t v) { return __uint_as_float(v & 0xFFFF0000u); }
__device__ __forceinline__ float rbf(float x) { return __bfloat162float(__float2bfloat16_rn(x)); }
__device__ __forceinline__ uint32_t fma_bf16x2(uint32_t a, uint32_t b, uint32_t c) {
    uint32_t r; asm("fma.rn.bf16x2 %0, %1, %2, %3;" : "=r"(r) : "r"(a), "r"(b), "r"(c)); return r;
}
__device__ __forceinline__ void stmatrix_x4(uint32_t addr, uint32_t r0, uint32_t r1, uint32_t r2, uint32_t r3) {
    asm volatile("stmatrix.sync.aligned.m8n8.x4.shared.b16 [%0], {%1, %2, %3, %4};" ::"r"(addr), "r"(r0), "r"(r1), "r"(r2), "r"(r3) : "memory");
}
__device__ __forceinline__ void stmatrix_x4_trans(uint32_t addr, uint32_t r0, uint32_t r1, uint32_t r2, uint32_t r3) {
    asm volatile("stmatrix.sync.aligned.m8n8.x4.trans.shared.b16 [%0], {%1, %2, %3, %4};" ::"r"(addr), "r"(r0), "r"(r1), "r"(r2), "r"(r3) : "memory");
}

__device__ __forceinline__ void wgmma_k1_n136(float (&d)[68], uint64_t desca, uint64_t descb, int scale_d) {
  asm volatile("{\n.reg .pred p;\nsetp.ne.b32 p, %70, 0;\n"
    "wgmma.mma_async.sync.aligned.m64n136k16.f32.bf16.bf16 "
    "{%0, %1, %2, %3, %4, %5, %6, %7, %8, %9, %10, %11, %12, %13, %14, %15, %16, %17, %18, %19, %20, %21, %22, %23, %24, %25, %26, %27, %28, %29, %30, %31, %32, %33, %34, %35, %36, %37, %38, %39, %40, %41, %42, %43, %44, %45, %46, %47, %48, %49, %50, %51, %52, %53, %54, %55, %56, %57, %58, %59, %60, %61, %62, %63, %64, %65, %66, %67}, "
    "%68, %69, p, 1, 1, 1, 0;\n}\n"
    : "+f"(d[0]), "+f"(d[1]), "+f"(d[2]), "+f"(d[3]), "+f"(d[4]), "+f"(d[5]), "+f"(d[6]), "+f"(d[7]), "+f"(d[8]), "+f"(d[9]), "+f"(d[10]), "+f"(d[11]), "+f"(d[12]), "+f"(d[13]), "+f"(d[14]), "+f"(d[15]), "+f"(d[16]), "+f"(d[17]), "+f"(d[18]), "+f"(d[19]), "+f"(d[20]), "+f"(d[21]), "+f"(d[22]), "+f"(d[23]), "+f"(d[24]), "+f"(d[25]), "+f"(d[26]), "+f"(d[27]), "+f"(d[28]), "+f"(d[29]), "+f"(d[30]), "+f"(d[31]), "+f"(d[32]), "+f"(d[33]), "+f"(d[34]), "+f"(d[35]), "+f"(d[36]), "+f"(d[37]), "+f"(d[38]), "+f"(d[39]), "+f"(d[40]), "+f"(d[41]), "+f"(d[42]), "+f"(d[43]), "+f"(d[44]), "+f"(d[45]), "+f"(d[46]), "+f"(d[47]), "+f"(d[48]), "+f"(d[49]), "+f"(d[50]), "+f"(d[51]), "+f"(d[52]), "+f"(d[53]), "+f"(d[54]), "+f"(d[55]), "+f"(d[56]), "+f"(d[57]), "+f"(d[58]), "+f"(d[59]), "+f"(d[60]), "+f"(d[61]), "+f"(d[62]), "+f"(d[63]), "+f"(d[64]), "+f"(d[65]), "+f"(d[66]), "+f"(d[67])
    : "l"(desca), "l"(descb), "r"(scale_d));
}
__device__ __forceinline__ void wgmma_qk_n64(float (&d)[32], uint32_t a0, uint32_t a1, uint32_t a2, uint32_t a3, uint64_t descb) {
  asm volatile("{\n.reg .pred p;\nsetp.ne.b32 p, 0, 0;\n"
    "wgmma.mma_async.sync.aligned.m64n64k16.f32.bf16.bf16 "
    "{%0, %1, %2, %3, %4, %5, %6, %7, %8, %9, %10, %11, %12, %13, %14, %15, %16, %17, %18, %19, %20, %21, %22, %23, %24, %25, %26, %27, %28, %29, %30, %31}, "
    "{%32, %33, %34, %35}, %36, p, 1, 1, 0;\n}\n"
    : "=f"(d[0]), "=f"(d[1]), "=f"(d[2]), "=f"(d[3]), "=f"(d[4]), "=f"(d[5]), "=f"(d[6]), "=f"(d[7]), "=f"(d[8]), "=f"(d[9]), "=f"(d[10]), "=f"(d[11]), "=f"(d[12]), "=f"(d[13]), "=f"(d[14]), "=f"(d[15]), "=f"(d[16]), "=f"(d[17]), "=f"(d[18]), "=f"(d[19]), "=f"(d[20]), "=f"(d[21]), "=f"(d[22]), "=f"(d[23]), "=f"(d[24]), "=f"(d[25]), "=f"(d[26]), "=f"(d[27]), "=f"(d[28]), "=f"(d[29]), "=f"(d[30]), "=f"(d[31])
    : "r"(a0), "r"(a1), "r"(a2), "r"(a3), "l"(descb));
}
__device__ __forceinline__ void wgmma_pv_n24(float (&d)[12], uint32_t a0, uint32_t a1, uint32_t a2, uint32_t a3, uint64_t descb) {
  asm volatile("{\n.reg .pred p;\nsetp.eq.b32 p, 0, 0;\n"
    "wgmma.mma_async.sync.aligned.m64n24k16.f32.bf16.bf16 "
    "{%0, %1, %2, %3, %4, %5, %6, %7, %8, %9, %10, %11}, "
    "{%12, %13, %14, %15}, %16, p, 1, 1, 1;\n}\n"
    : "+f"(d[0]), "+f"(d[1]), "+f"(d[2]), "+f"(d[3]), "+f"(d[4]), "+f"(d[5]), "+f"(d[6]), "+f"(d[7]), "+f"(d[8]), "+f"(d[9]), "+f"(d[10]), "+f"(d[11])
    : "r"(a0), "r"(a1), "r"(a2), "r"(a3), "l"(descb));
}
__device__ __forceinline__ void wgmma_k3_n64(float (&d)[32], uint64_t desca, uint64_t descb, int scale_d) {
  asm volatile("{\n.reg .pred p;\nsetp.ne.b32 p, %34, 0;\n"
    "wgmma.mma_async.sync.aligned.m64n64k16.f32.bf16.bf16 "
    "{%0, %1, %2, %3, %4, %5, %6, %7, %8, %9, %10, %11, %12, %13, %14, %15, %16, %17, %18, %19, %20, %21, %22, %23, %24, %25, %26, %27, %28, %29, %30, %31}, "
    "%32, %33, p, 1, 1, 0, 1;\n}\n"
    : "+f"(d[0]), "+f"(d[1]), "+f"(d[2]), "+f"(d[3]), "+f"(d[4]), "+f"(d[5]), "+f"(d[6]), "+f"(d[7]), "+f"(d[8]), "+f"(d[9]), "+f"(d[10]), "+f"(d[11]), "+f"(d[12]), "+f"(d[13]), "+f"(d[14]), "+f"(d[15]), "+f"(d[16]), "+f"(d[17]), "+f"(d[18]), "+f"(d[19]), "+f"(d[20]), "+f"(d[21]), "+f"(d[22]), "+f"(d[23]), "+f"(d[24]), "+f"(d[25]), "+f"(d[26]), "+f"(d[27]), "+f"(d[28]), "+f"(d[29]), "+f"(d[30]), "+f"(d[31])
    : "l"(desca), "l"(descb), "r"(scale_d));
}
__device__ __forceinline__ void wgmma_bias_n40(float (&d)[32], uint64_t desca, uint64_t descb) {
  asm volatile("{\n.reg .pred p;\nsetp.eq.b32 p, 0, 0;\n"
    "wgmma.mma_async.sync.aligned.m64n40k16.f32.bf16.bf16 "
    "{%0, %1, %2, %3, %4, %5, %6, %7, %8, %9, %10, %11, %12, %13, %14, %15, %16, %17, %18, %19}, "
    "%20, %21, p, 1, 1, 0, 0;\n}\n"
    : "+f"(d[0]), "+f"(d[1]), "+f"(d[2]), "+f"(d[3]), "+f"(d[4]), "+f"(d[5]), "+f"(d[6]), "+f"(d[7]), "+f"(d[8]), "+f"(d[9]), "+f"(d[10]), "+f"(d[11]), "+f"(d[12]), "+f"(d[13]), "+f"(d[14]), "+f"(d[15]), "+f"(d[16]), "+f"(d[17]), "+f"(d[18]), "+f"(d[19])
    : "l"(desca), "l"(descb));
}

constexpr int K1_XS = 17408;
constexpr int K1_WS = 24576;
constexpr int K1_ST = K1_XS + K1_WS;
constexpr int K1_NST = 5;
constexpr int K1_OFF_MISC = K1_NST * K1_ST;
constexpr int K1_SMEM = K1_OFF_MISC + 2048 + 1024;
constexpr float QSCALE = 0.25f * 1.4426950408889634f;

__global__ void __launch_bounds__(544, 1)
k1_qkv(const __grid_constant__ CUtensorMap tm_x, const __grid_constant__ CUtensorMap tm_w, const __nv_bfloat16* __restrict__ x) {
    extern __shared__ uint8_t smem_raw[];
    const uint32_t sraw = smem_u32(smem_raw);
    const uint32_t sb = (sraw + 1023) & ~1023u;
    uint8_t* sp = smem_raw + (sb - sraw);
    const uint32_t full = sb + K1_OFF_MISC;
    const uint32_t empty = full + 64;
    float* s_mr = (float*)(sp + K1_OFF_MISC + 256);

    const int tid = threadIdx.x, warp = tid >> 5, lane = tid & 31;
    const int mt = blockIdx.x >> 3, nt = blockIdx.x & 7;
    pdl_launch();
    if (tid == 512) {
        for (int i = 0; i < K1_NST; i++) { mbar_init(full + 8 * i, 1); mbar_init(empty + 8 * i, 3); }
        fence_barrier_init();
        for (int kb = 0; kb < K1_NST; kb++) {
            mbar_expect_tx(full + 8 * kb, 16384 + K1_WS);
            tma_load_2d(sb + kb * K1_ST, &tm_x, kb * 64, mt * 128, full + 8 * kb);
            tma_load_3d(sb + kb * K1_ST + K1_XS, &tm_w, nt * 64, kb * 64, 0, full + 8 * kb);
        }
    }
    if (tid < K1_NST * 64) {
        *(uint4*)(sp + (tid >> 6) * K1_ST + 16384 + (tid & 63) * 16) =
            make_uint4(0x3F803F80u, 0x3F803F80u, 0x3F803F80u, 0x3F803F80u);
    }
    fence_proxy_async();
    __syncthreads();

    if (warp == 16) {
        if (lane == 0) {
            for (int kb = K1_NST; kb < 8; kb++) {
                const int s = kb % K1_NST;
                mbar_wait(empty + 8 * s, 0);
                mbar_expect_tx(full + 8 * s, 16384 + K1_WS);
                tma_load_2d(sb + s * K1_ST, &tm_x, kb * 64, mt * 128, full + 8 * s);
                tma_load_3d(sb + s * K1_ST + K1_XS, &tm_w, nt * 64, kb * 64, 0, full + 8 * s);
            }
        }
        __syncwarp();
        if (lane < FF / 128) g_act[blockIdx.x * (FF / 128) + lane] = 0xFFFFFFFFu;
        for (int i = lane; i < 128; i += 32) g_part[blockIdx.x * 128 + i] = make_float4(0.f, 0.f, 0.f, 0.f);
        if (blockIdx.x == 1) { g_cand[lane] = make_uint4(0, 0, 0, 0); g_cand[lane + 32] = make_uint4(0, 0, 0, 0); g_hflag[lane] = 0; g_sflag[lane] = 0; }
        if (lane < 2) g_oflag[(blockIdx.x * 2 + lane) * 32] = 0;
    } else if (warp >= 12) {
        const int r = tid - 384;
        const unsigned int tag = *(volatile unsigned int*)&g_epoch + 1u;
        {
            const int row = mt * 128 + nt * 16 + (r >> 3);
            const uint4* xp = (const uint4*)(x + (size_t)row * DM) + (r & 7);
            uint4 v[8];
#pragma unroll
            for (int i = 0; i < 8; i++) v[i] = __ldg(xp + i * 8);
            float s1 = 0.f;
#pragma unroll
            for (int i = 0; i < 8; i++)
                s1 += ((bf_lo(v[i].x) + bf_hi(v[i].x)) + (bf_lo(v[i].y) + bf_hi(v[i].y))) + ((bf_lo(v[i].z) + bf_hi(v[i].z)) + (bf_lo(v[i].w) + bf_hi(v[i].w)));
#pragma unroll
            for (int o = 1; o < 8; o <<= 1) s1 += __shfl_xor_sync(0xffffffffu, s1, o);
            const float mean = s1 * (1.f / DM);
            float q0 = 0.f, q1 = 0.f;
#pragma unroll
            for (int i = 0; i < 8; i++) {
                const uint32_t w[4] = {v[i].x, v[i].y, v[i].z, v[i].w};
#pragma unroll
                for (int j = 0; j < 4; j++) {
                    const float a = bf_lo(w[j]) - mean, b = bf_hi(w[j]) - mean;
                    q0 = fmaf(a, a, q0); q1 = fmaf(b, b, q1);
                }
            }
            float q = q0 + q1;
#pragma unroll
            for (int o = 1; o < 8; o <<= 1) q += __shfl_xor_sync(0xffffffffu, q, o);
            const float den = rbf(sqrtf(rbf(rbf(q * (1.f / DM)) + 1e-5f)));
            if ((r & 7) == 0)
                asm volatile("st.relaxed.gpu.global.v4.f32 [%0], {%1, %2, %3, %4};" ::"l"(g_ln1 + row), "f"(rbf(mean)), "f"(1.f / den),
                             "f"(__uint_as_float(tag)), "f"(0.f) : "memory");
        }
        {
            float4 v;
            int spins = 0;
            do {
                asm volatile("ld.relaxed.gpu.global.v4.f32 {%0, %1, %2, %3}, [%4];" : "=f"(v.x), "=f"(v.y), "=f"(v.z), "=f"(v.w) : "l"(g_ln1 + mt * 128 + r) : "memory");
            } while (__float_as_uint(v.z) != tag && ++spins < (1 << 22));
            s_mr[(r >> 1) * 4 + (r & 1)] = v.x;
            s_mr[(r >> 1) * 4 + 2 + (r & 1)] = v.y;
        }
        named_arrive(1, 512);
    } else {
        const int part = warp >> 2, hw = warp & 3;
        float acc[68];
#pragma unroll
        for (int i = 0; i < 68; i++) acc[i] = 0.f;
        fence_regs(acc);
#pragma unroll 1
        for (int kb = 0; kb < 8; kb++) {
            const int s = kb % K1_NST;
            mbar_wait(full + 8 * s, (kb / K1_NST) & 1);
            const uint64_t da = make_desc(sb + s * K1_ST + K1_XS + part * 8192, 1024, 1024, 1);
            const uint64_t db = make_desc(sb + s * K1_ST, 16, 1024, 1);
            wg_fence();
#pragma unroll
            for (int k = 0; k < 4; k++) wgmma_k1_n136(acc, da + k * 128, db + k * 2, (kb | k) != 0);
            wg_commit();
            if (kb > 0 && kb <= 8 - K1_NST) {
                wg_wait<1>();
                if ((tid & 127) == 0) mbar_arrive(empty + 8 * (kb - 1));
            }
        }
        wg_wait<0>();
        fence_regs(acc);
        named_sync(1, 512);

        const int t = lane & 3;
        const float cs0 = acc[64], cs1 = acc[66];
        const float sc = (part == 0) ? QSCALE : 1.f;
        const uint32_t stg = sb + (hw >> 1) * K1_ST + K1_XS + part * 8192 + (hw & 1) * 4096;
        const uint32_t st_addr = stg + ((lane >> 3) & 1) * 2048 + ((lane >> 4) * 8 + (lane & 7)) * 16;
#pragma unroll
        for (int j = 0; j < 16; j += 2) {
            uint32_t rr[4];
#pragma unroll
            for (int u = 0; u < 2; u++) {
                const int jj = j + u;
                const float4 mr = *(const float4*)(s_mr + (4 * jj + t) * 4);
                const float2 m2 = make_float2(mr.x, mr.y);
                const float ra = mr.z * sc, rb = mr.w * sc;
                rr[2 * u] = pack_bf16((acc[4 * jj] - m2.x * cs0) * ra, (acc[4 * jj + 1] - m2.y * cs0) * rb);
                rr[2 * u + 1] = pack_bf16((acc[4 * jj + 2] - m2.x * cs1) * ra, (acc[4 * jj + 3] - m2.y * cs1) * rb);
            }
            stmatrix_x4_trans(st_addr + j * 128, rr[0], rr[1], rr[2], rr[3]);
        }
        fence_proxy_async();
        __syncwarp();
        const int head = nt * 4 + hw;
        if (lane == 0) {
            uint8_t* dst;
            uint32_t hstride;
            if (part == 0) { dst = g_q + (size_t)head * 65536 + mt * 2048; hstride = 32768; }
            else { dst = g_kv + (size_t)head * 131072 + (mt >> 1) * 16384 + (part - 1) * 8192 + (mt & 1) * 2048; hstride = 4096; }
            bulk_s2g(dst, stg, 2048);
            bulk_s2g(dst + hstride, stg + 2048, 2048);
            asm volatile("cp.async.bulk.commit_group;" ::: "memory");
        }
        float nmax = 0.f;
#pragma unroll
        for (int i = 0; i < 4; i++) {
            const int tok = lane + 32 * i;
            const uint4 a = *(const uint4*)(sp + (stg - sb) + tok * 16);
            const uint4 b = *(const uint4*)(sp + (stg - sb) + 2048 + tok * 16);
            uint32_t n0 = fma_bf16x2(a.x, a.x, 0u), n1 = fma_bf16x2(b.x, b.x, 0u);
            n0 = fma_bf16x2(a.y, a.y, n0); n1 = fma_bf16x2(b.y, b.y, n1);
            n0 = fma_bf16x2(a.z, a.z, n0); n1 = fma_bf16x2(b.z, b.z, n1);
            n0 = fma_bf16x2(a.w, a.w, n0); n1 = fma_bf16x2(b.w, b.w, n1);
            const float n2 = ((bf_lo(n0) + bf_hi(n0)) + (bf_lo(n1) + bf_hi(n1))) * 1.125f;
            nmax = (n2 > nmax || n2 != n2) ? n2 : nmax;
        }
#pragma unroll
        for (int o = 16; o > 0; o >>= 1) {
            const float v = __shfl_xor_sync(0xffffffffu, nmax, o);
            nmax = (v > nmax || v != v) ? v : nmax;
        }
        if (lane == 0) {
            g_norm[(head * 16 + mt) * 3 + part] = nmax;
            asm volatile("cp.async.bulk.wait_group.read 0;" ::: "memory");
        }
    }
}

#define POLL_NS 50
constexpr int KF_CH_G = 16384, KF_CH_S = 20480, KF_NCH = 8;
constexpr int KF_OFF_WO = KF_NCH * KF_CH_S;
constexpr int KF_OFF_MISC = -2048;
constexpr int KF_SMEM = 2048 + KF_OFF_WO + 65536 + 1024;

__device__ __forceinline__ uint32_t exp2_pair_poly(float t0, float t1, uint32_t c2) {
    const uint32_t w = __byte_perm(__float_as_uint(t0), __float_as_uint(t1), 0x5410);
    uint32_t z;
    asm("lop3.b32 %0, %1, %2, %3, 0xEA;" : "=r"(z) : "r"(w), "r"(0x007F007Fu), "r"(0x3F803F80u));
    uint32_t p = fma_bf16x2(c2, z, 0xbc73bc73u);
    p = fma_bf16x2(p, z, 0x3f2f3f2fu);
    return p + w - z;
}
#define NEA 40
#define NEB 40
#define BIAS_(n) wgmma_bias_n##n
#define BIAS(n) BIAS_(n)
template <int LO, int HI, int NE>
__device__ __forceinline__ void softmax_part(const float (&s)[32], uint32_t (&p)[16], uint32_t c2) {
#pragma unroll
    for (int i = LO; i < HI; i++) {
        if (i < NE / 4) p[i] = exp2_pair_poly(s[2 * i], s[2 * i + 1], c2);
        else p[i] = pack_bf16(ex2f(s[2 * i]), ex2f(s[2 * i + 1]));
    }
}
#define KF_PV(P, OFF)                                                                              \
    _Pragma("unroll") for (int kk = 0; kk < 4; kk++)                                               \
        wgmma_pv_n24(o, P[4 * kk], P[4 * kk + 1], P[4 * kk + 2], P[4 * kk + 3], dv + ((OFF) + kk * 16));

__device__ __forceinline__ uint32_t make_key(float r_bf16, int token) {
    const uint32_t u = __float_as_uint(r_bf16) >> 16;
    const uint32_t o = (u & 0x8000u) ? (~u & 0xFFFFu) : (u | 0x8000u);
    return (o << 16) | (uint32_t)(0xFFFF - token);
}
__device__ __forceinline__ float key_value(uint32_t k) {
    const uint32_t o = k >> 16;
    const uint32_t u = (o & 0x8000u) ? (o & 0x7FFFu) : (~o & 0xFFFFu);
    return __uint_as_float(u << 16);
}
__device__ __forceinline__ int key_token(uint32_t k) { return 0xFFFF - (int)(k & 0xFFFFu); }
__device__ __forceinline__ void warp_top2(uint32_t a, uint32_t b, uint32_t& k1, uint32_t& k2) {
    k1 = __reduce_max_sync(0xffffffffu, a > b ? a : b);
    const uint32_t a2 = (a == k1) ? 0u : a, b2 = (b == k1) ? 0u : b;
    k2 = __reduce_max_sync(0xffffffffu, a2 > b2 ? a2 : b2);
}
__device__ __forceinline__ unsigned int ld_acquire(const unsigned int* p) {
    unsigned int v; asm volatile("ld.acquire.gpu.global.u32 %0, [%1];" : "=r"(v) : "l"(p) : "memory"); return v;
}
__device__ __forceinline__ void red_release_add(unsigned int* p) {
    asm volatile("red.release.gpu.global.add.u32 [%0], 1;" ::"l"(p) : "memory");
}

__global__ void __launch_bounds__(512, 1)
kf_main(const __grid_constant__ CUtensorMap tm_o, const __grid_constant__ CUtensorMap tm_wo,
        const __grid_constant__ CUtensorMap tm_g, const __grid_constant__ CUtensorMap tm_u, const __grid_constant__ CUtensorMap tm_d,
        const __nv_bfloat16* __restrict__ x, const __nv_bfloat16* __restrict__ wo, const __nv_bfloat16* __restrict__ w_r,
        const __nv_bfloat16* __restrict__ w_gate, const __nv_bfloat16* __restrict__ w_up, const __nv_bfloat16* __restrict__ w_down,
        __nv_bfloat16* __restrict__ out) {
    extern __shared__ uint8_t smem_raw[];
    const uint32_t sraw = smem_u32(smem_raw);
    const uint32_t sb = ((sraw + 1023) & ~1023u) + 2048;
    uint8_t* sp = smem_raw + (sb - sraw);
    const uint32_t smisc = sb - 2048u;
    const uint32_t kvbar = smisc;
    const uint32_t wbar = kvbar + 64;
    const uint32_t obar = wbar + 64;
    const uint32_t gbar = obar + 64;
    const uint32_t dbar = gbar + 8;
    unsigned int* s_cnt = (unsigned int*)(sp + KF_OFF_MISC + 208);
    volatile unsigned int* s_order = (volatile unsigned int*)(sp + KF_OFF_MISC + 1056);
    uint32_t* s_key = (uint32_t*)(sp + KF_OFF_MISC + 256);
    float* s_gu = (float*)(sp + KF_OFF_WO + 49152 + 8192 + 4608);
    uint4* s_sel = (uint4*)(sp + KF_OFF_MISC + 1024);
    const int tid = threadIdx.x;
    const int head = blockIdx.x >> 2, quarter = blockIdx.x & 3;
    const int mt = blockIdx.x >> 2, nt = blockIdx.x & 3;
    if (tid == 0) {
        for (int c = 0; c < 26; c++) mbar_init(kvbar + 8 * c, 1);
        for (int c = 0; c < 6; c++) s_cnt[c] = 0;
        fence_barrier_init();
    }
    if (tid < 24) *(uint4*)(sp + KF_OFF_MISC + 1152 + tid * 16) =
        tid < 8 ? make_uint4(0x42FE4380u, 0x00003D80u, 0u, 0u) : (tid < 16 ? make_uint4(0x3F804380u, 0x00003DC0u, 0u, 0u) : make_uint4(0u, 0u, 0u, 0u));
    for (int i = tid; i < KF_NCH * 256; i += 512)
        *(uint4*)(sp + (i >> 8) * KF_CH_S + 16384 + (i & 255) * 16) =
            make_uint4(0x3F803F80u, 0x3F803F80u, 0x3F803F80u, 0x3F803F80u);
    fence_proxy_async();
    __syncthreads();
    pdl_wait();
    const uint8_t* kvsrc = g_kv + (size_t)head * (KF_NCH * KF_CH_G);
    if (tid == 32) {
        mbar_expect_tx(kvbar, KF_CH_G);
        bulk_g2s(sb, kvsrc, KF_CH_G, kvbar);
    }
    const int wg = tid >> 7, warp = (tid >> 5) & 3, lane = tid & 31, g = lane >> 2, t = lane & 3;
    if (tid < 32) {
        const int m16 = lane & 15;
        float kn = g_norm[(head * 16 + m16) * 3 + 1];
        float vn = g_norm[(head * 16 + m16) * 3 + 2];
        float qn = g_norm[(head * 16 + quarter * 4 + (lane & 3)) * 3 + 0];
        const bool bad = !(kn < 1e30f) || !(vn < 1e9f) || !(qn < 1e30f);
#pragma unroll
        for (int o = 8; o > 0; o >>= 1) {
            kn = fmaxf(kn, __shfl_xor_sync(0xffffffffu, kn, o));
            qn = fmaxf(qn, __shfl_xor_sync(0xffffffffu, qn, o));
        }
        const bool ok = __all_sync(0xffffffffu, !bad && (qn * kn <= 9000.f));
        if (lane == 0) s_cnt[4] = ok ? 1u : 0u;
    }
    uint32_t qn2[2][4];
#pragma unroll
    for (int ps = 0; ps < 2; ps++) {
        const uint8_t* qb = g_q + (size_t)head * 65536 + (quarter * 512 + ps * 256 + wg * 64 + warp * 16 + g) * 16 + t * 4;
        qn2[ps][0] = *(const uint32_t*)(qb);
        qn2[ps][1] = *(const uint32_t*)(qb + 128);
        qn2[ps][2] = *(const uint32_t*)(qb + 32768);
        qn2[ps][3] = *(const uint32_t*)(qb + 32768 + 128);
    }

    __syncthreads();
    const bool fast = __all_sync(0xffffffffu, s_cnt[4] != 0u);
    if (tid == 32) {
        for (int c = 1; c < KF_NCH; c++) {
            mbar_expect_tx(kvbar + 8 * c, KF_CH_G);
            bulk_g2s(sb + c * KF_CH_S, kvsrc + c * KF_CH_G, KF_CH_G, kvbar + 8 * c);
        }
        for (int kb = 0; kb < 4; kb++) {
            mbar_expect_tx(wbar + 8 * kb, 16384);
            tma_load_3d(sb + KF_OFF_WO + kb * 16384, &tm_wo, 0, kb * 64, nt * 2, wbar + 8 * kb);
        }
        prefetch_l2((const uint8_t*)wo + blockIdx.x * 4096, 4096);
        prefetch_l2((const uint8_t*)w_gate + blockIdx.x * 14336, 14336);
        prefetch_l2((const uint8_t*)w_up + blockIdx.x * 14336, 14336);
        prefetch_l2((const uint8_t*)w_down + blockIdx.x * 14336, 14336);
    }
    const uint64_t dbias_a = make_desc(smisc + 1152, 0, 0, 0);
    const uint64_t dbias_b = make_desc(smisc + 1280, 128, 0, 0);
    const uint32_t c2reg = 0x3eab3eabu;
    const uint64_t dk0 = make_desc(sb, 4096, 128, 0);
    const uint64_t dv0 = make_desc(sb + 8192, 128, 4096, 0);

#pragma unroll 1
    for (int pass = 0; pass < 2; pass++) {
        const int row0 = quarter * 512 + pass * 256 + wg * 64 + warp * 16 + g;
        uint32_t qa[4];
#pragma unroll
        for (int i = 0; i < 4; i++) qa[i] = pass ? qn2[1][i] : qn2[0][i];
        float o[12];
#pragma unroll
        for (int i = 0; i < 12; i++) o[i] = 0.f;
        fence_regs(o);
#define KF_RELEASE_CHUNK(c)                                                                          \
        if (pass == 1 && (c) >= 1 && (c) <= 4) {                                                     \
            named_sync(4 + wg, 128);            \
            if ((tid & 127) == 0 && atomicAdd(&s_cnt[(c) - 1], 1u) == 3u) {                          \
                mbar_expect_tx(wbar + 8 * (3 + (c)), 16384);                                         \
                tma_load_3d(sb + ((c) - 1) * KF_CH_S, &tm_wo, 0, (3 + (c)) * 64, nt * 2, wbar + 8 * (3 + (c))); \
            }                                                                                        \
        }
        if (fast) {
#pragma unroll 1
            for (int c = 0; c < KF_NCH; c++) {
                const uint64_t dk = dk0 + (uint64_t)(c * (KF_CH_S >> 4));
                const uint64_t dv = dv0 + (uint64_t)(c * (KF_CH_S >> 4));
                float s0[32], s1[32], s2[32], s3[32];
                uint32_t p0[16], p1[16], p2[16], p3[16];
                mbar_wait(kvbar + 8 * c, 0);
                wg_wait<1>();
                wg_fence();
                wgmma_qk_n64(s0, qa[0], qa[1], qa[2], qa[3], dk);
                BIAS(NEA)(s0, dbias_a, dbias_b);
                wg_commit();
                wg_wait<1>();
                KF_RELEASE_CHUNK(c);
                wg_fence();
                wgmma_qk_n64(s1, qa[0], qa[1], qa[2], qa[3], dk + 64);
                BIAS(NEB)(s1, dbias_a, dbias_b);
                wg_commit();
                wg_wait<1>();
                fence_regs(s0);
                softmax_part<0, 16, NEA>(s0, p0, c2reg);
                wg_fence();
                KF_PV(p0, 0);
                wg_commit();
                wg_wait<1>();
                fence_regs(s1);
                softmax_part<0, 8, NEB>(s1, p1, c2reg);
                wg_wait<0>();
                wg_fence();
                wgmma_qk_n64(s2, qa[0], qa[1], qa[2], qa[3], dk + 128);
                BIAS(NEA)(s2, dbias_a, dbias_b);
                wg_commit();
                softmax_part<8, 16, NEB>(s1, p1, c2reg);
                wg_fence();
                KF_PV(p1, 64);
                wg_commit();
                wg_wait<1>();
                fence_regs(s2);
                softmax_part<0, 8, NEA>(s2, p2, c2reg);
                wg_wait<0>();
                wg_fence();
                wgmma_qk_n64(s3, qa[0], qa[1], qa[2], qa[3], dk + 192);
                BIAS(NEB)(s3, dbias_a, dbias_b);
                wg_commit();
                softmax_part<8, 16, NEA>(s2, p2, c2reg);
                wg_fence();
                KF_PV(p2, 128);
                wg_commit();
                wg_wait<1>();
                fence_regs(s3);
                softmax_part<0, 16, NEB>(s3, p3, c2reg);
                wg_fence();
                KF_PV(p3, 192);
                wg_commit();
            }
            wg_wait<0>();
            fence_regs(o);
        } else {
            float m0 = -INFINITY, m1 = -INFINITY;
#pragma unroll 1
            for (int b = 0; b < 32; b++) {
                const int c = b >> 2;
                const uint64_t dk = dk0 + (uint64_t)(c * (KF_CH_S >> 4) + (b & 3) * 64);
                const uint64_t dv = dv0 + (uint64_t)(c * (KF_CH_S >> 4) + (b & 3) * 64);
                float s[32];
                uint32_t p[16];
                mbar_wait(kvbar + 8 * c, 0);
                wg_fence();
                wgmma_qk_n64(s, qa[0], qa[1], qa[2], qa[3], dk);
                wg_commit();
                if ((b & 3) == 0) { KF_RELEASE_CHUNK(c); }
                wg_wait<0>();
                fence_regs(s);
                float x0 = s[0], x1 = s[2];
#pragma unroll
                for (int j = 0; j < 8; j++) {
                    x0 = fmaxf(x0, fmaxf(s[4 * j], s[4 * j + 1]));
                    x1 = fmaxf(x1, fmaxf(s[4 * j + 2], s[4 * j + 3]));
                }
                x0 = fmaxf(x0, __shfl_xor_sync(0xffffffffu, x0, 1));
                x0 = fmaxf(x0, __shfl_xor_sync(0xffffffffu, x0, 2));
                x1 = fmaxf(x1, __shfl_xor_sync(0xffffffffu, x1, 1));
                x1 = fmaxf(x1, __shfl_xor_sync(0xffffffffu, x1, 2));
                const float n0 = fmaxf(m0, x0), n1 = fmaxf(m1, x1);
                const float c0 = ex2f(m0 - n0), c1 = ex2f(m1 - n1);
                m0 = n0; m1 = n1;
#pragma unroll
                for (int j = 0; j < 3; j++) {
                    o[4 * j] *= c0; o[4 * j + 1] *= c0; o[4 * j + 2] *= c1; o[4 * j + 3] *= c1;
                }
#pragma unroll
                for (int j = 0; j < 8; j++) {
                    p[2 * j] = pack_bf16(ex2f(s[4 * j] - n0), ex2f(s[4 * j + 1] - n0));
                    p[2 * j + 1] = pack_bf16(ex2f(s[4 * j + 2] - n1), ex2f(s[4 * j + 3] - n1));
                }
                fence_regs(o);
                wg_fence();
                KF_PV(p, 0);
                wg_commit();
                wg_wait<0>();
                fence_regs(o);
            }
        }
        const float inv0 = 1.f / o[8], inv1 = 1.f / o[10];
        {
            uint32_t v0 = pack_bf16(o[0] * inv0, o[1] * inv0), v1 = pack_bf16(o[4] * inv0, o[5] * inv0);
            uint32_t v2 = pack_bf16(o[2] * inv1, o[3] * inv1), v3 = pack_bf16(o[6] * inv1, o[7] * inv1);
            const bool o1 = t & 1, o2 = t & 2;
            uint32_t s0 = o1 ? v0 : v1, s1 = o1 ? v2 : v3;
            s0 = __shfl_xor_sync(0xffffffffu, s0, 1); s1 = __shfl_xor_sync(0xffffffffu, s1, 1);
            uint32_t a0 = o1 ? s0 : v0, a1 = o1 ? v1 : s0, b0 = o1 ? s1 : v2, b1 = o1 ? v3 : s1;
            uint32_t x0 = o2 ? a0 : b0, x1 = o2 ? a1 : b1;
            x0 = __shfl_xor_sync(0xffffffffu, x0, 2); x1 = __shfl_xor_sync(0xffffffffu, x1, 2);
            uint4 r;
            r.x = o2 ? x0 : a0; r.y = o2 ? x1 : a1; r.z = o2 ? b0 : x0; r.w = o2 ? b1 : x1;
            *(uint4*)(g_o + (size_t)(row0 + (t >> 1) * 8) * DM + head * 16 + (t & 1) * 8) = r;
        }
    }
    if ((tid >> 5) != 10) named_arrive(1, 512);
    named_sync(4 + wg, 128);
    if ((tid & 127) == 0) {
        asm volatile("fence.acq_rel.gpu;" ::: "memory");
        asm volatile("red.relaxed.gpu.global.add.u32 [%0], 1;" ::"l"(&g_oflag[((quarter * 8 + 4 + wg) * 8 + (head >> 2)) * 32]) : "memory");
        asm volatile("red.relaxed.gpu.global.add.u32 [%0], 1;" ::"l"(&g_oflag[((quarter * 8 + wg) * 8 + (head >> 2)) * 32]) : "memory");
    }

    if (wg < 2) {
        const int wi = warp;
        const int r0 = mt * 64 + wi * 16 + g;
        const int cb = nt * 128 + wg * 64;
        uint32_t xr[16], wr[8];
#pragma unroll
        for (int j = 0; j < 8; j++) {
            xr[2 * j] = __ldg((const uint32_t*)(x + (size_t)r0 * DM + cb + 8 * j + 2 * t));
            xr[2 * j + 1] = __ldg((const uint32_t*)(x + (size_t)(r0 + 8) * DM + cb + 8 * j + 2 * t));
            wr[j] = __ldg((const uint32_t*)(w_r + cb + 8 * j + 2 * t));
        }
        float wsum = 0.f;
        {
            const uint4 a = __ldg((const uint4*)(w_r + lane * 16)), b = __ldg((const uint4*)(w_r + lane * 16 + 8));
            const uint32_t w[8] = {a.x, a.y, a.z, a.w, b.x, b.y, b.z, b.w};
#pragma unroll
            for (int i = 0; i < 8; i++) wsum += bf_lo(w[i]) + bf_hi(w[i]);
#pragma unroll
            for (int o = 16; o > 0; o >>= 1) wsum += __shfl_xor_sync(0xffffffffu, wsum, o);
        }
        float acc[32];
#pragma unroll
        for (int i = 0; i < 32; i++) acc[i] = 0.f;
        fence_regs(acc);
#pragma unroll 1
        for (int i = 0; i < 8; i++) {
            mbar_wait(obar + 8 * i, 0);
            const int kb = __shfl_sync(0xffffffffu, (int)s_order[i], 0);
            mbar_wait(wbar + 8 * kb, 0);
            const uint32_t wa = (kb < 4) ? (KF_OFF_WO + kb * 16384) : ((kb - 4) * KF_CH_S);
            const uint64_t da = make_desc(sb + (4 + (kb >> 1)) * KF_CH_S + (kb & 1) * 8192, 16, 1024, 1);
            const uint64_t db = make_desc(sb + wa + wg * 8192, 1024, 1024, 1);
            wg_fence();
#pragma unroll
            for (int k = 0; k < 4; k++) wgmma_k3_n64(acc, da + k * 2, db + k * 128, (i | k) != 0);
            wg_commit();
        }
        wg_wait<0>();
        fence_regs(acc);
        float hv[32];
        uint32_t hp[16];
        float s0 = 0.f, s1 = 0.f, d0 = 0.f, d1 = 0.f;
#pragma unroll
        for (int j = 0; j < 8; j++) {
            const uint32_t a01 = pack_bf16(acc[4 * j], acc[4 * j + 1]), a23 = pack_bf16(acc[4 * j + 2], acc[4 * j + 3]);
            hp[2 * j] = pack_bf16(bf_lo(xr[2 * j]) + bf_lo(a01), bf_hi(xr[2 * j]) + bf_hi(a01));
            hp[2 * j + 1] = pack_bf16(bf_lo(xr[2 * j + 1]) + bf_lo(a23), bf_hi(xr[2 * j + 1]) + bf_hi(a23));
            hv[4 * j] = bf_lo(hp[2 * j]); hv[4 * j + 1] = bf_hi(hp[2 * j]);
            hv[4 * j + 2] = bf_lo(hp[2 * j + 1]); hv[4 * j + 3] = bf_hi(hp[2 * j + 1]);
            const float wl = bf_lo(wr[j]), wh = bf_hi(wr[j]);
            s0 += hv[4 * j] + hv[4 * j + 1];
            s1 += hv[4 * j + 2] + hv[4 * j + 3];
            d0 = fmaf(hv[4 * j], wl, fmaf(hv[4 * j + 1], wh, d0));
            d1 = fmaf(hv[4 * j + 2], wl, fmaf(hv[4 * j + 3], wh, d1));
        }
        float mu0 = s0 * (1.f / 16), mu1 = s1 * (1.f / 16);
        float q0 = 0.f, q1 = 0.f;
#pragma unroll
        for (int j = 0; j < 8; j++) {
            float a = hv[4 * j] - mu0, b = hv[4 * j + 1] - mu0, c = hv[4 * j + 2] - mu1, d = hv[4 * j + 3] - mu1;
            q0 = fmaf(a, a, fmaf(b, b, q0));
            q1 = fmaf(c, c, fmaf(d, d, q1));
        }
#pragma unroll
        for (int o = 1; o < 4; o <<= 1) {
            const float m0 = __shfl_xor_sync(0xffffffffu, mu0, o), m1 = __shfl_xor_sync(0xffffffffu, mu1, o);
            const float e0 = __shfl_xor_sync(0xffffffffu, q0, o), e1 = __shfl_xor_sync(0xffffffffu, q1, o);
            d0 += __shfl_xor_sync(0xffffffffu, d0, o);
            d1 += __shfl_xor_sync(0xffffffffu, d1, o);
            const float f0 = mu0 - m0, f1 = mu1 - m1;
            q0 = q0 + e0 + f0 * f0 * (8.f * o);
            q1 = q1 + e1 + f1 * f1 * (8.f * o);
            mu0 = 0.5f * (mu0 + m0); mu1 = 0.5f * (mu1 + m1);
        }
        float4* part = g_part + (size_t)mt * 512 + wi * 16 + g;
        if (t < 2) {
            float4* dst = part + (nt * 2 + wg) * 64 + t * 8;
            const float a = t ? mu1 : mu0, b = t ? q1 : q0, c = t ? d1 : d0;
            asm volatile("st.relaxed.gpu.global.v4.f32 [%0], {%1, %2, %3, %4};" ::"l"(dst), "f"(a), "f"(b), "f"(c), "f"(1.0f) : "memory");
        }
        const uint32_t stg_off = KF_OFF_WO + (wi >> 1) * 16384 + wg * 8192 + (wi & 1) * 4096;
        const uint32_t stg_o = sb + stg_off, stg_h = stg_o + 2048;
        const int srow = (lane & 7) + ((lane >> 3) & 1) * 8;
        const int sj = lane >> 4;
        named_sync(4 + wg, 128);
#pragma unroll
        for (int j = 0; j < 8; j += 2) {
            const uint32_t off = srow * 128 + (((j + sj) ^ (srow & 7)) << 4);
            stmatrix_x4(stg_h + off, hp[2 * j], hp[2 * j + 1], hp[2 * j + 2], hp[2 * j + 3]);
        }
        __syncwarp();
#pragma unroll
        for (int i = 0; i < 4; i++) {
            const int row = i * 4 + (lane >> 3), ch = lane & 7;
            const uint4 vh = *(const uint4*)(sp + stg_off + 2048 + row * 128 + ((ch ^ (row & 7)) << 4));
            *(uint4*)(g_h + (size_t)(mt * 64 + wi * 16 + row) * DM + cb + ch * 8) = vh;
        }
        named_arrive(8, 288);
        float mean[2], den[2], rr[2];
        {
            float4 v[4];
            int spins = 0;
            while (true) {
#pragma unroll
                for (int i = 0; i < 4; i++) {
                    const float4* p = part + (t + (i & 1) * 4) * 64 + (i >> 1) * 8;
                    asm volatile("ld.relaxed.gpu.global.v4.f32 {%0, %1, %2, %3}, [%4];" : "=f"(v[i].x), "=f"(v[i].y), "=f"(v[i].z), "=f"(v[i].w) : "l"(p) : "memory");
                }
                const bool ok = (v[0].w != 0.f) && (v[1].w != 0.f) && (v[2].w != 0.f) && (v[3].w != 0.f);
                if (__all_sync(0xffffffffu, ok) || ++spins > (1 << 22)) break;
            }
#pragma unroll
            for (int u = 0; u < 2; u++) {
                float mu = v[2 * u].x + v[2 * u + 1].x, m2 = v[2 * u].y + v[2 * u + 1].y, hw = v[2 * u].z + v[2 * u + 1].z;
#pragma unroll
                for (int o = 1; o < 4; o <<= 1) {
                    mu += __shfl_xor_sync(0xffffffffu, mu, o);
                    m2 += __shfl_xor_sync(0xffffffffu, m2, o);
                    hw += __shfl_xor_sync(0xffffffffu, hw, o);
                }
                mu *= 0.125f;
                const float da = v[2 * u].x - mu, db = v[2 * u + 1].x - mu;
                float dd = 64.f * (da * da + db * db);
#pragma unroll
                for (int o = 1; o < 4; o <<= 1) dd += __shfl_xor_sync(0xffffffffu, dd, o);
                m2 += dd;
                mean[u] = rbf(mu);
                den[u] = rbf(sqrtf(rbf(rbf(m2 * (1.f / DM)) + 1e-5f)));
                rr[u] = rbf((hw - mean[u] * wsum) / den[u]);
            }
        }
        named_arrive(3, 512);
        if (nt == 0 && wg == 0) {
            float2* s_st = (float2*)(sp + KF_OFF_WO + 49152);
            if (t == 0) {
                s_key[wi * 16 + g] = make_key(rr[0], r0);
                s_key[wi * 16 + g + 8] = make_key(rr[1], r0 + 8);
                s_st[wi * 16 + g] = make_float2(mean[0], den[0]);
                s_st[wi * 16 + g + 8] = make_float2(mean[1], den[1]);
            }
            named_sync(4, 128);
            if (warp == 0) {
                uint32_t k1, k2;
                warp_top2(s_key[lane], s_key[lane + 32], k1, k2);
                if (lane < 2) {
                    const uint32_t k = lane ? k2 : k1;
                    const float2 st = s_st[key_token(k) & 63];
                    asm volatile("st.relaxed.gpu.global.v4.u32 [%0], {%1, %2, %3, %4};" ::"l"(g_cand + mt * 2 + lane), "r"(k),
                                 "r"(1u), "r"(__float_as_uint(st.x)), "r"(__float_as_uint(st.y)) : "memory");
                }
            }
        }
        const float i0 = 1.f / den[0], i1 = 1.f / den[1];
#pragma unroll
        for (int j = 0; j < 8; j += 2) {
            uint32_t ro[4];
#pragma unroll
            for (int u = 0; u < 2; u++) {
                const int jj = j + u;
                const float a = hv[4 * jj], b = hv[4 * jj + 1], c = hv[4 * jj + 2], d = hv[4 * jj + 3];
                const uint32_t u01 = pack_bf16(a - mean[0], b - mean[0]), u23 = pack_bf16(c - mean[1], d - mean[1]);
                const uint32_t n01 = pack_bf16(bf_lo(u01) * i0, bf_hi(u01) * i0), n23 = pack_bf16(bf_lo(u23) * i1, bf_hi(u23) * i1);
                ro[2 * u] = pack_bf16(a + bf_lo(n01), b + bf_hi(n01));
                ro[2 * u + 1] = pack_bf16(c + bf_lo(n23), d + bf_hi(n23));
            }
            const uint32_t off = srow * 128 + (((j + sj) ^ (srow & 7)) << 4);
            stmatrix_x4(stg_o + off, ro[0], ro[1], ro[2], ro[3]);
        }
        __syncwarp();
#pragma unroll
        for (int i = 0; i < 4; i++) {
            const int row = i * 4 + (lane >> 3), ch = lane & 7;
            const uint4 vo = *(const uint4*)(sp + stg_off + row * 128 + ((ch ^ (row & 7)) << 4));
            *(uint4*)(out + (size_t)(mt * 64 + wi * 16 + row) * DM + cb + ch * 8) = vo;
        }
        named_sync(4 + wg, 128);
        if ((tid & 127) == 0) red_release_add(&g_sflag[mt]);
    } else {
        const bool worker = blockIdx.x < FF / 16;
        const bool downer = blockIdx.x >= 64;
        const int mtid = tid - 256, mwarp = mtid >> 5;
        const int c0 = (blockIdx.x - 64) * 8;
        float* s_x = (float*)(sp + KF_OFF_WO + 49152 + 8192);
        float* s_red = (float*)(sp + KF_OFF_WO + 49152 + 8192 + 4096);
        if (mwarp == 2) {
            named_sync(1, 512);
            uint32_t done = 0;
            int n = 0, spins = 0;
            while (done != 0xFFu && ++spins < (1 << 22)) {
                const bool rdy = lane < 8 && ld_acquire(&g_oflag[(mt * 8 + lane) * 32]) >= 4u;
                uint32_t todo = __ballot_sync(0xffffffffu, rdy) & ~done;
                done |= todo;
                if (todo && lane == 0) {
                    asm volatile("fence.proxy.async.global;" ::: "memory");
                    while (todo) {
                        const int kb = __ffs(todo) - 1;
                        todo &= todo - 1;
                        s_order[n] = kb;
                        mbar_expect_tx(obar + 8 * n, 8192);
                        tma_load_3d(sb + (4 + (kb >> 1)) * KF_CH_S + (kb & 1) * 8192, &tm_o, 0, mt * 64, kb, obar + 8 * n);
                        n++;
                    }
                }
                n = __shfl_sync(0xffffffffu, n, 0);
                if (done != 0xFFu) __nanosleep(POLL_NS);
            }
            if (lane == 0 && worker) {
                mbar_expect_tx(gbar, 32768);
                for (int i = 0; i < 4; i++) {
                    tma_load_2d(sb + i * KF_CH_S + 16384, &tm_g, blockIdx.x * 16, i * 128, gbar);
                    tma_load_2d(sb + (4 + i) * KF_CH_S + 16384, &tm_u, blockIdx.x * 16, i * 128, gbar);
                }
            }
        }
        if (mwarp == 1) {
            named_sync(8, 288);
            if (lane == 0) {
                red_release_add(&g_hflag[mt]);
                if (downer) {
                    mbar_expect_tx(dbar, 7 * 4096);
                    for (int i = 0; i < 7; i++) tma_load_2d(sb + (4 + (i >> 2)) * KF_CH_S + (i & 3) * 4096, &tm_d, c0, i * 256, dbar);
                }
            }
            __syncwarp();
        }
        named_sync(3, 512);
        if (mwarp == 0) {
            uint4 ca, cb4;
            int spins = 0;
            while (true) {
                asm volatile("ld.relaxed.gpu.global.v4.u32 {%0, %1, %2, %3}, [%4];" : "=r"(ca.x), "=r"(ca.y), "=r"(ca.z), "=r"(ca.w) : "l"(g_cand + 2 * lane) : "memory");
                asm volatile("ld.relaxed.gpu.global.v4.u32 {%0, %1, %2, %3}, [%4];" : "=r"(cb4.x), "=r"(cb4.y), "=r"(cb4.z), "=r"(cb4.w) : "l"(g_cand + 2 * lane + 1) : "memory");
                const unsigned int hf = ld_acquire(&g_hflag[lane]);
                const bool ok = ca.y != 0 && cb4.y != 0 && hf >= 4u;
                if (__all_sync(0xffffffffu, ok) || ++spins > (1 << 22)) break;
            }
            uint32_t k1, k2;
            warp_top2(ca.x, cb4.x, k1, k2);
            if (ca.x == k1) s_sel[0] = ca;
            if (cb4.x == k1) s_sel[0] = cb4;
            if (ca.x == k2) s_sel[1] = ca;
            if (cb4.x == k2) s_sel[1] = cb4;
        }
        named_sync(2, 256);
        int idx[2];
        float mean[2], inv[2], rv[2];
#pragma unroll
        for (int u = 0; u < 2; u++) {
            const uint4 c = s_sel[u];
            idx[u] = key_token(c.x);
            rv[u] = key_value(c.x);
            mean[u] = __uint_as_float(c.z);
            inv[u] = 1.f / __uint_as_float(c.w);
        }
        float hfin = 0.f;
        if (downer && mtid < 16) hfin = __bfloat162float(__ldcg((const __nv_bfloat16*)(g_h + (size_t)((mtid >> 3) ? idx[1] : idx[0]) * DM + c0 + (mtid & 7))));
        if (worker) {
            {
                const uint32_t h0 = __ldcg((const uint32_t*)(g_h + (size_t)idx[0] * DM + 2 * mtid));
                const uint32_t h1 = __ldcg((const uint32_t*)(g_h + (size_t)idx[1] * DM + 2 * mtid));
                const uint32_t u0 = pack_bf16(bf_lo(h0) - mean[0], bf_hi(h0) - mean[0]), u1 = pack_bf16(bf_lo(h1) - mean[1], bf_hi(h1) - mean[1]);
                const uint32_t n0 = pack_bf16(bf_lo(u0) * inv[0], bf_hi(u0) * inv[0]), n1 = pack_bf16(bf_lo(u1) * inv[1], bf_hi(u1) * inv[1]);
                *(float4*)(s_x + 4 * mtid) = make_float4(bf_lo(n0), bf_lo(n1), bf_hi(n0), bf_hi(n1));
            }
            mbar_wait(gbar, 0);
            named_sync(2, 256);
            float acc[16];
#pragma unroll
            for (int i = 0; i < 16; i++) acc[i] = 0.f;
            const uint8_t* wbase = sp + ((mwarp >> 2) * 4 + (mwarp & 3)) * KF_CH_S + 16384 + lane * 16;
            const float* xb = s_x + 2 * (128 * (mwarp & 3) + (lane >> 1));
#pragma unroll
            for (int j = 0; j < 8; j++) {
                const uint4 w = *(const uint4*)(wbase + j * 512);
                const float2 xx = *(const float2*)(xb + 32 * j);
                const uint32_t ww[4] = {w.x, w.y, w.z, w.w};
#pragma unroll
                for (int q = 0; q < 4; q++) {
                    const float wl = bf_lo(ww[q]), wh = bf_hi(ww[q]);
                    acc[2 * q] = fmaf(xx.x, wl, acc[2 * q]); acc[2 * q + 1] = fmaf(xx.x, wh, acc[2 * q + 1]);
                    acc[8 + 2 * q] = fmaf(xx.y, wl, acc[8 + 2 * q]); acc[8 + 2 * q + 1] = fmaf(xx.y, wh, acc[8 + 2 * q + 1]);
                }
            }
#define KF_STEP(O, N)                                                          \
            {                                                                  \
                const bool up = (lane & (O)) != 0;                             \
                _Pragma("unroll") for (int i = 0; i < (N); i++) {              \
                    const float send = up ? acc[i] : acc[i + (N)];             \
                    const float keep = up ? acc[i + (N)] : acc[i];             \
                    acc[i] = keep + __shfl_xor_sync(0xffffffffu, send, (O));   \
                }                                                              \
            }
            KF_STEP(16, 8) KF_STEP(8, 4) KF_STEP(4, 2) KF_STEP(2, 1)
            {
                const int v = ((lane & 16) ? 8 : 0) + ((lane & 8) ? 4 : 0) + ((lane & 4) ? 2 : 0) + ((lane & 2) ? 1 : 0);
                s_gu[mwarp * 32 + (v >> 3) * 16 + (lane & 1) * 8 + (v & 7)] = acc[0];
            }
            named_sync(2, 256);
            if (mtid < 16) {
                uint32_t a2 = 0;
#pragma unroll
                for (int u = 0; u < 2; u++) {
                    const float* pg = s_gu + u * 16 + mtid;
                    const float gb = rbf((pg[0] + pg[32]) + (pg[64] + pg[96]));
                    const float ub = rbf((pg[128] + pg[160]) + (pg[192] + pg[224]));
                    const float sg = rbf(gb / (1.f + __expf(-gb)));
                    const float a = sg * ub;
                    uint32_t ab = (uint32_t)__bfloat16_as_ushort(__float2bfloat16_rn(a));
                    if (ab == 0xFFFFu) ab = 0x7FFFu;
                    a2 |= ab << (16 * u);
                }
                asm volatile("st.relaxed.gpu.global.u32 [%0], %1;" ::"l"(g_act + blockIdx.x * 16 + mtid), "r"(a2) : "memory");
            }
        }
        if (downer) {
            uint32_t av[7];
            {
                int spins = 0;
                while (true) {
                    bool ok = true;
#pragma unroll
                    for (int j = 0; j < 7; j++) {
                        asm volatile("ld.relaxed.gpu.global.u32 %0, [%1];" : "=r"(av[j]) : "l"(g_act + mtid + 256 * j) : "memory");
                        ok = ok && ((av[j] & 0xFFFFu) != 0xFFFFu) && ((av[j] >> 16) != 0xFFFFu);
                    }
                    if (mtid < 2) ok = ok && (ld_acquire(&g_sflag[(mtid ? idx[1] : idx[0]) >> 6]) >= 8u);
                    if (__all_sync(0xffffffffu, ok) || ++spins > (1 << 20)) break;
                    __nanosleep(20);
                }
            }
            mbar_wait(dbar, 0);
            float acc[16];
#pragma unroll
            for (int i = 0; i < 16; i++) acc[i] = 0.f;
#pragma unroll
            for (int j = 0; j < 7; j++) {
                const uint4 w = *(const uint4*)(sp + (4 + (j >> 2)) * KF_CH_S + (j & 3) * 4096 + mtid * 16);
                const float a0 = bf_lo(av[j]), a1 = bf_hi(av[j]);
                const uint32_t ww[4] = {w.x, w.y, w.z, w.w};
#pragma unroll
                for (int q = 0; q < 4; q++) {
                    const float wl = bf_lo(ww[q]), wh = bf_hi(ww[q]);
                    acc[2 * q] = fmaf(a0, wl, acc[2 * q]); acc[2 * q + 1] = fmaf(a0, wh, acc[2 * q + 1]);
                    acc[8 + 2 * q] = fmaf(a1, wl, acc[8 + 2 * q]); acc[8 + 2 * q + 1] = fmaf(a1, wh, acc[8 + 2 * q + 1]);
                }
            }
            KF_STEP(16, 8) KF_STEP(8, 4) KF_STEP(4, 2) KF_STEP(2, 1)
            acc[0] += __shfl_xor_sync(0xffffffffu, acc[0], 1);
            if ((lane & 1) == 0) {
                const int v = ((lane & 16) ? 8 : 0) + ((lane & 8) ? 4 : 0) + ((lane & 4) ? 2 : 0) + ((lane & 2) ? 1 : 0);
                s_red[mwarp * 16 + v] = acc[0];
            }
            named_sync(2, 256);
            if (mtid < 16) {
                const int u = mtid >> 3;
                float y = 0.f;
#pragma unroll
                for (int w = 0; w < 8; w++) y += s_red[w * 16 + mtid];
                const float sig = rbf(1.f / (1.f + __expf(-(u ? rv[1] : rv[0]))));
                const float xn = rbf(rbf(hfin - (u ? mean[1] : mean[0])) * (u ? inv[1] : inv[0]));
                const float ov = hfin + rbf(xn + rbf(rbf(y) * sig));
                out[(size_t)(u ? idx[1] : idx[0]) * DM + c0 + (mtid & 7)] = __float2bfloat16_rn(ov);
            }
            if (blockIdx.x == gridDim.x - 1 && mtid == 0) g_epoch = g_epoch + 1u;
        }
    }
}

typedef CUresult (*PFN_encodeTiled)(CUtensorMap*, CUtensorMapDataType, cuuint32_t, void*, const cuuint64_t*, const cuuint64_t*,
                                    const cuuint32_t*, const cuuint32_t*, CUtensorMapInterleave, CUtensorMapSwizzle,
                                    CUtensorMapL2promotion, CUtensorMapFloatOOBfill);

void make_map(PFN_encodeTiled enc, CUtensorMap* m, const void* ptr, uint64_t cols, uint64_t rows, uint32_t bcols, uint32_t brows) {
    cuuint64_t dims[2] = {cols, rows};
    cuuint64_t strides[1] = {cols * 2};
    cuuint32_t box[2] = {bcols, brows};
    cuuint32_t es[2] = {1, 1};
    enc(m, CU_TENSOR_MAP_DATA_TYPE_BFLOAT16, 2, const_cast<void*>(ptr), dims, strides, box, es, CU_TENSOR_MAP_INTERLEAVE_NONE,
        CU_TENSOR_MAP_SWIZZLE_128B, CU_TENSOR_MAP_L2_PROMOTION_L2_256B, CU_TENSOR_MAP_FLOAT_OOB_FILL_NONE);
}

void make_map3(PFN_encodeTiled enc, CUtensorMap* m, const void* ptr, uint64_t d0, uint64_t rows, uint64_t d2, uint64_t row_stride_bytes,
               uint64_t d2_stride_bytes, uint32_t b0, uint32_t b1, uint32_t b2) {
    cuuint64_t dims[3] = {d0, rows, d2};
    cuuint64_t strides[2] = {row_stride_bytes, d2_stride_bytes};
    cuuint32_t box[3] = {b0, b1, b2};
    cuuint32_t es[3] = {1, 1, 1};
    enc(m, CU_TENSOR_MAP_DATA_TYPE_BFLOAT16, 3, const_cast<void*>(ptr), dims, strides, box, es, CU_TENSOR_MAP_INTERLEAVE_NONE,
        CU_TENSOR_MAP_SWIZZLE_128B, CU_TENSOR_MAP_L2_PROMOTION_L2_256B, CU_TENSOR_MAP_FLOAT_OOB_FILL_NONE);
}

void make_map_plain(PFN_encodeTiled enc, CUtensorMap* m, const void* ptr, uint64_t cols, uint64_t rows, uint32_t bcols, uint32_t brows) {
    cuuint64_t dims[2] = {cols, rows};
    cuuint64_t strides[1] = {cols * 2};
    cuuint32_t box[2] = {bcols, brows};
    cuuint32_t es[2] = {1, 1};
    enc(m, CU_TENSOR_MAP_DATA_TYPE_BFLOAT16, 2, const_cast<void*>(ptr), dims, strides, box, es, CU_TENSOR_MAP_INTERLEAVE_NONE,
        CU_TENSOR_MAP_SWIZZLE_NONE, CU_TENSOR_MAP_L2_PROMOTION_NONE, CU_TENSOR_MAP_FLOAT_OOB_FILL_NONE);
}

template <typename... KArgs, typename... Args>
void launch(void (*kern)(KArgs...), int grid, int block, int smem, bool pdl, Args... args) {
    cudaLaunchConfig_t cfg = {};
    cfg.gridDim = dim3(grid);
    cfg.blockDim = dim3(block);
    cfg.dynamicSmemBytes = smem;
    cfg.stream = cudaStreamPerThread;
    cudaLaunchAttribute at[1];
    at[0].id = cudaLaunchAttributeProgrammaticStreamSerialization;
    at[0].val.programmaticStreamSerializationAllowed = 1;
    cfg.attrs = at;
    cfg.numAttrs = pdl ? 1 : 0;
    cudaLaunchKernelEx(&cfg, kern, KArgs(args)...);
}

}

extern "C" void kernel_launch(void* const* d_in, const int* in_sizes, int n_in, void* d_out, int out_size) {
    const __nv_bfloat16* x = (const __nv_bfloat16*)d_in[0];
    const __nv_bfloat16* wqkv = (const __nv_bfloat16*)d_in[1];
    const __nv_bfloat16* wo = (const __nv_bfloat16*)d_in[2];
    const __nv_bfloat16* w_r = (const __nv_bfloat16*)d_in[4];
    const __nv_bfloat16* w_gate = (const __nv_bfloat16*)d_in[5];
    const __nv_bfloat16* w_up = (const __nv_bfloat16*)d_in[6];
    const __nv_bfloat16* w_down = (const __nv_bfloat16*)d_in[7];
    __nv_bfloat16* out = (__nv_bfloat16*)d_out;

    static PFN_encodeTiled enc = nullptr;
    static void* g_o_ptr = nullptr;
    if (!enc) {
        cudaDriverEntryPointQueryResult qres;
        void* fn = nullptr;
        cudaGetDriverEntryPoint("cuTensorMapEncodeTiled", &fn, cudaEnableDefault, &qres);
        enc = (PFN_encodeTiled)fn;
        cudaGetSymbolAddress(&g_o_ptr, g_o);
        cudaFuncSetAttribute(k1_qkv, cudaFuncAttributeMaxDynamicSharedMemorySize, K1_SMEM);
        cudaFuncSetAttribute(kf_main, cudaFuncAttributeMaxDynamicSharedMemorySize, KF_SMEM);
    }
    CUtensorMap tm_x, tm_w, tm_o, tm_wo, tm_g, tm_u, tm_d;
    make_map_plain(enc, &tm_d, w_down, DM, FF, 8, 256);
    make_map_plain(enc, &tm_g, w_gate, FF, DM, 16, 128);
    make_map_plain(enc, &tm_u, w_up, FF, DM, 16, 128);
    make_map(enc, &tm_x, x, DM, SEQ, 64, 128);
    make_map3(enc, &tm_w, wqkv, DM, DM, 3, 3 * DM * 2, DM * 2, 64, 64, 3);
    make_map3(enc, &tm_o, g_o_ptr, 64, SEQ, 8, DM * 2, 128, 64, 64, 1);
    make_map3(enc, &tm_wo, wo, 64, DM, 8, DM * 2, 128, 64, 64, 2);

    const bool pdl = true;
    launch(k1_qkv, 128, 544, K1_SMEM, false, tm_x, tm_w, x);
    launch(kf_main, 128, 512, KF_SMEM, pdl, tm_o, tm_wo, tm_g, tm_u, tm_d, x, wo, w_r, w_gate, w_up, w_down, out);
}
```

```cpp
#include <cuda_runtime.h>
#include <cuda_bf16.h>
#include <cuda.h>
#include <stdint.h>

namespace {

constexpr int SEQ = 2048, DM = 512, NH = 32, FF = 1792;

__device__ __align__(1024) uint8_t g_q[NH * 2 * SEQ * 16];
__device__ __align__(1024) uint8_t g_kv[NH * 8 * 16384];
__device__ float g_norm[16 * NH * 3];
__device__ __align__(1024) __nv_bfloat16 g_o[SEQ * DM];
__device__ __align__(1024) __nv_bfloat16 g_h[SEQ * DM];
__device__ __align__(16) uint4 g_cand[64];
__device__ unsigned int g_oflag[32 * 8 * 32];
__device__ unsigned int g_hflag[32];
__device__ unsigned int g_sflag[32];
__device__ unsigned int g_act[FF];
__device__ unsigned int g_epoch;
__device__ __align__(16) float4 g_ln1[SEQ];
__device__ __align__(16) float4 g_part[32 * 8 * 64];

__device__ __forceinline__ uint32_t smem_u32(const void* p) { return (uint32_t)__cvta_generic_to_shared(p); }
__device__ __forceinline__ void wg_fence() { asm volatile("wgmma.fence.sync.aligned;" ::: "memory"); }
__device__ __forceinline__ void wg_commit() { asm volatile("wgmma.commit_group.sync.aligned;" ::: "memory"); }
template <int N> __device__ __forceinline__ void wg_wait() { asm volatile("wgmma.wait_group.sync.aligned %0;" ::"n"(N) : "memory"); }
template <int N> __device__ __forceinline__ void fence_regs(float (&r)[N]) {
#pragma unroll
    for (int i = 0; i < N; i++) asm volatile("" : "+f"(r[i])::"memory");
}
__device__ __forceinline__ uint64_t make_desc(uint32_t addr, uint32_t lbo, uint32_t sbo, uint32_t swz) {
    uint64_t d = 0;
    d |= (uint64_t)((addr & 0x3FFFF) >> 4);
    d |= (uint64_t)((lbo & 0x3FFFF) >> 4) << 16;
    d |= (uint64_t)((sbo & 0x3FFFF) >> 4) << 32;
    d |= (uint64_t)swz << 62;
    return d;
}
__device__ __forceinline__ void mbar_init(uint32_t bar, uint32_t cnt) {
    asm volatile("mbarrier.init.shared::cta.b64 [%0], %1;" ::"r"(bar), "r"(cnt) : "memory");
}
__device__ __forceinline__ void mbar_expect_tx(uint32_t bar, uint32_t bytes) {
    asm volatile("mbarrier.arrive.expect_tx.shared::cta.b64 _, [%0], %1;" ::"r"(bar), "r"(bytes) : "memory");
}
__device__ __forceinline__ void mbar_arrive(uint32_t bar) {
    asm volatile("mbarrier.arrive.shared::cta.b64 _, [%0];" ::"r"(bar) : "memory");
}
__device__ __forceinline__ void mbar_wait(uint32_t bar, uint32_t parity) {
    asm volatile(
        "{\n.reg .pred p;\nWAIT_%=:\n"
        "mbarrier.try_wait.parity.shared::cta.b64 p, [%0], %1;\n"
        "@p bra DONE_%=;\nbra WAIT_%=;\nDONE_%=:\n}\n" ::"r"(bar), "r"(parity) : "memory");
}
__device__ __forceinline__ void bulk_g2s(uint32_t dst, const void* src, uint32_t bytes, uint32_t bar) {
    asm volatile("cp.async.bulk.shared::cluster.global.mbarrier::complete_tx::bytes [%0], [%1], %2, [%3];" ::"r"(dst),
                 "l"(src), "r"(bytes), "r"(bar) : "memory");
}
__device__ __forceinline__ void bulk_s2g(void* dst, uint32_t src, uint32_t bytes) {
    asm volatile("cp.async.bulk.global.shared::cta.bulk_group [%0], [%1], %2;" ::"l"(dst), "r"(src), "r"(bytes) : "memory");
}
__device__ __forceinline__ void tma_load_2d(uint32_t dst, const CUtensorMap* tm, int c0, int c1, uint32_t bar) {
    asm volatile("cp.async.bulk.tensor.2d.shared::cluster.global.mbarrier::complete_tx::bytes [%0], [%1, {%3, %4}], [%2];" ::"r"(dst),
                 "l"(tm), "r"(bar), "r"(c0), "r"(c1) : "memory");
}
__device__ __forceinline__ void tma_load_3d(uint32_t dst, const CUtensorMap* tm, int c0, int c1, int c2, uint32_t bar) {
    asm volatile("cp.async.bulk.tensor.3d.shared::cluster.global.mbarrier::complete_tx::bytes [%0], [%1, {%3, %4, %5}], [%2];" ::"r"(dst),
                 "l"(tm), "r"(bar), "r"(c0), "r"(c1), "r"(c2) : "memory");
}
__device__ __forceinline__ void prefetch_l2(const void* p, uint32_t bytes) {
    asm volatile("cp.async.bulk.prefetch.L2.global [%0], %1;" ::"l"(p), "r"(bytes) : "memory");
}
__device__ __forceinline__ void fence_proxy_async() { asm volatile("fence.proxy.async.shared::cta;" ::: "memory"); }
__device__ __forceinline__ void fence_barrier_init() { asm volatile("fence.mbarrier_init.release.cluster;" ::: "memory"); }
__device__ __forceinline__ void pdl_launch() { asm volatile("griddepcontrol.launch_dependents;" ::: "memory"); }
__device__ __forceinline__ void pdl_wait() { asm volatile("griddepcontrol.wait;" ::: "memory"); }
__device__ __forceinline__ void named_sync(int id, int n) { asm volatile("bar.sync %0, %1;" ::"r"(id), "r"(n) : "memory"); }
__device__ __forceinline__ void named_arrive(int id, int n) { asm volatile("bar.arrive %0, %1;" ::"r"(id), "r"(n) : "memory"); }

__device__ __forceinline__ float ex2f(float x) { float y; asm("ex2.approx.ftz.f32 %0, %1;" : "=f"(y) : "f"(x)); return y; }
__device__ __forceinline__ uint32_t pack_bf16(float lo, float hi) {
    uint32_t r; asm("cvt.rn.bf16x2.f32 %0, %1, %2;" : "=r"(r) : "f"(hi), "f"(lo)); return r;
}
__device__ __forceinline__ float bf_lo(uint32_t v) { return __uint_as_float(v << 16); }
__device__ __forceinline__ float bf_hi(uint32_t v) { return __uint_as_float(v & 0xFFFF0000u); }
__device__ __forceinline__ float rbf(float x) { return __bfloat162float(__float2bfloat16_rn(x)); }
__device__ __forceinline__ uint32_t fma_bf16x2(uint32_t a, uint32_t b, uint32_t c) {
    uint32_t r; asm("fma.rn.bf16x2 %0, %1, %2, %3;" : "=r"(r) : "r"(a), "r"(b), "r"(c)); return r;
}
__device__ __forceinline__ void stmatrix_x4(uint32_t addr, uint32_t r0, uint32_t r1, uint32_t r2, uint32_t r3) {
    asm volatile("stmatrix.sync.aligned.m8n8.x4.shared.b16 [%0], {%1, %2, %3, %4};" ::"r"(addr), "r"(r0), "r"(r1), "r"(r2), "r"(r3) : "memory");
}
__device__ __forceinline__ void stmatrix_x4_trans(uint32_t addr, uint32_t r0, uint32_t r1, uint32_t r2, uint32_t r3) {
    asm volatile("stmatrix.sync.aligned.m8n8.x4.trans.shared.b16 [%0], {%1, %2, %3, %4};" ::"r"(addr), "r"(r0), "r"(r1), "r"(r2), "r"(r3) : "memory");
}

__device__ __forceinline__ void wgmma_k1_n136(float (&d)[68], uint64_t desca, uint64_t descb, int scale_d) {
  asm volatile("{\n.reg .pred p;\nsetp.ne.b32 p, %70, 0;\n"
    "wgmma.mma_async.sync.aligned.m64n136k16.f32.bf16.bf16 "
    "{%0, %1, %2, %3, %4, %5, %6, %7, %8, %9, %10, %11, %12, %13, %14, %15, %16, %17, %18, %19, %20, %21, %22, %23, %24, %25, %26, %27, %28, %29, %30, %31, %32, %33, %34, %35, %36, %37, %38, %39, %40, %41, %42, %43, %44, %45, %46, %47, %48, %49, %50, %51, %52, %53, %54, %55, %56, %57, %58, %59, %60, %61, %62, %63, %64, %65, %66, %67}, "
    "%68, %69, p, 1, 1, 1, 0;\n}\n"
    : "+f"(d[0]), "+f"(d[1]), "+f"(d[2]), "+f"(d[3]), "+f"(d[4]), "+f"(d[5]), "+f"(d[6]), "+f"(d[7]), "+f"(d[8]), "+f"(d[9]), "+f"(d[10]), "+f"(d[11]), "+f"(d[12]), "+f"(d[13]), "+f"(d[14]), "+f"(d[15]), "+f"(d[16]), "+f"(d[17]), "+f"(d[18]), "+f"(d[19]), "+f"(d[20]), "+f"(d[21]), "+f"(d[22]), "+f"(d[23]), "+f"(d[24]), "+f"(d[25]), "+f"(d[26]), "+f"(d[27]), "+f"(d[28]), "+f"(d[29]), "+f"(d[30]), "+f"(d[31]), "+f"(d[32]), "+f"(d[33]), "+f"(d[34]), "+f"(d[35]), "+f"(d[36]), "+f"(d[37]), "+f"(d[38]), "+f"(d[39]), "+f"(d[40]), "+f"(d[41]), "+f"(d[42]), "+f"(d[43]), "+f"(d[44]), "+f"(d[45]), "+f"(d[46]), "+f"(d[47]), "+f"(d[48]), "+f"(d[49]), "+f"(d[50]), "+f"(d[51]), "+f"(d[52]), "+f"(d[53]), "+f"(d[54]), "+f"(d[55]), "+f"(d[56]), "+f"(d[57]), "+f"(d[58]), "+f"(d[59]), "+f"(d[60]), "+f"(d[61]), "+f"(d[62]), "+f"(d[63]), "+f"(d[64]), "+f"(d[65]), "+f"(d[66]), "+f"(d[67])
    : "l"(desca), "l"(descb), "r"(scale_d));
}
__device__ __forceinline__ void wgmma_qk_n64(float (&d)[32], uint32_t a0, uint32_t a1, uint32_t a2, uint32_t a3, uint64_t descb) {
  asm volatile("{\n.reg .pred p;\nsetp.ne.b32 p, 0, 0;\n"
    "wgmma.mma_async.sync.aligned.m64n64k16.f32.bf16.bf16 "
    "{%0, %1, %2, %3, %4, %5, %6, %7, %8, %9, %10, %11, %12, %13, %14, %15, %16, %17, %18, %19, %20, %21, %22, %23, %24, %25, %26, %27, %28, %29, %30, %31}, "
    "{%32, %33, %34, %35}, %36, p, 1, 1, 0;\n}\n"
    : "=f"(d[0]), "=f"(d[1]), "=f"(d[2]), "=f"(d[3]), "=f"(d[4]), "=f"(d[5]), "=f"(d[6]), "=f"(d[7]), "=f"(d[8]), "=f"(d[9]), "=f"(d[10]), "=f"(d[11]), "=f"(d[12]), "=f"(d[13]), "=f"(d[14]), "=f"(d[15]), "=f"(d[16]), "=f"(d[17]), "=f"(d[18]), "=f"(d[19]), "=f"(d[20]), "=f"(d[21]), "=f"(d[22]), "=f"(d[23]), "=f"(d[24]), "=f"(d[25]), "=f"(d[26]), "=f"(d[27]), "=f"(d[28]), "=f"(d[29]), "=f"(d[30]), "=f"(d[31])
    : "r"(a0), "r"(a1), "r"(a2), "r"(a3), "l"(descb));
}
__device__ __forceinline__ void wgmma_pv_n24(float (&d)[12], uint32_t a0, uint32_t a1, uint32_t a2, uint32_t a3, uint64_t descb) {
  asm volatile("{\n.reg .pred p;\nsetp.eq.b32 p, 0, 0;\n"
    "wgmma.mma_async.sync.aligned.m64n24k16.f32.bf16.bf16 "
    "{%0, %1, %2, %3, %4, %5, %6, %7, %8, %9, %10, %11}, "
    "{%12, %13, %14, %15}, %16, p, 1, 1, 1;\n}\n"
    : "+f"(d[0]), "+f"(d[1]), "+f"(d[2]), "+f"(d[3]), "+f"(d[4]), "+f"(d[5]), "+f"(d[6]), "+f"(d[7]), "+f"(d[8]), "+f"(d[9]), "+f"(d[10]), "+f"(d[11])
    : "r"(a0), "r"(a1), "r"(a2), "r"(a3), "l"(descb));
}
__device__ __forceinline__ void wgmma_k3_n64(float (&d)[32], uint64_t desca, uint64_t descb, int scale_d) {
  asm volatile("{\n.reg .pred p;\nsetp.ne.b32 p, %34, 0;\n"
    "wgmma.mma_async.sync.aligned.m64n64k16.f32.bf16.bf16 "
    "{%0, %1, %2, %3, %4, %5, %6, %7, %8, %9, %10, %11, %12, %13, %14, %15, %16, %17, %18, %19, %20, %21, %22, %23, %24, %25, %26, %27, %28, %29, %30, %31}, "
    "%32, %33, p, 1, 1, 0, 1;\n}\n"
    : "+f"(d[0]), "+f"(d[1]), "+f"(d[2]), "+f"(d[3]), "+f"(d[4]), "+f"(d[5]), "+f"(d[6]), "+f"(d[7]), "+f"(d[8]), "+f"(d[9]), "+f"(d[10]), "+f"(d[11]), "+f"(d[12]), "+f"(d[13]), "+f"(d[14]), "+f"(d[15]), "+f"(d[16]), "+f"(d[17]), "+f"(d[18]), "+f"(d[19]), "+f"(d[20]), "+f"(d[21]), "+f"(d[22]), "+f"(d[23]), "+f"(d[24]), "+f"(d[25]), "+f"(d[26]), "+f"(d[27]), "+f"(d[28]), "+f"(d[29]), "+f"(d[30]), "+f"(d[31])
    : "l"(desca), "l"(descb), "r"(scale_d));
}
__device__ __forceinline__ void wgmma_bias_n40(float (&d)[32], uint64_t desca, uint64_t descb) {
  asm volatile("{\n.reg .pred p;\nsetp.eq.b32 p, 0, 0;\n"
    "wgmma.mma_async.sync.aligned.m64n40k16.f32.bf16.bf16 "
    "{%0, %1, %2, %3, %4, %5, %6, %7, %8, %9, %10, %11, %12, %13, %14, %15, %16, %17, %18, %19}, "
    "%20, %21, p, 1, 1, 0, 0;\n}\n"
    : "+f"(d[0]), "+f"(d[1]), "+f"(d[2]), "+f"(d[3]), "+f"(d[4]), "+f"(d[5]), "+f"(d[6]), "+f"(d[7]), "+f"(d[8]), "+f"(d[9]), "+f"(d[10]), "+f"(d[11]), "+f"(d[12]), "+f"(d[13]), "+f"(d[14]), "+f"(d[15]), "+f"(d[16]), "+f"(d[17]), "+f"(d[18]), "+f"(d[19])
    : "l"(desca), "l"(descb));
}

constexpr int K1_XS = 17408;
constexpr int K1_WS = 24576;
constexpr int K1_ST = K1_XS + K1_WS;
constexpr int K1_NST = 5;
constexpr int K1_OFF_MISC = K1_NST * K1_ST;
constexpr int K1_SMEM = K1_OFF_MISC + 2048 + 1024;
constexpr float QSCALE = 0.25f * 1.4426950408889634f;

__global__ void __launch_bounds__(544, 1)
k1_qkv(const __grid_constant__ CUtensorMap tm_x, const __grid_constant__ CUtensorMap tm_w, const __nv_bfloat16* __restrict__ x) {
    extern __shared__ uint8_t smem_raw[];
    const uint32_t sraw = smem_u32(smem_raw);
    const uint32_t sb = (sraw + 1023) & ~1023u;
    uint8_t* sp = smem_raw + (sb - sraw);
    const uint32_t full = sb + K1_OFF_MISC;
    const uint32_t empty = full + 64;
    float* s_mr = (float*)(sp + K1_OFF_MISC + 256);

    const int tid = threadIdx.x, warp = tid >> 5, lane = tid & 31;
    const int mt = blockIdx.x >> 3, nt = blockIdx.x & 7;
    pdl_launch();
    if (tid == 512) {
        for (int i = 0; i < K1_NST; i++) { mbar_init(full + 8 * i, 1); mbar_init(empty + 8 * i, 3); }
        fence_barrier_init();
        for (int kb = 0; kb < K1_NST; kb++) {
            mbar_expect_tx(full + 8 * kb, 16384 + K1_WS);
            tma_load_2d(sb + kb * K1_ST, &tm_x, kb * 64, mt * 128, full + 8 * kb);
            tma_load_3d(sb + kb * K1_ST + K1_XS, &tm_w, nt * 64, kb * 64, 0, full + 8 * kb);
        }
    }
    if (tid < K1_NST * 64) {
        *(uint4*)(sp + (tid >> 6) * K1_ST + 16384 + (tid & 63) * 16) =
            make_uint4(0x3F803F80u, 0x3F803F80u, 0x3F803F80u, 0x3F803F80u);
    }
    fence_proxy_async();
    __syncthreads();

    if (warp == 16) {
        if (lane == 0) {
            for (int kb = K1_NST; kb < 8; kb++) {
                const int s = kb % K1_NST;
                mbar_wait(empty + 8 * s, 0);
                mbar_expect_tx(full + 8 * s, 16384 + K1_WS);
                tma_load_2d(sb + s * K1_ST, &tm_x, kb * 64, mt * 128, full + 8 * s);
                tma_load_3d(sb + s * K1_ST + K1_XS, &tm_w, nt * 64, kb * 64, 0, full + 8 * s);
            }
        }
        __syncwarp();
        if (lane < FF / 128) g_act[blockIdx.x * (FF / 128) + lane] = 0xFFFFFFFFu;
        for (int i = lane; i < 128; i += 32) g_part[blockIdx.x * 128 + i] = make_float4(0.f, 0.f, 0.f, 0.f);
        if (blockIdx.x == 1) { g_cand[lane] = make_uint4(0, 0, 0, 0); g_cand[lane + 32] = make_uint4(0, 0, 0, 0); g_hflag[lane] = 0; g_sflag[lane] = 0; }
        if (lane < 2) g_oflag[(blockIdx.x * 2 + lane) * 32] = 0;
    } else if (warp >= 12) {
        const int r = tid - 384;
        const unsigned int tag = *(volatile unsigned int*)&g_epoch + 1u;
        {
            const int row = mt * 128 + nt * 16 + (r >> 3);
            const uint4* xp = (const uint4*)(x + (size_t)row * DM) + (r & 7);
            uint4 v[8];
#pragma unroll
            for (int i = 0; i < 8; i++) v[i] = __ldg(xp + i * 8);
            float s1 = 0.f;
#pragma unroll
            for (int i = 0; i < 8; i++)
                s1 += ((bf_lo(v[i].x) + bf_hi(v[i].x)) + (bf_lo(v[i].y) + bf_hi(v[i].y))) + ((bf_lo(v[i].z) + bf_hi(v[i].z)) + (bf_lo(v[i].w) + bf_hi(v[i].w)));
#pragma unroll
            for (int o = 1; o < 8; o <<= 1) s1 += __shfl_xor_sync(0xffffffffu, s1, o);
            const float mean = s1 * (1.f / DM);
            float q0 = 0.f, q1 = 0.f;
#pragma unroll
            for (int i = 0; i < 8; i++) {
                const uint32_t w[4] = {v[i].x, v[i].y, v[i].z, v[i].w};
#pragma unroll
                for (int j = 0; j < 4; j++) {
                    const float a = bf_lo(w[j]) - mean, b = bf_hi(w[j]) - mean;
                    q0 = fmaf(a, a, q0); q1 = fmaf(b, b, q1);
                }
            }
            float q = q0 + q1;
#pragma unroll
            for (int o = 1; o < 8; o <<= 1) q += __shfl_xor_sync(0xffffffffu, q, o);
            const float den = rbf(sqrtf(rbf(rbf(q * (1.f / DM)) + 1e-5f)));
            if ((r & 7) == 0)
                asm volatile("st.relaxed.gpu.global.v4.f32 [%0], {%1, %2, %3, %4};" ::"l"(g_ln1 + row), "f"(rbf(mean)), "f"(1.f / den),
                             "f"(__uint_as_float(tag)), "f"(0.f) : "memory");
        }
        {
            float4 v;
            int spins = 0;
            do {
                asm volatile("ld.relaxed.gpu.global.v4.f32 {%0, %1, %2, %3}, [%4];" : "=f"(v.x), "=f"(v.y), "=f"(v.z), "=f"(v.w) : "l"(g_ln1 + mt * 128 + r) : "memory");
            } while (__float_as_uint(v.z) != tag && ++spins < (1 << 22));
            s_mr[(r >> 1) * 4 + (r & 1)] = v.x;
            s_mr[(r >> 1) * 4 + 2 + (r & 1)] = v.y;
        }
        named_arrive(1, 512);
    } else {
        const int part = warp >> 2, hw = warp & 3;
        float acc[68];
#pragma unroll
        for (int i = 0; i < 68; i++) acc[i] = 0.f;
        fence_regs(acc);
#pragma unroll 1
        for (int kb = 0; kb < 8; kb++) {
            const int s = kb % K1_NST;
            mbar_wait(full + 8 * s, (kb / K1_NST) & 1);
            const uint64_t da = make_desc(sb + s * K1_ST + K1_XS + part * 8192, 1024, 1024, 1);
            const uint64_t db = make_desc(sb + s * K1_ST, 16, 1024, 1);
            wg_fence();
#pragma unroll
            for (int k = 0; k < 4; k++) wgmma_k1_n136(acc, da + k * 128, db + k * 2, (kb | k) != 0);
            wg_commit();
            if (kb > 0 && kb <= 8 - K1_NST) {
                wg_wait<1>();
                if ((tid & 127) == 0) mbar_arrive(empty + 8 * (kb - 1));
            }
        }
        wg_wait<0>();
        fence_regs(acc);
        named_sync(1, 512);

        const int t = lane & 3;
        const float cs0 = acc[64], cs1 = acc[66];
        const float sc = (part == 0) ? QSCALE : 1.f;
        const uint32_t stg = sb + (hw >> 1) * K1_ST + K1_XS + part * 8192 + (hw & 1) * 4096;
        const uint32_t st_addr = stg + ((lane >> 3) & 1) * 2048 + ((lane >> 4) * 8 + (lane & 7)) * 16;
#pragma unroll
        for (int j = 0; j < 16; j += 2) {
            uint32_t rr[4];
#pragma unroll
            for (int u = 0; u < 2; u++) {
                const int jj = j + u;
                const float4 mr = *(const float4*)(s_mr + (4 * jj + t) * 4);
                const float2 m2 = make_float2(mr.x, mr.y);
                const float ra = mr.z * sc, rb = mr.w * sc;
                rr[2 * u] = pack_bf16((acc[4 * jj] - m2.x * cs0) * ra, (acc[4 * jj + 1] - m2.y * cs0) * rb);
                rr[2 * u + 1] = pack_bf16((acc[4 * jj + 2] - m2.x * cs1) * ra, (acc[4 * jj + 3] - m2.y * cs1) * rb);
            }
            stmatrix_x4_trans(st_addr + j * 128, rr[0], rr[1], rr[2], rr[3]);
        }
        fence_proxy_async();
        __syncwarp();
        const int head = nt * 4 + hw;
        if (lane == 0) {
            uint8_t* dst;
            uint32_t hstride;
            if (part == 0) { dst = g_q + (size_t)head * 65536 + mt * 2048; hstride = 32768; }
            else { dst = g_kv + (size_t)head * 131072 + (mt >> 1) * 16384 + (part - 1) * 8192 + (mt & 1) * 2048; hstride = 4096; }
            bulk_s2g(dst, stg, 2048);
            bulk_s2g(dst + hstride, stg + 2048, 2048);
            asm volatile("cp.async.bulk.commit_group;" ::: "memory");
        }
        float nmax = 0.f;
#pragma unroll
        for (int i = 0; i < 4; i++) {
            const int tok = lane + 32 * i;
            const uint4 a = *(const uint4*)(sp + (stg - sb) + tok * 16);
            const uint4 b = *(const uint4*)(sp + (stg - sb) + 2048 + tok * 16);
            uint32_t n0 = fma_bf16x2(a.x, a.x, 0u), n1 = fma_bf16x2(b.x, b.x, 0u);
            n0 = fma_bf16x2(a.y, a.y, n0); n1 = fma_bf16x2(b.y, b.y, n1);
            n0 = fma_bf16x2(a.z, a.z, n0); n1 = fma_bf16x2(b.z, b.z, n1);
            n0 = fma_bf16x2(a.w, a.w, n0); n1 = fma_bf16x2(b.w, b.w, n1);
            const float n2 = ((bf_lo(n0) + bf_hi(n0)) + (bf_lo(n1) + bf_hi(n1))) * 1.125f;
            nmax = (n2 > nmax || n2 != n2) ? n2 : nmax;
        }
#pragma unroll
        for (int o = 16; o > 0; o >>= 1) {
            const float v = __shfl_xor_sync(0xffffffffu, nmax, o);
            nmax = (v > nmax || v != v) ? v : nmax;
        }
        if (lane == 0) {
            g_norm[(head * 16 + mt) * 3 + part] = nmax;
            asm volatile("cp.async.bulk.wait_group.read 0;" ::: "memory");
        }
    }
}

#define POLL_NS 50
constexpr int KF_CH_G = 16384, KF_CH_S = 20480, KF_NCH = 8;
constexpr int KF_OFF_WO = KF_NCH * KF_CH_S;
constexpr int KF_OFF_MISC = -2048;
constexpr int KF_SMEM = 2048 + KF_OFF_WO + 65536 + 1024;

__device__ __forceinline__ uint32_t exp2_pair_poly(float t0, float t1, uint32_t c2) {
    const uint32_t w = __byte_perm(__float_as_uint(t0), __float_as_uint(t1), 0x5410);
    uint32_t z;
    asm("lop3.b32 %0, %1, %2, %3, 0xEA;" : "=r"(z) : "r"(w), "r"(0x007F007Fu), "r"(0x3F803F80u));
    uint32_t p = fma_bf16x2(c2, z, 0xbc73bc73u);
    p = fma_bf16x2(p, z, 0x3f2f3f2fu);
    return p + w - z;
}
#define NEA 40
#define NEB 40
#define BIAS_(n) wgmma_bias_n##n
#define BIAS(n) BIAS_(n)
template <int LO, int HI, int NE>
__device__ __forceinline__ void softmax_part(const float (&s)[32], uint32_t (&p)[16], uint32_t c2) {
#pragma unroll
    for (int i = LO; i < HI; i++) {
        if (i < NE / 4) p[i] = exp2_pair_poly(s[2 * i], s[2 * i + 1], c2);
        else p[i] = pack_bf16(ex2f(s[2 * i]), ex2f(s[2 * i + 1]));
    }
}
#define KF_PV(P, OFF)                                                                              \
    _Pragma("unroll") for (int kk = 0; kk < 4; kk++)                                               \
        wgmma_pv_n24(o, P[4 * kk], P[4 * kk + 1], P[4 * kk + 2], P[4 * kk + 3], dv + ((OFF) + kk * 16));

__device__ __forceinline__ uint32_t make_key(float r_bf16, int token) {
    const uint32_t u = __float_as_uint(r_bf16) >> 16;
    const uint32_t o = (u & 0x8000u) ? (~u & 0xFFFFu) : (u | 0x8000u);
    return (o << 16) | (uint32_t)(0xFFFF - token);
}
__device__ __forceinline__ float key_value(uint32_t k) {
    const uint32_t o = k >> 16;
    const uint32_t u = (o & 0x8000u) ? (o & 0x7FFFu) : (~o & 0xFFFFu);
    return __uint_as_float(u << 16);
}
__device__ __forceinline__ int key_token(uint32_t k) { return 0xFFFF - (int)(k & 0xFFFFu); }
__device__ __forceinline__ void warp_top2(uint32_t a, uint32_t b, uint32_t& k1, uint32_t& k2) {
    k1 = __reduce_max_sync(0xffffffffu, a > b ? a : b);
    const uint32_t a2 = (a == k1) ? 0u : a, b2 = (b == k1) ? 0u : b;
    k2 = __reduce_max_sync(0xffffffffu, a2 > b2 ? a2 : b2);
}
__device__ __forceinline__ unsigned int ld_acquire(const unsigned int* p) {
    unsigned int v; asm volatile("ld.acquire.gpu.global.u32 %0, [%1];" : "=r"(v) : "l"(p) : "memory"); return v;
}
__device__ __forceinline__ void red_release_add(unsigned int* p) {
    asm volatile("red.release.gpu.global.add.u32 [%0], 1;" ::"l"(p) : "memory");
}

__global__ void __launch_bounds__(512, 1)
kf_main(const __grid_constant__ CUtensorMap tm_o, const __grid_constant__ CUtensorMap tm_wo,
        const __grid_constant__ CUtensorMap tm_g, const __grid_constant__ CUtensorMap tm_u, const __grid_constant__ CUtensorMap tm_d,
        const __nv_bfloat16* __restrict__ x, const __nv_bfloat16* __restrict__ wo, const __nv_bfloat16* __restrict__ w_r,
        const __nv_bfloat16* __restrict__ w_gate, const __nv_bfloat16* __restrict__ w_up, const __nv_bfloat16* __restrict__ w_down,
        __nv_bfloat16* __restrict__ out) {
    extern __shared__ uint8_t smem_raw[];
    const uint32_t sraw = smem_u32(smem_raw);
    const uint32_t sb = ((sraw + 1023) & ~1023u) + 2048;
    uint8_t* sp = smem_raw + (sb - sraw);
    const uint32_t smisc = sb - 2048u;
    const uint32_t kvbar = smisc;
    const uint32_t wbar = kvbar + 64;
    const uint32_t obar = wbar + 64;
    const uint32_t gbar = obar + 64;
    const uint32_t dbar = gbar + 8;
    unsigned int* s_cnt = (unsigned int*)(sp + KF_OFF_MISC + 208);
    volatile unsigned int* s_order = (volatile unsigned int*)(sp + KF_OFF_MISC + 1056);
    uint32_t* s_key = (uint32_t*)(sp + KF_OFF_MISC + 256);
    float* s_gu = (float*)(sp + KF_OFF_WO + 49152 + 8192 + 4608);
    uint4* s_sel = (uint4*)(sp + KF_OFF_MISC + 1024);
    const int tid = threadIdx.x;
    const int head = blockIdx.x >> 2, quarter = blockIdx.x & 3;
    const int mt = blockIdx.x >> 2, nt = blockIdx.x & 3;
    if (tid == 0) {
        for (int c = 0; c < 26; c++) mbar_init(kvbar + 8 * c, 1);
        for (int c = 0; c < 6; c++) s_cnt[c] = 0;
        fence_barrier_init();
    }
    if (tid < 24) *(uint4*)(sp + KF_OFF_MISC + 1152 + tid * 16) =
        tid < 8 ? make_uint4(0x42FE4380u, 0x00003D80u, 0u, 0u) : (tid < 16 ? make_uint4(0x3F804380u, 0x00003DC0u, 0u, 0u) : make_uint4(0u, 0u, 0u, 0u));
    for (int i = tid; i < KF_NCH * 256; i += 512)
        *(uint4*)(sp + (i >> 8) * KF_CH_S + 16384 + (i & 255) * 16) =
            make_uint4(0x3F803F80u, 0x3F803F80u, 0x3F803F80u, 0x3F803F80u);
    fence_proxy_async();
    __syncthreads();
    pdl_wait();
    const uint8_t* kvsrc = g_kv + (size_t)head * (KF_NCH * KF_CH_G);
    if (tid == 32) {
        mbar_expect_tx(kvbar, KF_CH_G);
        bulk_g2s(sb, kvsrc, KF_CH_G, kvbar);
    }
    const int wg = tid >> 7, warp = (tid >> 5) & 3, lane = tid & 31, g = lane >> 2, t = lane & 3;
    if (tid < 32) {
        const int m16 = lane & 15;
        float kn = g_norm[(head * 16 + m16) * 3 + 1];
        float vn = g_norm[(head * 16 + m16) * 3 + 2];
        float qn = g_norm[(head * 16 + quarter * 4 + (lane & 3)) * 3 + 0];
        const bool bad = !(kn < 1e30f) || !(vn < 1e9f) || !(qn < 1e30f);
#pragma unroll
        for (int o = 8; o > 0; o >>= 1) {
            kn = fmaxf(kn, __shfl_xor_sync(0xffffffffu, kn, o));
            qn = fmaxf(qn, __shfl_xor_sync(0xffffffffu, qn, o));
        }
        const bool ok = __all_sync(0xffffffffu, !bad && (qn * kn <= 9000.f));
        if (lane == 0) s_cnt[4] = ok ? 1u : 0u;
    }
    uint32_t qn2[2][4];
#pragma unroll
    for (int ps = 0; ps < 2; ps++) {
        const uint8_t* qb = g_q + (size_t)head * 65536 + (quarter * 512 + ps * 256 + wg * 64 + warp * 16 + g) * 16 + t * 4;
        qn2[ps][0] = *(const uint32_t*)(qb);
        qn2[ps][1] = *(const uint32_t*)(qb + 128);
        qn2[ps][2] = *(const uint32_t*)(qb + 32768);
        qn2[ps][3] = *(const uint32_t*)(qb + 32768 + 128);
    }

    __syncthreads();
    const bool fast = __all_sync(0xffffffffu, s_cnt[4] != 0u);
    if (lane == 0) {
        const int w = tid >> 5;
        if (w < 7) {
            mbar_expect_tx(kvbar + 8 * (w + 1), KF_CH_G);
            bulk_g2s(sb + (w + 1) * KF_CH_S, kvsrc + (w + 1) * KF_CH_G, KF_CH_G, kvbar + 8 * (w + 1));
        } else if (w < 11) {
            mbar_expect_tx(wbar + 8 * (w - 7), 16384);
            tma_load_3d(sb + KF_OFF_WO + (w - 7) * 16384, &tm_wo, 0, (w - 7) * 64, nt * 2, wbar + 8 * (w - 7));
        } else if (w == 11) {
            prefetch_l2((const uint8_t*)wo + blockIdx.x * 4096, 4096);
        } else if (w < 15) {
            const uint8_t* wp = (const uint8_t*)(w == 12 ? w_gate : (w == 13 ? w_up : w_down));
            prefetch_l2(wp + blockIdx.x * 14336, 14336);
        }
    }
    __syncwarp();
    const uint64_t dbias_a = make_desc(smisc + 1152, 0, 0, 0);
    const uint64_t dbias_b = make_desc(smisc + 1280, 128, 0, 0);
    const uint32_t c2reg = 0x3eab3eabu;
    const uint64_t dk0 = make_desc(sb, 4096, 128, 0);
    const uint64_t dv0 = make_desc(sb + 8192, 128, 4096, 0);

#pragma unroll 1
    for (int pass = 0; pass < 2; pass++) {
        const int row0 = quarter * 512 + pass * 256 + wg * 64 + warp * 16 + g;
        uint32_t qa[4];
#pragma unroll
        for (int i = 0; i < 4; i++) qa[i] = pass ? qn2[1][i] : qn2[0][i];
        float o[12];
#pragma unroll
        for (int i = 0; i < 12; i++) o[i] = 0.f;
        fence_regs(o);
#define KF_RELEASE_CHUNK(c)                                                                          \
        if (pass == 1 && (c) >= 1 && (c) <= 4) {                                                     \
            named_sync(4 + wg, 128);            \
            if ((tid & 127) == 0 && atomicAdd(&s_cnt[(c) - 1], 1u) == 3u) {                          \
                mbar_expect_tx(wbar + 8 * (3 + (c)), 16384);                                         \
                tma_load_3d(sb + ((c) - 1) * KF_CH_S, &tm_wo, 0, (3 + (c)) * 64, nt * 2, wbar + 8 * (3 + (c))); \
            }                                                                                        \
        }
        if (fast) {
#pragma unroll 1
            for (int c = 0; c < KF_NCH; c++) {
                const uint64_t dk = dk0 + (uint64_t)(c * (KF_CH_S >> 4));
                const uint64_t dv = dv0 + (uint64_t)(c * (KF_CH_S >> 4));
                float s0[32], s1[32], s2[32], s3[32];
                uint32_t p0[16], p1[16], p2[16], p3[16];
                mbar_wait(kvbar + 8 * c, 0);
                wg_wait<1>();
                wg_fence();
                wgmma_qk_n64(s0, qa[0], qa[1], qa[2], qa[3], dk);
                BIAS(NEA)(s0, dbias_a, dbias_b);
                wg_commit();
                wg_wait<1>();
                KF_RELEASE_CHUNK(c);
                wg_fence();
                wgmma_qk_n64(s1, qa[0], qa[1], qa[2], qa[3], dk + 64);
                BIAS(NEB)(s1, dbias_a, dbias_b);
                wg_commit();
                wg_wait<1>();
                fence_regs(s0);
                softmax_part<0, 16, NEA>(s0, p0, c2reg);
                wg_fence();
                KF_PV(p0, 0);
                wg_commit();
                wg_wait<1>();
                fence_regs(s1);
                softmax_part<0, 8, NEB>(s1, p1, c2reg);
                wg_wait<0>();
                wg_fence();
                wgmma_qk_n64(s2, qa[0], qa[1], qa[2], qa[3], dk + 128);
                BIAS(NEA)(s2, dbias_a, dbias_b);
                wg_commit();
                softmax_part<8, 16, NEB>(s1, p1, c2reg);
                wg_fence();
                KF_PV(p1, 64);
                wg_commit();
                wg_wait<1>();
                fence_regs(s2);
                softmax_part<0, 8, NEA>(s2, p2, c2reg);
                wg_wait<0>();
                wg_fence();
                wgmma_qk_n64(s3, qa[0], qa[1], qa[2], qa[3], dk + 192);
                BIAS(NEB)(s3, dbias_a, dbias_b);
                wg_commit();
                softmax_part<8, 16, NEA>(s2, p2, c2reg);
                wg_fence();
                KF_PV(p2, 128);
                wg_commit();
                wg_wait<1>();
                fence_regs(s3);
                softmax_part<0, 16, NEB>(s3, p3, c2reg);
                wg_fence();
                KF_PV(p3, 192);
                wg_commit();
            }
            wg_wait<0>();
            fence_regs(o);
        } else {
            float m0 = -INFINITY, m1 = -INFINITY;
#pragma unroll 1
            for (int b = 0; b < 32; b++) {
                const int c = b >> 2;
                const uint64_t dk = dk0 + (uint64_t)(c * (KF_CH_S >> 4) + (b & 3) * 64);
                const uint64_t dv = dv0 + (uint64_t)(c * (KF_CH_S >> 4) + (b & 3) * 64);
                float s[32];
                uint32_t p[16];
                mbar_wait(kvbar + 8 * c, 0);
                wg_fence();
                wgmma_qk_n64(s, qa[0], qa[1], qa[2], qa[3], dk);
                wg_commit();
                if ((b & 3) == 0) { KF_RELEASE_CHUNK(c); }
                wg_wait<0>();
                fence_regs(s);
                float x0 = s[0], x1 = s[2];
#pragma unroll
                for (int j = 0; j < 8; j++) {
                    x0 = fmaxf(x0, fmaxf(s[4 * j], s[4 * j + 1]));
                    x1 = fmaxf(x1, fmaxf(s[4 * j + 2], s[4 * j + 3]));
                }
                x0 = fmaxf(x0, __shfl_xor_sync(0xffffffffu, x0, 1));
                x0 = fmaxf(x0, __shfl_xor_sync(0xffffffffu, x0, 2));
                x1 = fmaxf(x1, __shfl_xor_sync(0xffffffffu, x1, 1));
                x1 = fmaxf(x1, __shfl_xor_sync(0xffffffffu, x1, 2));
                const float n0 = fmaxf(m0, x0), n1 = fmaxf(m1, x1);
                const float c0 = ex2f(m0 - n0), c1 = ex2f(m1 - n1);
                m0 = n0; m1 = n1;
#pragma unroll
                for (int j = 0; j < 3; j++) {
                    o[4 * j] *= c0; o[4 * j + 1] *= c0; o[4 * j + 2] *= c1; o[4 * j + 3] *= c1;
                }
#pragma unroll
                for (int j = 0; j < 8; j++) {
                    p[2 * j] = pack_bf16(ex2f(s[4 * j] - n0), ex2f(s[4 * j + 1] - n0));
                    p[2 * j + 1] = pack_bf16(ex2f(s[4 * j + 2] - n1), ex2f(s[4 * j + 3] - n1));
                }
                fence_regs(o);
                wg_fence();
                KF_PV(p, 0);
                wg_commit();
                wg_wait<0>();
                fence_regs(o);
            }
        }
        const float inv0 = 1.f / o[8], inv1 = 1.f / o[10];
        {
            uint32_t v0 = pack_bf16(o[0] * inv0, o[1] * inv0), v1 = pack_bf16(o[4] * inv0, o[5] * inv0);
            uint32_t v2 = pack_bf16(o[2] * inv1, o[3] * inv1), v3 = pack_bf16(o[6] * inv1, o[7] * inv1);
            const bool o1 = t & 1, o2 = t & 2;
            uint32_t s0 = o1 ? v0 : v1, s1 = o1 ? v2 : v3;
            s0 = __shfl_xor_sync(0xffffffffu, s0, 1); s1 = __shfl_xor_sync(0xffffffffu, s1, 1);
            uint32_t a0 = o1 ? s0 : v0, a1 = o1 ? v1 : s0, b0 = o1 ? s1 : v2, b1 = o1 ? v3 : s1;
            uint32_t x0 = o2 ? a0 : b0, x1 = o2 ? a1 : b1;
            x0 = __shfl_xor_sync(0xffffffffu, x0, 2); x1 = __shfl_xor_sync(0xffffffffu, x1, 2);
            uint4 r;
            r.x = o2 ? x0 : a0; r.y = o2 ? x1 : a1; r.z = o2 ? b0 : x0; r.w = o2 ? b1 : x1;
            *(uint4*)(g_o + (size_t)(row0 + (t >> 1) * 8) * DM + head * 16 + (t & 1) * 8) = r;
        }
    }
    if ((tid >> 5) != 10) named_arrive(1, 512);
    named_sync(4 + wg, 128);
    if ((tid & 127) == 0) {
        asm volatile("fence.acq_rel.gpu;" ::: "memory");
        asm volatile("red.relaxed.gpu.global.add.u32 [%0], 1;" ::"l"(&g_oflag[((quarter * 8 + 4 + wg) * 8 + (head >> 2)) * 32]) : "memory");
        asm volatile("red.relaxed.gpu.global.add.u32 [%0], 1;" ::"l"(&g_oflag[((quarter * 8 + wg) * 8 + (head >> 2)) * 32]) : "memory");
    }

    if (wg < 2) {
        const int wi = warp;
        const int r0 = mt * 64 + wi * 16 + g;
        const int cb = nt * 128 + wg * 64;
        uint32_t xr[16], wr[8];
#pragma unroll
        for (int j = 0; j < 8; j++) {
            xr[2 * j] = __ldg((const uint32_t*)(x + (size_t)r0 * DM + cb + 8 * j + 2 * t));
            xr[2 * j + 1] = __ldg((const uint32_t*)(x + (size_t)(r0 + 8) * DM + cb + 8 * j + 2 * t));
            wr[j] = __ldg((const uint32_t*)(w_r + cb + 8 * j + 2 * t));
        }
        float wsum = 0.f;
        {
            const uint4 a = __ldg((const uint4*)(w_r + lane * 16)), b = __ldg((const uint4*)(w_r + lane * 16 + 8));
            const uint32_t w[8] = {a.x, a.y, a.z, a.w, b.x, b.y, b.z, b.w};
#pragma unroll
            for (int i = 0; i < 8; i++) wsum += bf_lo(w[i]) + bf_hi(w[i]);
#pragma unroll
            for (int o = 16; o > 0; o >>= 1) wsum += __shfl_xor_sync(0xffffffffu, wsum, o);
        }
        float acc[32];
#pragma unroll
        for (int i = 0; i < 32; i++) acc[i] = 0.f;
        fence_regs(acc);
#pragma unroll 1
        for (int i = 0; i < 8; i++) {
            mbar_wait(obar + 8 * i, 0);
            const int kb = __shfl_sync(0xffffffffu, (int)s_order[i], 0);
            mbar_wait(wbar + 8 * kb, 0);
            const uint32_t wa = (kb < 4) ? (KF_OFF_WO + kb * 16384) : ((kb - 4) * KF_CH_S);
            const uint64_t da = make_desc(sb + (4 + (kb >> 1)) * KF_CH_S + (kb & 1) * 8192, 16, 1024, 1);
            const uint64_t db = make_desc(sb + wa + wg * 8192, 1024, 1024, 1);
            wg_fence();
#pragma unroll
            for (int k = 0; k < 4; k++) wgmma_k3_n64(acc, da + k * 2, db + k * 128, (i | k) != 0);
            wg_commit();
        }
        wg_wait<0>();
        fence_regs(acc);
        float hv[32];
        uint32_t hp[16];
        float s0 = 0.f, s1 = 0.f, d0 = 0.f, d1 = 0.f;
#pragma unroll
        for (int j = 0; j < 8; j++) {
            const uint32_t a01 = pack_bf16(acc[4 * j], acc[4 * j + 1]), a23 = pack_bf16(acc[4 * j + 2], acc[4 * j + 3]);
            hp[2 * j] = pack_bf16(bf_lo(xr[2 * j]) + bf_lo(a01), bf_hi(xr[2 * j]) + bf_hi(a01));
            hp[2 * j + 1] = pack_bf16(bf_lo(xr[2 * j + 1]) + bf_lo(a23), bf_hi(xr[2 * j + 1]) + bf_hi(a23));
            hv[4 * j] = bf_lo(hp[2 * j]); hv[4 * j + 1] = bf_hi(hp[2 * j]);
            hv[4 * j + 2] = bf_lo(hp[2 * j + 1]); hv[4 * j + 3] = bf_hi(hp[2 * j + 1]);
            const float wl = bf_lo(wr[j]), wh = bf_hi(wr[j]);
            s0 += hv[4 * j] + hv[4 * j + 1];
            s1 += hv[4 * j + 2] + hv[4 * j + 3];
            d0 = fmaf(hv[4 * j], wl, fmaf(hv[4 * j + 1], wh, d0));
            d1 = fmaf(hv[4 * j + 2], wl, fmaf(hv[4 * j + 3], wh, d1));
        }
        float mu0 = s0 * (1.f / 16), mu1 = s1 * (1.f / 16);
        float q0 = 0.f, q1 = 0.f;
#pragma unroll
        for (int j = 0; j < 8; j++) {
            float a = hv[4 * j] - mu0, b = hv[4 * j + 1] - mu0, c = hv[4 * j + 2] - mu1, d = hv[4 * j + 3] - mu1;
            q0 = fmaf(a, a, fmaf(b, b, q0));
            q1 = fmaf(c, c, fmaf(d, d, q1));
        }
#pragma unroll
        for (int o = 1; o < 4; o <<= 1) {
            const float m0 = __shfl_xor_sync(0xffffffffu, mu0, o), m1 = __shfl_xor_sync(0xffffffffu, mu1, o);
            const float e0 = __shfl_xor_sync(0xffffffffu, q0, o), e1 = __shfl_xor_sync(0xffffffffu, q1, o);
            d0 += __shfl_xor_sync(0xffffffffu, d0, o);
            d1 += __shfl_xor_sync(0xffffffffu, d1, o);
            const float f0 = mu0 - m0, f1 = mu1 - m1;
            q0 = q0 + e0 + f0 * f0 * (8.f * o);
            q1 = q1 + e1 + f1 * f1 * (8.f * o);
            mu0 = 0.5f * (mu0 + m0); mu1 = 0.5f * (mu1 + m1);
        }
        float4* part = g_part + (size_t)mt * 512 + wi * 16 + g;
        if (t < 2) {
            float4* dst = part + (nt * 2 + wg) * 64 + t * 8;
            const float a = t ? mu1 : mu0, b = t ? q1 : q0, c = t ? d1 : d0;
            asm volatile("st.relaxed.gpu.global.v4.f32 [%0], {%1, %2, %3, %4};" ::"l"(dst), "f"(a), "f"(b), "f"(c), "f"(1.0f) : "memory");
        }
        const uint32_t stg_off = KF_OFF_WO + (wi >> 1) * 16384 + wg * 8192 + (wi & 1) * 4096;
        const uint32_t stg_o = sb + stg_off, stg_h = stg_o + 2048;
        const int srow = (lane & 7) + ((lane >> 3) & 1) * 8;
        const int sj = lane >> 4;
        named_sync(4 + wg, 128);
#pragma unroll
        for (int j = 0; j < 8; j += 2) {
            const uint32_t off = srow * 128 + (((j + sj) ^ (srow & 7)) << 4);
            stmatrix_x4(stg_h + off, hp[2 * j], hp[2 * j + 1], hp[2 * j + 2], hp[2 * j + 3]);
        }
        __syncwarp();
#pragma unroll
        for (int i = 0; i < 4; i++) {
            const int row = i * 4 + (lane >> 3), ch = lane & 7;
            const uint4 vh = *(const uint4*)(sp + stg_off + 2048 + row * 128 + ((ch ^ (row & 7)) << 4));
            *(uint4*)(g_h + (size_t)(mt * 64 + wi * 16 + row) * DM + cb + ch * 8) = vh;
        }
        named_arrive(8, 288);
        float mean[2], den[2], rr[2];
        {
            float4 v[4];
            int spins = 0;
            while (true) {
#pragma unroll
                for (int i = 0; i < 4; i++) {
                    const float4* p = part + (t + (i & 1) * 4) * 64 + (i >> 1) * 8;
                    asm volatile("ld.relaxed.gpu.global.v4.f32 {%0, %1, %2, %3}, [%4];" : "=f"(v[i].x), "=f"(v[i].y), "=f"(v[i].z), "=f"(v[i].w) : "l"(p) : "memory");
                }
                const bool ok = (v[0].w != 0.f) && (v[1].w != 0.f) && (v[2].w != 0.f) && (v[3].w != 0.f);
                if (__all_sync(0xffffffffu, ok) || ++spins > (1 << 22)) break;
            }
#pragma unroll
            for (int u = 0; u < 2; u++) {
                float mu = v[2 * u].x + v[2 * u + 1].x, m2 = v[2 * u].y + v[2 * u + 1].y, hw = v[2 * u].z + v[2 * u + 1].z;
#pragma unroll
                for (int o = 1; o < 4; o <<= 1) {
                    mu += __shfl_xor_sync(0xffffffffu, mu, o);
                    m2 += __shfl_xor_sync(0xffffffffu, m2, o);
                    hw += __shfl_xor_sync(0xffffffffu, hw, o);
                }
                mu *= 0.125f;
                const float da = v[2 * u].x - mu, db = v[2 * u + 1].x - mu;
                float dd = 64.f * (da * da + db * db);
#pragma unroll
                for (int o = 1; o < 4; o <<= 1) dd += __shfl_xor_sync(0xffffffffu, dd, o);
                m2 += dd;
                mean[u] = rbf(mu);
                den[u] = rbf(sqrtf(rbf(rbf(m2 * (1.f / DM)) + 1e-5f)));
                rr[u] = rbf((hw - mean[u] * wsum) / den[u]);
            }
        }
        named_arrive(3, 512);
        if (nt == 0 && wg == 0) {
            float2* s_st = (float2*)(sp + KF_OFF_WO + 49152);
            if (t == 0) {
                s_key[wi * 16 + g] = make_key(rr[0], r0);
                s_key[wi * 16 + g + 8] = make_key(rr[1], r0 + 8);
                s_st[wi * 16 + g] = make_float2(mean[0], den[0]);
                s_st[wi * 16 + g + 8] = make_float2(mean[1], den[1]);
            }
            named_sync(4, 128);
            if (warp == 0) {
                uint32_t k1, k2;
                warp_top2(s_key[lane], s_key[lane + 32], k1, k2);
                if (lane < 2) {
                    const uint32_t k = lane ? k2 : k1;
                    const float2 st = s_st[key_token(k) & 63];
                    asm volatile("st.relaxed.gpu.global.v4.u32 [%0], {%1, %2, %3, %4};" ::"l"(g_cand + mt * 2 + lane), "r"(k),
                                 "r"(1u), "r"(__float_as_uint(st.x)), "r"(__float_as_uint(st.y)) : "memory");
                }
            }
        }
        const float i0 = 1.f / den[0], i1 = 1.f / den[1];
#pragma unroll
        for (int j = 0; j < 8; j += 2) {
            uint32_t ro[4];
#pragma unroll
            for (int u = 0; u < 2; u++) {
                const int jj = j + u;
                const float a = hv[4 * jj], b = hv[4 * jj + 1], c = hv[4 * jj + 2], d = hv[4 * jj + 3];
                const uint32_t u01 = pack_bf16(a - mean[0], b - mean[0]), u23 = pack_bf16(c - mean[1], d - mean[1]);
                const uint32_t n01 = pack_bf16(bf_lo(u01) * i0, bf_hi(u01) * i0), n23 = pack_bf16(bf_lo(u23) * i1, bf_hi(u23) * i1);
                ro[2 * u] = pack_bf16(a + bf_lo(n01), b + bf_hi(n01));
                ro[2 * u + 1] = pack_bf16(c + bf_lo(n23), d + bf_hi(n23));
            }
            const uint32_t off = srow * 128 + (((j + sj) ^ (srow & 7)) << 4);
            stmatrix_x4(stg_o + off, ro[0], ro[1], ro[2], ro[3]);
        }
        __syncwarp();
#pragma unroll
        for (int i = 0; i < 4; i++) {
            const int row = i * 4 + (lane >> 3), ch = lane & 7;
            const uint4 vo = *(const uint4*)(sp + stg_off + row * 128 + ((ch ^ (row & 7)) << 4));
            *(uint4*)(out + (size_t)(mt * 64 + wi * 16 + row) * DM + cb + ch * 8) = vo;
        }
        named_sync(4 + wg, 128);
        if ((tid & 127) == 0) red_release_add(&g_sflag[mt]);
    } else {
        const bool worker = blockIdx.x < FF / 16;
        const bool downer = blockIdx.x >= 64;
        const int mtid = tid - 256, mwarp = mtid >> 5;
        const int c0 = (blockIdx.x - 64) * 8;
        float* s_x = (float*)(sp + KF_OFF_WO + 49152 + 8192);
        float* s_red = (float*)(sp + KF_OFF_WO + 49152 + 8192 + 4096);
        if (mwarp == 2) {
            named_sync(1, 512);
            uint32_t done = 0;
            int n = 0, spins = 0;
            while (done != 0xFFu && ++spins < (1 << 22)) {
                const bool rdy = lane < 8 && ld_acquire(&g_oflag[(mt * 8 + lane) * 32]) >= 4u;
                uint32_t todo = __ballot_sync(0xffffffffu, rdy) & ~done;
                done |= todo;
                if (todo && lane == 0) {
                    asm volatile("fence.proxy.async.global;" ::: "memory");
                    while (todo) {
                        const int kb = __ffs(todo) - 1;
                        todo &= todo - 1;
                        s_order[n] = kb;
                        mbar_expect_tx(obar + 8 * n, 8192);
                        tma_load_3d(sb + (4 + (kb >> 1)) * KF_CH_S + (kb & 1) * 8192, &tm_o, 0, mt * 64, kb, obar + 8 * n);
                        n++;
                    }
                }
                n = __shfl_sync(0xffffffffu, n, 0);
                if (done != 0xFFu) __nanosleep(POLL_NS);
            }
            if (lane == 0 && worker) {
                mbar_expect_tx(gbar, 32768);
                for (int i = 0; i < 4; i++) {
                    tma_load_2d(sb + i * KF_CH_S + 16384, &tm_g, blockIdx.x * 16, i * 128, gbar);
                    tma_load_2d(sb + (4 + i) * KF_CH_S + 16384, &tm_u, blockIdx.x * 16, i * 128, gbar);
                }
            }
        }
        if (mwarp == 1) {
            named_sync(8, 288);
            if (lane == 0) {
                red_release_add(&g_hflag[mt]);
                if (downer) {
                    mbar_expect_tx(dbar, 7 * 4096);
                    for (int i = 0; i < 7; i++) tma_load_2d(sb + (4 + (i >> 2)) * KF_CH_S + (i & 3) * 4096, &tm_d, c0, i * 256, dbar);
                }
            }
            __syncwarp();
        }
        named_sync(3, 512);
        if (mwarp == 0) {
            uint4 ca, cb4;
            int spins = 0;
            while (true) {
                asm volatile("ld.relaxed.gpu.global.v4.u32 {%0, %1, %2, %3}, [%4];" : "=r"(ca.x), "=r"(ca.y), "=r"(ca.z), "=r"(ca.w) : "l"(g_cand + 2 * lane) : "memory");
                asm volatile("ld.relaxed.gpu.global.v4.u32 {%0, %1, %2, %3}, [%4];" : "=r"(cb4.x), "=r"(cb4.y), "=r"(cb4.z), "=r"(cb4.w) : "l"(g_cand + 2 * lane + 1) : "memory");
                const unsigned int hf = ld_acquire(&g_hflag[lane]);
                const bool ok = ca.y != 0 && cb4.y != 0 && hf >= 4u;
                if (__all_sync(0xffffffffu, ok) || ++spins > (1 << 22)) break;
            }
            uint32_t k1, k2;
            warp_top2(ca.x, cb4.x, k1, k2);
            if (ca.x == k1) s_sel[0] = ca;
            if (cb4.x == k1) s_sel[0] = cb4;
            if (ca.x == k2) s_sel[1] = ca;
            if (cb4.x == k2) s_sel[1] = cb4;
        }
        named_sync(2, 256);
        int idx[2];
        float mean[2], inv[2], rv[2];
#pragma unroll
        for (int u = 0; u < 2; u++) {
            const uint4 c = s_sel[u];
            idx[u] = key_token(c.x);
            rv[u] = key_value(c.x);
            mean[u] = __uint_as_float(c.z);
            inv[u] = 1.f / __uint_as_float(c.w);
        }
        float hfin = 0.f;
        if (downer && mtid < 16) hfin = __bfloat162float(__ldcg((const __nv_bfloat16*)(g_h + (size_t)((mtid >> 3) ? idx[1] : idx[0]) * DM + c0 + (mtid & 7))));
        if (worker) {
            {
                const uint32_t h0 = __ldcg((const uint32_t*)(g_h + (size_t)idx[0] * DM + 2 * mtid));
                const uint32_t h1 = __ldcg((const uint32_t*)(g_h + (size_t)idx[1] * DM + 2 * mtid));
                const uint32_t u0 = pack_bf16(bf_lo(h0) - mean[0], bf_hi(h0) - mean[0]), u1 = pack_bf16(bf_lo(h1) - mean[1], bf_hi(h1) - mean[1]);
                const uint32_t n0 = pack_bf16(bf_lo(u0) * inv[0], bf_hi(u0) * inv[0]), n1 = pack_bf16(bf_lo(u1) * inv[1], bf_hi(u1) * inv[1]);
                *(float4*)(s_x + 4 * mtid) = make_float4(bf_lo(n0), bf_lo(n1), bf_hi(n0), bf_hi(n1));
            }
            mbar_wait(gbar, 0);
            named_sync(2, 256);
            float acc[16];
#pragma unroll
            for (int i = 0; i < 16; i++) acc[i] = 0.f;
            const uint8_t* wbase = sp + ((mwarp >> 2) * 4 + (mwarp & 3)) * KF_CH_S + 16384 + lane * 16;
            const float* xb = s_x + 2 * (128 * (mwarp & 3) + (lane >> 1));
#pragma unroll
            for (int j = 0; j < 8; j++) {
                const uint4 w = *(const uint4*)(wbase + j * 512);
                const float2 xx = *(const float2*)(xb + 32 * j);
                const uint32_t ww[4] = {w.x, w.y, w.z, w.w};
#pragma unroll
                for (int q = 0; q < 4; q++) {
                    const float wl = bf_lo(ww[q]), wh = bf_hi(ww[q]);
                    acc[2 * q] = fmaf(xx.x, wl, acc[2 * q]); acc[2 * q + 1] = fmaf(xx.x, wh, acc[2 * q + 1]);
                    acc[8 + 2 * q] = fmaf(xx.y, wl, acc[8 + 2 * q]); acc[8 + 2 * q + 1] = fmaf(xx.y, wh, acc[8 + 2 * q + 1]);
                }
            }
#define KF_STEP(O, N)                                                          \
            {                                                                  \
                const bool up = (lane & (O)) != 0;                             \
                _Pragma("unroll") for (int i = 0; i < (N); i++) {              \
                    const float send = up ? acc[i] : acc[i + (N)];             \
                    const float keep = up ? acc[i + (N)] : acc[i];             \
                    acc[i] = keep + __shfl_xor_sync(0xffffffffu, send, (O));   \
                }                                                              \
            }
            KF_STEP(16, 8) KF_STEP(8, 4) KF_STEP(4, 2) KF_STEP(2, 1)
            {
                const int v = ((lane & 16) ? 8 : 0) + ((lane & 8) ? 4 : 0) + ((lane & 4) ? 2 : 0) + ((lane & 2) ? 1 : 0);
                s_gu[mwarp * 32 + (v >> 3) * 16 + (lane & 1) * 8 + (v & 7)] = acc[0];
            }
            named_sync(2, 256);
            if (mtid < 16) {
                uint32_t a2 = 0;
#pragma unroll
                for (int u = 0; u < 2; u++) {
                    const float* pg = s_gu + u * 16 + mtid;
                    const float gb = rbf((pg[0] + pg[32]) + (pg[64] + pg[96]));
                    const float ub = rbf((pg[128] + pg[160]) + (pg[192] + pg[224]));
                    const float sg = rbf(gb / (1.f + __expf(-gb)));
                    const float a = sg * ub;
                    uint32_t ab = (uint32_t)__bfloat16_as_ushort(__float2bfloat16_rn(a));
                    if (ab == 0xFFFFu) ab = 0x7FFFu;
                    a2 |= ab << (16 * u);
                }
                asm volatile("st.relaxed.gpu.global.u32 [%0], %1;" ::"l"(g_act + blockIdx.x * 16 + mtid), "r"(a2) : "memory");
            }
        }
        if (downer) {
            uint32_t av[7];
            {
                int spins = 0;
                while (true) {
                    bool ok = true;
#pragma unroll
                    for (int j = 0; j < 7; j++) {
                        asm volatile("ld.relaxed.gpu.global.u32 %0, [%1];" : "=r"(av[j]) : "l"(g_act + mtid + 256 * j) : "memory");
                        ok = ok && ((av[j] & 0xFFFFu) != 0xFFFFu) && ((av[j] >> 16) != 0xFFFFu);
                    }
                    if (mtid < 2) ok = ok && (ld_acquire(&g_sflag[(mtid ? idx[1] : idx[0]) >> 6]) >= 8u);
                    if (__all_sync(0xffffffffu, ok) || ++spins > (1 << 20)) break;
                    __nanosleep(20);
                }
            }
            mbar_wait(dbar, 0);
            float acc[16];
#pragma unroll
            for (int i = 0; i < 16; i++) acc[i] = 0.f;
#pragma unroll
            for (int j = 0; j < 7; j++) {
                const uint4 w = *(const uint4*)(sp + (4 + (j >> 2)) * KF_CH_S + (j & 3) * 4096 + mtid * 16);
                const float a0 = bf_lo(av[j]), a1 = bf_hi(av[j]);
                const uint32_t ww[4] = {w.x, w.y, w.z, w.w};
#pragma unroll
                for (int q = 0; q < 4; q++) {
                    const float wl = bf_lo(ww[q]), wh = bf_hi(ww[q]);
                    acc[2 * q] = fmaf(a0, wl, acc[2 * q]); acc[2 * q + 1] = fmaf(a0, wh, acc[2 * q + 1]);
                    acc[8 + 2 * q] = fmaf(a1, wl, acc[8 + 2 * q]); acc[8 + 2 * q + 1] = fmaf(a1, wh, acc[8 + 2 * q + 1]);
                }
            }
            KF_STEP(16, 8) KF_STEP(8, 4) KF_STEP(4, 2) KF_STEP(2, 1)
            acc[0] += __shfl_xor_sync(0xffffffffu, acc[0], 1);
            if ((lane & 1) == 0) {
                const int v = ((lane & 16) ? 8 : 0) + ((lane & 8) ? 4 : 0) + ((lane & 4) ? 2 : 0) + ((lane & 2) ? 1 : 0);
                s_red[mwarp * 16 + v] = acc[0];
            }
            named_sync(2, 256);
            if (mtid < 16) {
                const int u = mtid >> 3;
                float y = 0.f;
#pragma unroll
                for (int w = 0; w < 8; w++) y += s_red[w * 16 + mtid];
                const float sig = rbf(1.f / (1.f + __expf(-(u ? rv[1] : rv[0]))));
                const float xn = rbf(rbf(hfin - (u ? mean[1] : mean[0])) * (u ? inv[1] : inv[0]));
                const float ov = hfin + rbf(xn + rbf(rbf(y) * sig));
                out[(size_t)(u ? idx[1] : idx[0]) * DM + c0 + (mtid & 7)] = __float2bfloat16_rn(ov);
            }
            if (blockIdx.x == gridDim.x - 1 && mtid == 0) g_epoch = g_epoch + 1u;
        }
    }
}

typedef CUresult (*PFN_encodeTiled)(CUtensorMap*, CUtensorMapDataType, cuuint32_t, void*, const cuuint64_t*, const cuuint64_t*,
                                    const cuuint32_t*, const cuuint32_t*, CUtensorMapInterleave, CUtensorMapSwizzle,
                                    CUtensorMapL2promotion, CUtensorMapFloatOOBfill);

void make_map(PFN_encodeTiled enc, CUtensorMap* m, const void* ptr, uint64_t cols, uint64_t rows, uint32_t bcols, uint32_t brows) {
    cuuint64_t dims[2] = {cols, rows};
    cuuint64_t strides[1] = {cols * 2};
    cuuint32_t box[2] = {bcols, brows};
    cuuint32_t es[2] = {1, 1};
    enc(m, CU_TENSOR_MAP_DATA_TYPE_BFLOAT16, 2, const_cast<void*>(ptr), dims, strides, box, es, CU_TENSOR_MAP_INTERLEAVE_NONE,
        CU_TENSOR_MAP_SWIZZLE_128B, CU_TENSOR_MAP_L2_PROMOTION_L2_256B, CU_TENSOR_MAP_FLOAT_OOB_FILL_NONE);
}

void make_map3(PFN_encodeTiled enc, CUtensorMap* m, const void* ptr, uint64_t d0, uint64_t rows, uint64_t d2, uint64_t row_stride_bytes,
               uint64_t d2_stride_bytes, uint32_t b0, uint32_t b1, uint32_t b2) {
    cuuint64_t dims[3] = {d0, rows, d2};
    cuuint64_t strides[2] = {row_stride_bytes, d2_stride_bytes};
    cuuint32_t box[3] = {b0, b1, b2};
    cuuint32_t es[3] = {1, 1, 1};
    enc(m, CU_TENSOR_MAP_DATA_TYPE_BFLOAT16, 3, const_cast<void*>(ptr), dims, strides, box, es, CU_TENSOR_MAP_INTERLEAVE_NONE,
        CU_TENSOR_MAP_SWIZZLE_128B, CU_TENSOR_MAP_L2_PROMOTION_L2_256B, CU_TENSOR_MAP_FLOAT_OOB_FILL_NONE);
}

void make_map_plain(PFN_encodeTiled enc, CUtensorMap* m, const void* ptr, uint64_t cols, uint64_t rows, uint32_t bcols, uint32_t brows) {
    cuuint64_t dims[2] = {cols, rows};
    cuuint64_t strides[1] = {cols * 2};
    cuuint32_t box[2] = {bcols, brows};
    cuuint32_t es[2] = {1, 1};
    enc(m, CU_TENSOR_MAP_DATA_TYPE_BFLOAT16, 2, const_cast<void*>(ptr), dims, strides, box, es, CU_TENSOR_MAP_INTERLEAVE_NONE,
        CU_TENSOR_MAP_SWIZZLE_NONE, CU_TENSOR_MAP_L2_PROMOTION_NONE, CU_TENSOR_MAP_FLOAT_OOB_FILL_NONE);
}

template <typename... KArgs, typename... Args>
void launch(void (*kern)(KArgs...), int grid, int block, int smem, bool pdl, Args... args) {
    cudaLaunchConfig_t cfg = {};
    cfg.gridDim = dim3(grid);
    cfg.blockDim = dim3(block);
    cfg.dynamicSmemBytes = smem;
    cfg.stream = cudaStreamPerThread;
    cudaLaunchAttribute at[1];
    at[0].id = cudaLaunchAttributeProgrammaticStreamSerialization;
    at[0].val.programmaticStreamSerializationAllowed = 1;
    cfg.attrs = at;
    cfg.numAttrs = pdl ? 1 : 0;
    cudaLaunchKernelEx(&cfg, kern, KArgs(args)...);
}

}

extern "C" void kernel_launch(void* const* d_in, const int* in_sizes, int n_in, void* d_out, int out_size) {
    const __nv_bfloat16* x = (const __nv_bfloat16*)d_in[0];
    const __nv_bfloat16* wqkv = (const __nv_bfloat16*)d_in[1];
    const __nv_bfloat16* wo = (const __nv_bfloat16*)d_in[2];
    const __nv_bfloat16* w_r = (const __nv_bfloat16*)d_in[4];
    const __nv_bfloat16* w_gate = (const __nv_bfloat16*)d_in[5];
    const __nv_bfloat16* w_up = (const __nv_bfloat16*)d_in[6];
    const __nv_bfloat16* w_down = (const __nv_bfloat16*)d_in[7];
    __nv_bfloat16* out = (__nv_bfloat16*)d_out;

    static PFN_encodeTiled enc = nullptr;
    static void* g_o_ptr = nullptr;
    if (!enc) {
        cudaDriverEntryPointQueryResult qres;
        void* fn = nullptr;
        cudaGetDriverEntryPoint("cuTensorMapEncodeTiled", &fn, cudaEnableDefault, &qres);
        enc = (PFN_encodeTiled)fn;
        cudaGetSymbolAddress(&g_o_ptr, g_o);
        cudaFuncSetAttribute(k1_qkv, cudaFuncAttributeMaxDynamicSharedMemorySize, K1_SMEM);
        cudaFuncSetAttribute(kf_main, cudaFuncAttributeMaxDynamicSharedMemorySize, KF_SMEM);
    }
    CUtensorMap tm_x, tm_w, tm_o, tm_wo, tm_g, tm_u, tm_d;
    make_map_plain(enc, &tm_d, w_down, DM, FF, 8, 256);
    make_map_plain(enc, &tm_g, w_gate, FF, DM, 16, 128);
    make_map_plain(enc, &tm_u, w_up, FF, DM, 16, 128);
    make_map(enc, &tm_x, x, DM, SEQ, 64, 128);
    make_map3(enc, &tm_w, wqkv, DM, DM, 3, 3 * DM * 2, DM * 2, 64, 64, 3);
    make_map3(enc, &tm_o, g_o_ptr, 64, SEQ, 8, DM * 2, 128, 64, 64, 1);
    make_map3(enc, &tm_wo, wo, 64, DM, 8, DM * 2, 128, 64, 64, 2);

    const bool pdl = true;
    launch(k1_qkv, 128, 544, K1_SMEM, false, tm_x, tm_w, x);
    launch(kf_main, 128, 512, KF_SMEM, pdl, tm_o, tm_wo, tm_g, tm_u, tm_d, x, wo, w_r, w_gate, w_up, w_down, out);
}
```
